```python
import torch

def _softmax(x, axis=-1):
    return torch.softmax(x, dim=axis)

def _gelu(x):
    return torch.nn.functional.gelu(x, approximate='tanh')

def _silu(x):
    return torch.nn.functional.silu(x)

def _sigmoid(x):
    return torch.sigmoid(x)

def _layernorm(x, axis=-1, eps=1e-05):
    m = x.mean(dim=axis, keepdim=True)
    v = x.var(dim=axis, keepdim=True, unbiased=False)
    return (x - m) / torch.sqrt(v + eps)

def _scatter_add(tgt, idx, src, axis=0):
    return tgt.clone().index_add_(axis, idx, src)

def _segment_sum(src, seg, n):
    out = torch.zeros((n,) + src.shape[1:], dtype=src.dtype)
    return out.index_add_(0, seg, src)

def _pad(x, pw):
    flat = tuple((v for pair in reversed(pw) for v in pair))
    return torch.nn.functional.pad(x, flat)
kernel_name = 'adaLN_cond__mha_block__glu_gated_swiglu__prompt'

def setup_inputs():

    _w = lambda a: (lambda t: t.to(torch.bfloat16) if t.is_floating_point() else t)(torch.as_tensor(a))

    def _A_setup():
        B, S, D, H = (1, 2048, 512, 32)
        return {'x': _w((lambda *s: torch.randn(*s, dtype=torch.bfloat16) * 0.05)(B, S, D)), 'wqkv': _w((lambda *s: torch.randn(*s, dtype=torch.bfloat16) * 0.05)(D, 3 * D)), 'wo': _w((lambda *s: torch.randn(*s, dtype=torch.bfloat16) * 0.05)(D, D))}
    _A_in = _A_setup()

    def _B_setup():
        B, S, D, F = (1, 2048, 512, 1376)
        return {'x': _w((lambda *s: torch.randn(*s, dtype=torch.bfloat16) * 0.05)(B, S, D)), 'w1': _w((lambda *s: torch.randn(*s, dtype=torch.bfloat16) * 0.8)(D, F) * (2.0 / D) ** 0.5), 'w3': _w((lambda *s: torch.randn(*s, dtype=torch.bfloat16) * 0.8)(D, F) * (2.0 / D) ** 0.5), 'w2': _w((lambda *s: torch.randn(*s, dtype=torch.bfloat16) * 0.8)(F, D) * (2.0 / F) ** 0.5)}
    _B_in = _B_setup()
    return {'A_x': _A_in['x'], 'A_wqkv': _A_in['wqkv'], 'A_wo': _A_in['wo'], 'B_x': _B_in['x'], 'B_w1': _B_in['w1'], 'B_w3': _B_in['w3'], 'B_w2': _B_in['w2'], 'c': _w((lambda *s: torch.randn(*s, dtype=torch.bfloat16) * 0.2)(1, 512) * 8.0), 'w_mod': _w((lambda *s: torch.randn(*s, dtype=torch.bfloat16) * 0.2)(512, 6 * 512) * 512 ** (-0.5) * 8.0)}

def reference(A_x, A_wqkv, A_wo, B_x, B_w1, B_w3, B_w2, c, w_mod):

    def _A_ref(x, wqkv, wo):
        B, S, D = x.shape
        H = 32
        Dh = D // H
        qkv = (lambda x, *d: x.permute(*d))((x @ wqkv).reshape(B, S, 3, H, Dh), 2, 0, 3, 1, 4)
        q, k, v = (qkv[0], qkv[1], qkv[2])
        scores = torch.einsum('bhqd,bhkd->bhqk', q, k) * Dh ** (-0.5)
        p = _softmax(scores, axis=-1)
        o = torch.einsum('bhqk,bhkd->bhqd', p, v)
        return (lambda x, *d: x.permute(*d))(o, 0, 2, 1, 3).reshape(B, S, D) @ wo

    def _B_ref(x, w1, w3, w2):
        gate = torch.einsum('bsd,df->bsf', x, w1)
        up = torch.einsum('bsd,df->bsf', x, w3)
        h = _silu(gate) * up
        out = torch.einsum('bsf,fd->bsd', h, w2)
        return out
    x = A_x
    mod = (_silu(c) @ w_mod).reshape(c.shape[0], 6, 1, -1)
    sa, ca, ga, sb, cb, gb = (mod[:, 0].clone(), mod[:, 1].clone(), mod[:, 2].clone(), mod[:, 3].clone(), mod[:, 4].clone(), mod[:, 5].clone())
    h = _layernorm(x, axis=-1) * (1 + ca) + sa
    x = x + ga * _A_ref(h, A_wqkv, A_wo)
    h = _layernorm(x, axis=-1) * (1 + cb) + sb
    x = x + gb * _B_ref(h, B_w1, B_w3, B_w2)
    return x
```

```cpp
#include <cuda_runtime.h>
#include <cuda_bf16.h>
#include <cuda.h>
#include <stdint.h>
typedef __nv_bfloat16 bf16;
constexpr int S_ = 2048, D_ = 512, F_ = 1376;
__device__ __align__(1024) float g_mod[3072];
__device__ __align__(1024) bf16 g_qkv[192 * 2048 * 8];
__device__ __align__(1024) float g_kmax[32 * 128];
__device__ __align__(1024) bf16 g_o[16 * 64 * 128 * 8];
__device__ __align__(1024) bf16 g_x1[16 * 64 * 128 * 8];
__device__ __align__(1024) float2 g_st[2048 * 8];
__device__ __align__(1024) bf16 g_h[16 * 172 * 128 * 8];

__device__ __forceinline__ uint32_t smem_u32(const void* p) { return (uint32_t)__cvta_generic_to_shared(p); }
__device__ __forceinline__ void mbar_init(uint32_t b, int n) { asm volatile("mbarrier.init.shared::cta.b64 [%0],%1;" ::"r"(b), "r"(n) : "memory"); }
__device__ __forceinline__ void mbar_expect(uint32_t b, int bytes) { asm volatile("mbarrier.arrive.expect_tx.shared::cta.b64 _,[%0],%1;" ::"r"(b), "r"(bytes) : "memory"); }
__device__ __forceinline__ void mbar_arrive(uint32_t b) { asm volatile("mbarrier.arrive.shared::cta.b64 _,[%0];" ::"r"(b) : "memory"); }
__device__ __forceinline__ void mbar_wait(uint32_t b, int parity) {
  uint32_t ok;
  int spins = 0;
  do {
    asm volatile("{\n.reg .pred p;\nmbarrier.try_wait.parity.shared::cta.b64 p,[%1],%2;\nselp.u32 %0,1,0,p;\n}\n" : "=r"(ok) : "r"(b), "r"(parity) : "memory");
    if (++spins > (1 << 22)) __trap();
  } while (!ok);
}
__device__ __forceinline__ void fence_init() { asm volatile("fence.mbarrier_init.release.cluster;" ::: "memory"); }
__device__ __forceinline__ void fence_async() { asm volatile("fence.proxy.async.shared::cta;" ::: "memory"); }
__device__ __forceinline__ void bulk_load(uint32_t dst, const void* src, int bytes, uint32_t bar) {
  asm volatile("cp.async.bulk.shared::cluster.global.mbarrier::complete_tx::bytes [%0],[%1],%2,[%3];" ::"r"(dst), "l"(src), "r"(bytes), "r"(bar) : "memory");
}
__device__ __forceinline__ void tma2d(uint32_t dst, const CUtensorMap* m, int c0, int c1, uint32_t bar) {
  asm volatile("cp.async.bulk.tensor.2d.shared::cluster.global.mbarrier::complete_tx::bytes [%0],[%1,{%3,%4}],[%2];" ::"r"(dst), "l"(m), "r"(bar), "r"(c0), "r"(c1) : "memory");
}
__device__ __forceinline__ void l2_prefetch(const void* p, int bytes) { asm volatile("cp.async.bulk.prefetch.L2.global [%0],%1;" ::"l"(p), "r"(bytes) : "memory"); }
__device__ __forceinline__ void pdl_launch() { asm volatile("griddepcontrol.launch_dependents;" ::: "memory"); }
__device__ __forceinline__ void pdl_wait() { asm volatile("griddepcontrol.wait;" ::: "memory"); }
__device__ __forceinline__ void wg_fence() { asm volatile("wgmma.fence.sync.aligned;" ::: "memory"); }
__device__ __forceinline__ void wg_commit() { asm volatile("wgmma.commit_group.sync.aligned;" ::: "memory"); }
template <int N> __device__ __forceinline__ void wg_wait() { asm volatile("wgmma.wait_group.sync.aligned %0;" ::"n"(N) : "memory"); }
template <int N> __device__ __forceinline__ void reg_fence(float (&d)[N]) {
#pragma unroll
  for (int i = 0; i < N; i++) asm volatile("" : "+f"(d[i])::"memory");
}
__device__ __forceinline__ uint64_t mk_desc(uint32_t addr, uint32_t lbo, uint32_t sbo, uint32_t mode) {
  return (uint64_t)((addr >> 4) & 0x3FFF) | ((uint64_t)(lbo >> 4) << 16) | ((uint64_t)(sbo >> 4) << 32) | ((uint64_t)mode << 62);
}
__device__ __forceinline__ void ldsm4(uint32_t a, uint32_t (&r)[4]) {
  asm volatile("ldmatrix.sync.aligned.m8n8.x4.shared.b16 {%0,%1,%2,%3},[%4];" : "=r"(r[0]), "=r"(r[1]), "=r"(r[2]), "=r"(r[3]) : "r"(a) : "memory");
}
__device__ __forceinline__ uint32_t pack_rn(float lo, float hi) { uint32_t r; asm("cvt.rn.bf16x2.f32 %0,%1,%2;" : "=r"(r) : "f"(hi), "f"(lo)); return r; }
__device__ __forceinline__ uint32_t pack_rz(float lo, float hi) { uint32_t r; asm("cvt.rz.bf16x2.f32 %0,%1,%2;" : "=r"(r) : "f"(hi), "f"(lo)); return r; }
__device__ __forceinline__ float blo(uint32_t u) { return __uint_as_float(u << 16); }
__device__ __forceinline__ float bhi(uint32_t u) { return __uint_as_float(u & 0xFFFF0000u); }
__device__ __forceinline__ float rbf(float x) { return __bfloat162float(__float2bfloat16_rn(x)); }
__device__ __forceinline__ float qsum(float v) { v += __shfl_xor_sync(~0u, v, 1); return v + __shfl_xor_sync(~0u, v, 2); }
__device__ __forceinline__ float ex2(float x) { float r; asm("ex2.approx.ftz.f32 %0,%1;" : "=f"(r) : "f"(x)); return r; }
__device__ __forceinline__ void wgmma_rs_n128_t0(float (&d)[64],uint32_t a0,uint32_t a1,uint32_t a2,uint32_t a3,uint64_t db,int sc){
  asm volatile("{\n.reg .pred p;\nsetp.ne.b32 p,%69,0;\n"
    "wgmma.mma_async.sync.aligned.m64n128k16.f32.bf16.bf16 {%0,%1,%2,%3,%4,%5,%6,%7,%8,%9,%10,%11,%12,%13,%14,%15,%16,%17,%18,%19,%20,%21,%22,%23,%24,%25,%26,%27,%28,%29,%30,%31,%32,%33,%34,%35,%36,%37,%38,%39,%40,%41,%42,%43,%44,%45,%46,%47,%48,%49,%50,%51,%52,%53,%54,%55,%56,%57,%58,%59,%60,%61,%62,%63},{%64,%65,%66,%67},%68,p,1,1,0;\n}\n"
    :"+f"(d[0]),"+f"(d[1]),"+f"(d[2]),"+f"(d[3]),"+f"(d[4]),"+f"(d[5]),"+f"(d[6]),"+f"(d[7]),"+f"(d[8]),"+f"(d[9]),"+f"(d[10]),"+f"(d[11]),"+f"(d[12]),"+f"(d[13]),"+f"(d[14]),"+f"(d[15]),"+f"(d[16]),"+f"(d[17]),"+f"(d[18]),"+f"(d[19]),"+f"(d[20]),"+f"(d[21]),"+f"(d[22]),"+f"(d[23]),"+f"(d[24]),"+f"(d[25]),"+f"(d[26]),"+f"(d[27]),"+f"(d[28]),"+f"(d[29]),"+f"(d[30]),"+f"(d[31]),"+f"(d[32]),"+f"(d[33]),"+f"(d[34]),"+f"(d[35]),"+f"(d[36]),"+f"(d[37]),"+f"(d[38]),"+f"(d[39]),"+f"(d[40]),"+f"(d[41]),"+f"(d[42]),"+f"(d[43]),"+f"(d[44]),"+f"(d[45]),"+f"(d[46]),"+f"(d[47]),"+f"(d[48]),"+f"(d[49]),"+f"(d[50]),"+f"(d[51]),"+f"(d[52]),"+f"(d[53]),"+f"(d[54]),"+f"(d[55]),"+f"(d[56]),"+f"(d[57]),"+f"(d[58]),"+f"(d[59]),"+f"(d[60]),"+f"(d[61]),"+f"(d[62]),"+f"(d[63])
    :"r"(a0),"r"(a1),"r"(a2),"r"(a3),"l"(db),"r"(sc));
}
__device__ __forceinline__ void wgmma_rs_n176_t1(float (&d)[88],uint32_t a0,uint32_t a1,uint32_t a2,uint32_t a3,uint64_t db,int sc){
  asm volatile("{\n.reg .pred p;\nsetp.ne.b32 p,%93,0;\n"
    "wgmma.mma_async.sync.aligned.m64n176k16.f32.bf16.bf16 {%0,%1,%2,%3,%4,%5,%6,%7,%8,%9,%10,%11,%12,%13,%14,%15,%16,%17,%18,%19,%20,%21,%22,%23,%24,%25,%26,%27,%28,%29,%30,%31,%32,%33,%34,%35,%36,%37,%38,%39,%40,%41,%42,%43,%44,%45,%46,%47,%48,%49,%50,%51,%52,%53,%54,%55,%56,%57,%58,%59,%60,%61,%62,%63,%64,%65,%66,%67,%68,%69,%70,%71,%72,%73,%74,%75,%76,%77,%78,%79,%80,%81,%82,%83,%84,%85,%86,%87},{%88,%89,%90,%91},%92,p,1,1,1;\n}\n"
    :"+f"(d[0]),"+f"(d[1]),"+f"(d[2]),"+f"(d[3]),"+f"(d[4]),"+f"(d[5]),"+f"(d[6]),"+f"(d[7]),"+f"(d[8]),"+f"(d[9]),"+f"(d[10]),"+f"(d[11]),"+f"(d[12]),"+f"(d[13]),"+f"(d[14]),"+f"(d[15]),"+f"(d[16]),"+f"(d[17]),"+f"(d[18]),"+f"(d[19]),"+f"(d[20]),"+f"(d[21]),"+f"(d[22]),"+f"(d[23]),"+f"(d[24]),"+f"(d[25]),"+f"(d[26]),"+f"(d[27]),"+f"(d[28]),"+f"(d[29]),"+f"(d[30]),"+f"(d[31]),"+f"(d[32]),"+f"(d[33]),"+f"(d[34]),"+f"(d[35]),"+f"(d[36]),"+f"(d[37]),"+f"(d[38]),"+f"(d[39]),"+f"(d[40]),"+f"(d[41]),"+f"(d[42]),"+f"(d[43]),"+f"(d[44]),"+f"(d[45]),"+f"(d[46]),"+f"(d[47]),"+f"(d[48]),"+f"(d[49]),"+f"(d[50]),"+f"(d[51]),"+f"(d[52]),"+f"(d[53]),"+f"(d[54]),"+f"(d[55]),"+f"(d[56]),"+f"(d[57]),"+f"(d[58]),"+f"(d[59]),"+f"(d[60]),"+f"(d[61]),"+f"(d[62]),"+f"(d[63]),"+f"(d[64]),"+f"(d[65]),"+f"(d[66]),"+f"(d[67]),"+f"(d[68]),"+f"(d[69]),"+f"(d[70]),"+f"(d[71]),"+f"(d[72]),"+f"(d[73]),"+f"(d[74]),"+f"(d[75]),"+f"(d[76]),"+f"(d[77]),"+f"(d[78]),"+f"(d[79]),"+f"(d[80]),"+f"(d[81]),"+f"(d[82]),"+f"(d[83]),"+f"(d[84]),"+f"(d[85]),"+f"(d[86]),"+f"(d[87])
    :"r"(a0),"r"(a1),"r"(a2),"r"(a3),"l"(db),"r"(sc));
}
__device__ __forceinline__ void wgmma_rs_n192_t1(float (&d)[96],uint32_t a0,uint32_t a1,uint32_t a2,uint32_t a3,uint64_t db,int sc){
  asm volatile("{\n.reg .pred p;\nsetp.ne.b32 p,%101,0;\n"
    "wgmma.mma_async.sync.aligned.m64n192k16.f32.bf16.bf16 {%0,%1,%2,%3,%4,%5,%6,%7,%8,%9,%10,%11,%12,%13,%14,%15,%16,%17,%18,%19,%20,%21,%22,%23,%24,%25,%26,%27,%28,%29,%30,%31,%32,%33,%34,%35,%36,%37,%38,%39,%40,%41,%42,%43,%44,%45,%46,%47,%48,%49,%50,%51,%52,%53,%54,%55,%56,%57,%58,%59,%60,%61,%62,%63,%64,%65,%66,%67,%68,%69,%70,%71,%72,%73,%74,%75,%76,%77,%78,%79,%80,%81,%82,%83,%84,%85,%86,%87,%88,%89,%90,%91,%92,%93,%94,%95},{%96,%97,%98,%99},%100,p,1,1,1;\n}\n"
    :"+f"(d[0]),"+f"(d[1]),"+f"(d[2]),"+f"(d[3]),"+f"(d[4]),"+f"(d[5]),"+f"(d[6]),"+f"(d[7]),"+f"(d[8]),"+f"(d[9]),"+f"(d[10]),"+f"(d[11]),"+f"(d[12]),"+f"(d[13]),"+f"(d[14]),"+f"(d[15]),"+f"(d[16]),"+f"(d[17]),"+f"(d[18]),"+f"(d[19]),"+f"(d[20]),"+f"(d[21]),"+f"(d[22]),"+f"(d[23]),"+f"(d[24]),"+f"(d[25]),"+f"(d[26]),"+f"(d[27]),"+f"(d[28]),"+f"(d[29]),"+f"(d[30]),"+f"(d[31]),"+f"(d[32]),"+f"(d[33]),"+f"(d[34]),"+f"(d[35]),"+f"(d[36]),"+f"(d[37]),"+f"(d[38]),"+f"(d[39]),"+f"(d[40]),"+f"(d[41]),"+f"(d[42]),"+f"(d[43]),"+f"(d[44]),"+f"(d[45]),"+f"(d[46]),"+f"(d[47]),"+f"(d[48]),"+f"(d[49]),"+f"(d[50]),"+f"(d[51]),"+f"(d[52]),"+f"(d[53]),"+f"(d[54]),"+f"(d[55]),"+f"(d[56]),"+f"(d[57]),"+f"(d[58]),"+f"(d[59]),"+f"(d[60]),"+f"(d[61]),"+f"(d[62]),"+f"(d[63]),"+f"(d[64]),"+f"(d[65]),"+f"(d[66]),"+f"(d[67]),"+f"(d[68]),"+f"(d[69]),"+f"(d[70]),"+f"(d[71]),"+f"(d[72]),"+f"(d[73]),"+f"(d[74]),"+f"(d[75]),"+f"(d[76]),"+f"(d[77]),"+f"(d[78]),"+f"(d[79]),"+f"(d[80]),"+f"(d[81]),"+f"(d[82]),"+f"(d[83]),"+f"(d[84]),"+f"(d[85]),"+f"(d[86]),"+f"(d[87]),"+f"(d[88]),"+f"(d[89]),"+f"(d[90]),"+f"(d[91]),"+f"(d[92]),"+f"(d[93]),"+f"(d[94]),"+f"(d[95])
    :"r"(a0),"r"(a1),"r"(a2),"r"(a3),"l"(db),"r"(sc));
}
__device__ __forceinline__ void wgmma_rs_n24_t1(float (&d)[12],uint32_t a0,uint32_t a1,uint32_t a2,uint32_t a3,uint64_t db,int sc){
  asm volatile("{\n.reg .pred p;\nsetp.ne.b32 p,%17,0;\n"
    "wgmma.mma_async.sync.aligned.m64n24k16.f32.bf16.bf16 {%0,%1,%2,%3,%4,%5,%6,%7,%8,%9,%10,%11},{%12,%13,%14,%15},%16,p,1,1,1;\n}\n"
    :"+f"(d[0]),"+f"(d[1]),"+f"(d[2]),"+f"(d[3]),"+f"(d[4]),"+f"(d[5]),"+f"(d[6]),"+f"(d[7]),"+f"(d[8]),"+f"(d[9]),"+f"(d[10]),"+f"(d[11])
    :"r"(a0),"r"(a1),"r"(a2),"r"(a3),"l"(db),"r"(sc));
}
__device__ __forceinline__ void wgmma_ss_n128_t1(float (&d)[64],uint64_t da,uint64_t db,int sc){
  asm volatile("{\n.reg .pred p;\nsetp.ne.b32 p,%66,0;\n"
    "wgmma.mma_async.sync.aligned.m64n128k16.f32.bf16.bf16 {%0,%1,%2,%3,%4,%5,%6,%7,%8,%9,%10,%11,%12,%13,%14,%15,%16,%17,%18,%19,%20,%21,%22,%23,%24,%25,%26,%27,%28,%29,%30,%31,%32,%33,%34,%35,%36,%37,%38,%39,%40,%41,%42,%43,%44,%45,%46,%47,%48,%49,%50,%51,%52,%53,%54,%55,%56,%57,%58,%59,%60,%61,%62,%63},%64,%65,p,1,1,0,1;\n}\n"
    :"+f"(d[0]),"+f"(d[1]),"+f"(d[2]),"+f"(d[3]),"+f"(d[4]),"+f"(d[5]),"+f"(d[6]),"+f"(d[7]),"+f"(d[8]),"+f"(d[9]),"+f"(d[10]),"+f"(d[11]),"+f"(d[12]),"+f"(d[13]),"+f"(d[14]),"+f"(d[15]),"+f"(d[16]),"+f"(d[17]),"+f"(d[18]),"+f"(d[19]),"+f"(d[20]),"+f"(d[21]),"+f"(d[22]),"+f"(d[23]),"+f"(d[24]),"+f"(d[25]),"+f"(d[26]),"+f"(d[27]),"+f"(d[28]),"+f"(d[29]),"+f"(d[30]),"+f"(d[31]),"+f"(d[32]),"+f"(d[33]),"+f"(d[34]),"+f"(d[35]),"+f"(d[36]),"+f"(d[37]),"+f"(d[38]),"+f"(d[39]),"+f"(d[40]),"+f"(d[41]),"+f"(d[42]),"+f"(d[43]),"+f"(d[44]),"+f"(d[45]),"+f"(d[46]),"+f"(d[47]),"+f"(d[48]),"+f"(d[49]),"+f"(d[50]),"+f"(d[51]),"+f"(d[52]),"+f"(d[53]),"+f"(d[54]),"+f"(d[55]),"+f"(d[56]),"+f"(d[57]),"+f"(d[58]),"+f"(d[59]),"+f"(d[60]),"+f"(d[61]),"+f"(d[62]),"+f"(d[63])
    :"l"(da),"l"(db),"r"(sc));
}
__device__ __forceinline__ void wgmma_ss_n64_t1(float (&d)[32],uint64_t da,uint64_t db,int sc){
  asm volatile("{\n.reg .pred p;\nsetp.ne.b32 p,%34,0;\n"
    "wgmma.mma_async.sync.aligned.m64n64k16.f32.bf16.bf16 {%0,%1,%2,%3,%4,%5,%6,%7,%8,%9,%10,%11,%12,%13,%14,%15,%16,%17,%18,%19,%20,%21,%22,%23,%24,%25,%26,%27,%28,%29,%30,%31},%32,%33,p,1,1,0,1;\n}\n"
    :"+f"(d[0]),"+f"(d[1]),"+f"(d[2]),"+f"(d[3]),"+f"(d[4]),"+f"(d[5]),"+f"(d[6]),"+f"(d[7]),"+f"(d[8]),"+f"(d[9]),"+f"(d[10]),"+f"(d[11]),"+f"(d[12]),"+f"(d[13]),"+f"(d[14]),"+f"(d[15]),"+f"(d[16]),"+f"(d[17]),"+f"(d[18]),"+f"(d[19]),"+f"(d[20]),"+f"(d[21]),"+f"(d[22]),"+f"(d[23]),"+f"(d[24]),"+f"(d[25]),"+f"(d[26]),"+f"(d[27]),"+f"(d[28]),"+f"(d[29]),"+f"(d[30]),"+f"(d[31])
    :"l"(da),"l"(db),"r"(sc));
}

__global__ void __launch_bounds__(256) k_mod(const bf16* __restrict__ c, const bf16* __restrict__ w) {
  pdl_launch();
  __shared__ float red[8][32];
  const int t = threadIdx.x, n0 = blockIdx.x * 32 + (t & 3) * 8, r0 = t >> 2;
  uint4 v[8];
  float cs[8];
#pragma unroll
  for (int i = 0; i < 8; i++) v[i] = __ldg((const uint4*)(w + (size_t)(r0 + i * 64) * 3072 + n0));
#pragma unroll
  for (int i = 0; i < 8; i++) { float x = __bfloat162float(c[r0 + i * 64]); cs[i] = rbf(x / (1.f + __expf(-x))); }
  float a[8] = {0, 0, 0, 0, 0, 0, 0, 0};
#pragma unroll
  for (int i = 0; i < 8; i++) {
    a[0] += cs[i] * blo(v[i].x); a[1] += cs[i] * bhi(v[i].x); a[2] += cs[i] * blo(v[i].y); a[3] += cs[i] * bhi(v[i].y);
    a[4] += cs[i] * blo(v[i].z); a[5] += cs[i] * bhi(v[i].z); a[6] += cs[i] * blo(v[i].w); a[7] += cs[i] * bhi(v[i].w);
  }
#pragma unroll
  for (int j = 0; j < 8; j++) {
    a[j] += __shfl_xor_sync(~0u, a[j], 4); a[j] += __shfl_xor_sync(~0u, a[j], 8); a[j] += __shfl_xor_sync(~0u, a[j], 16);
  }
  if ((t & 31) < 4) {
#pragma unroll
    for (int j = 0; j < 8; j++) red[t >> 5][(t & 3) * 8 + j] = a[j];
  }
  __syncthreads();
  if (t < 32) {
    float s = 0;
#pragma unroll
    for (int i = 0; i < 8; i++) s += red[i][t];
    const int n = blockIdx.x * 32 + t, seg = n >> 9;
    s = rbf(s);
    if (seg == 1 || seg == 4) s = rbf(1.f + s);
    g_mod[n] = s;
  }
}

constexpr int LN_SMEM = 131072 + 4 * 24576 + 2048 + 256;
template <bool FFN>
__global__ void __launch_bounds__(384, 1) k_lngemm(const __grid_constant__ CUtensorMap mX, const __grid_constant__ CUtensorMap mB0,
                                                   const __grid_constant__ CUtensorMap mB1) {
  extern __shared__ __align__(1024) uint8_t smem[];
  const uint32_t sA = smem_u32(smem), sB = sA + 131072, sM = sB + 4 * 24576, bars = sM + 2048;
  const uint32_t bA = bars, bF = bars + 64, bE = bars + 96;
  const int tid = threadIdx.x, warp = tid >> 5, lane = tid & 31;
  const int rb = blockIdx.x >> 3, ct = blockIdx.x & 7;
  constexpr int NST = FFN ? 16 : 8, KS = FFN ? 2 : 4, BOX = FFN ? 4096 : 8192;
  pdl_launch();
  if (tid == 256) {
    for (int i = 0; i < 8; i++) mbar_init(bA + 8 * i, 1);
    for (int i = 0; i < 4; i++) { mbar_init(bF + 8 * i, 1); mbar_init(bE + 8 * i, 8); }
    fence_init();
  }
  __syncthreads();
  if (warp >= 8) {
    asm volatile("setmaxnreg.dec.sync.aligned.u32 40;");
    if (tid == 256) {
      auto loadB = [&](int s) {
        const uint32_t d = sB + (s & 3) * 24576, b = bF + (s & 3) * 8;
        mbar_expect(b, 24576);
        for (int j = 0; j < 3; j++) {
          if (FFN) { tma2d(d + j * BOX, &mB0, ct * 176 + j * 64, s * 32, b); tma2d(d + (3 + j) * BOX, &mB1, ct * 176 + j * 64, s * 32, b); }
          else tma2d(d + j * BOX, &mB0, ct * 192 + j * 64, s * 64, b);
        }
      };
      if (!FFN) for (int i = 0; i < 8; i++) { mbar_expect(bA + 8 * i, 16384); tma2d(sA + i * 16384, &mX, i * 64, rb * 128, bA + 8 * i); }
      for (int s = 0; s < 4; s++) loadB(s);
      if (FFN) {
        pdl_wait();
        for (int i = 0; i < 8; i++) { mbar_expect(bA + 8 * i, 16384); bulk_load(sA + i * 16384, g_x1 + (rb * 64 + i * 8) * 1024, 16384, bA + 8 * i); }
      }
      for (int s = 4; s < NST; s++) { mbar_wait(bE + (s & 3) * 8, ((s >> 2) - 1) & 1); loadB(s); }
    }
    return;
  }
  asm volatile("setmaxnreg.inc.sync.aligned.u32 232;");
  const int g = lane >> 2, t = lane & 3;
  const int lr = warp * 16 + (lane & 7) + ((lane >> 3) & 1) * 8;
  auto aaddr = [&](int ks) -> uint32_t {
    if (FFN) return sA + (ks * 2 + (lane >> 4)) * 2048 + lr * 16;
    return sA + (ks >> 2) * 16384 + lr * 128 + ((((ks & 3) * 2 + (lane >> 4)) ^ (lr & 7)) << 4);
  };
  const int row0 = rb * 128 + warp * 16 + g;
  float rs0, rs1, nm0, nm1;
  if (!FFN) {
    float s0 = 0, s1 = 0;
#pragma unroll 4
    for (int ks = 0; ks < 32; ks++) {
      if ((ks & 3) == 0) mbar_wait(bA + 2 * ks, 0);
      uint32_t r[4]; ldsm4(aaddr(ks), r);
      s0 += (blo(r[0]) + bhi(r[0])) + (blo(r[2]) + bhi(r[2]));
      s1 += (blo(r[1]) + bhi(r[1])) + (blo(r[3]) + bhi(r[3]));
    }
    const float m0 = qsum(s0) * (1.f / 512), m1 = qsum(s1) * (1.f / 512);
    float v0 = 0, v1 = 0, v2 = 0, v3 = 0;
#pragma unroll 4
    for (int ks = 0; ks < 32; ks++) {
      uint32_t r[4]; ldsm4(aaddr(ks), r);
      float d;
      d = blo(r[0]) - m0; v0 += d * d; d = bhi(r[0]) - m0; v2 += d * d; d = blo(r[2]) - m0; v0 += d * d; d = bhi(r[2]) - m0; v2 += d * d;
      d = blo(r[1]) - m1; v1 += d * d; d = bhi(r[1]) - m1; v3 += d * d; d = blo(r[3]) - m1; v1 += d * d; d = bhi(r[3]) - m1; v3 += d * d;
    }
    rs0 = rsqrtf(qsum(v0 + v2) * (1.f / 512) + 1e-5f); rs1 = rsqrtf(qsum(v1 + v3) * (1.f / 512) + 1e-5f);
    nm0 = -m0 * rs0; nm1 = -m1 * rs1;
    pdl_wait();
  } else {
    pdl_wait();
    const float4 p0 = *(const float4*)(g_st + row0 * 8 + t * 2), p1 = *(const float4*)(g_st + (row0 + 8) * 8 + t * 2);
    const float m0 = qsum(p0.x + p0.z) * 0.125f, m1 = qsum(p1.x + p1.z) * 0.125f;
    const float v0 = qsum(p0.y + p0.w + 64.f * ((p0.x - m0) * (p0.x - m0) + (p0.z - m0) * (p0.z - m0)));
    const float v1 = qsum(p1.y + p1.w + 64.f * ((p1.x - m1) * (p1.x - m1) + (p1.z - m1) * (p1.z - m1)));
    rs0 = rsqrtf(v0 * (1.f / 512) + 1e-5f); rs1 = rsqrtf(v1 * (1.f / 512) + 1e-5f);
    nm0 = -m0 * rs0; nm1 = -m1 * rs1;
  }
  {
    const float2 sh = *(const float2*)(g_mod + (FFN ? 1536 : 0) + tid * 2), sc = *(const float2*)(g_mod + (FFN ? 2048 : 512) + tid * 2);
    uint32_t* m = (uint32_t*)(smem + (sM - sA)) + (tid >> 3) * 16 + (tid & 3) * 4 + ((tid >> 2) & 1);
    m[0] = pack_rn(sc.x, sc.y); m[2] = pack_rn(sh.x, sh.y);
    asm volatile("bar.sync 1,256;" ::: "memory");
  }
  constexpr int NA = FFN ? 88 : 96;
  float acc0[NA], acc1[FFN ? 88 : 1];
  uint32_t a[2][4];
  auto prep = [&](int ks, uint32_t(&o)[4]) {
    if (FFN && (ks & 3) == 0) mbar_wait(bA + 2 * ks, 0);
    uint32_t r[4]; ldsm4(aaddr(ks), r);
    const uint4 m = *(const uint4*)(smem + (sM - sA) + ks * 64 + t * 16);
#pragma unroll
    for (int i = 0; i < 4; i++) {
      const float rs = (i & 1) ? rs1 : rs0, nm = (i & 1) ? nm1 : nm0;
      const uint32_t n = pack_rn(fmaf(blo(r[i]), rs, nm), fmaf(bhi(r[i]), rs, nm));
      asm("fma.rn.bf16x2 %0,%1,%2,%3;" : "=r"(o[i]) : "r"(n), "r"(i < 2 ? m.x : m.y), "r"(i < 2 ? m.z : m.w));
    }
  };
  prep(0, a[0]);
#pragma unroll 1
  for (int s = 0; s < NST; s++) {
    mbar_wait(bF + (s & 3) * 8, (s >> 2) & 1);
    const uint64_t db = mk_desc(sB + (s & 3) * 24576, BOX, 1024, 1);
#pragma unroll
    for (int k = 0; k < KS; k++) {
      const int ks = s * KS + k;
      uint32_t(&c)[4] = a[k & 1];
      wg_fence();
      if constexpr (FFN) {
        wgmma_rs_n176_t1(acc0, c[0], c[1], c[2], c[3], db + k * 128, ks);
        wgmma_rs_n176_t1(acc1, c[0], c[1], c[2], c[3], db + k * 128 + 3 * BOX / 16, ks);
      } else {
        wgmma_rs_n192_t1(acc0, c[0], c[1], c[2], c[3], db + k * 128, ks);
      }
      wg_commit();
      wg_wait<1>();
      if (k == 0 && s > 0 && lane == 0) mbar_arrive(bE + ((s - 1) & 3) * 8);
      if (ks < 31) prep(ks + 1, a[(k + 1) & 1]);
    }
  }
  wg_wait<0>();
  reg_fence(acc0);
  if constexpr (FFN) {
    reg_fence(acc1);
    uint32_t* o = (uint32_t*)g_h + ((rb * 172 + ct * 22) * 128 + warp * 16 + g) * 4 + t;
#pragma unroll
    for (int j = 0; j < 22; j++) {
      if (ct * 22 + j < 172) {
        float h[4];
#pragma unroll
        for (int i = 0; i < 4; i++) { const float x = acc0[4 * j + i]; h[i] = __fdividef(x, 1.f + ex2(-1.4426950408889634f * x)) * acc1[4 * j + i]; }
        o[j * 512] = pack_rn(h[0], h[1]);
        o[j * 512 + 32] = pack_rn(h[2], h[3]);
      }
    }
  } else {
    uint32_t* o = (uint32_t*)g_qkv + (ct * 24 * 2048 + row0) * 4 + t;
#pragma unroll
    for (int j = 0; j < 24; j += 2) {
      const int G = ct * 24 + j;
      const float sc = G < 64 ? 0.25f * 1.4426950408889634f : 1.f;
      uint32_t p[4];
#pragma unroll
      for (int i = 0; i < 4; i++) p[i] = pack_rn(acc0[4 * j + 2 * i] * sc, acc0[4 * j + 2 * i + 1] * sc);
      o[j * 8192] = p[0]; o[j * 8192 + 32] = p[1]; o[(j + 1) * 8192] = p[2]; o[(j + 1) * 8192 + 32] = p[3];
      if (G >= 64 && G < 128) {
        float n0 = blo(p[0]) * blo(p[0]) + bhi(p[0]) * bhi(p[0]) + blo(p[2]) * blo(p[2]) + bhi(p[2]) * bhi(p[2]);
        float n1 = blo(p[1]) * blo(p[1]) + bhi(p[1]) * bhi(p[1]) + blo(p[3]) * blo(p[3]) + bhi(p[3]) * bhi(p[3]);
        n0 = qsum(n0); n1 = qsum(n1);
        const uint32_t mx = __reduce_max_sync(~0u, max(__float_as_uint(n0), __float_as_uint(n1)));
        if (lane == 0) g_kmax[((G - 64) >> 1) * 128 + rb * 8 + warp] = __uint_as_float(mx);
      }
    }
  }
}

#define POLYMASK 0x52A552A5u
#define AUG 0
constexpr int AT_SMEM = 5 * 32768 + 256;
__device__ __forceinline__ uint32_t exp2_pair_fma(float s0, float s1, float c) {
  float y0, y1;
  asm("fma.rn.sat.f32 %0,%1,0f00008000,%2;" : "=f"(y0) : "f"(s0), "f"(c));
  asm("fma.rn.sat.f32 %0,%1,0f00008000,%2;" : "=f"(y1) : "f"(s1), "f"(c));
  const float u0 = __uint_as_float((__float_as_uint(y0) & 0x7FFFu) | 0x43800000u), u1 = __uint_as_float((__float_as_uint(y1) & 0x7FFFu) | 0x43800000u);
  const float l0 = fmaf(u0, 0.427682191f, -109.07412f), l1 = fmaf(u1, 0.427682191f, -109.07412f);
  const float p0 = fmaf(fmaf(l0, l0, 1.11545753f), l0, 0.469651312f), p1 = fmaf(fmaf(l1, l1, 1.11545753f), l1, 0.469651312f);
  const uint32_t e = __byte_perm(__float_as_uint(y0), __float_as_uint(y1), 0x6521), m = pack_rz(p0, p1);
  return (e & 0x7F807F80u) | (m & 0x807F807Fu);
}
template <uint32_t MASK, bool AG>
__device__ __forceinline__ void attn_pass(float (&o)[12], const uint32_t (&q)[4], float m0, float m1, uint32_t sK, uint32_t bars, bool first) {
  const uint64_t dk = mk_desc(sK, 32768, 128, 0), dv = mk_desc(sK + 65536, 128, 32768, 0), d1 = mk_desc(sK + 131072, 128, 128, 0);
  const float c0 = (AG ? 127.f : 127.f - m0) * __uint_as_float(0x8000u), c1 = (AG ? 127.f : 127.f - m1) * __uint_as_float(0x8000u);
  const uint32_t am0 = (threadIdx.x & 3) ? 0u : (__float_as_uint(-m0) >> 16), am1 = (threadIdx.x & 3) ? 0u : (__float_as_uint(-m1) >> 16);
  float s[64];
  uint32_t p[32];
  if (first) mbar_wait(bars, 0);
  wg_fence();
  if (AG) wgmma_rs_n128_t0(s, am0, am1, 0, 0, d1, 0);
  wgmma_rs_n128_t0(s, q[0], q[1], q[2], q[3], dk, AG);
  wg_commit();
  auto softmax = [&]() {
    wg_wait<0>();
    reg_fence(s);
#pragma unroll
    for (int j = 0; j < 32; j++) {
      if ((MASK >> j) & 1) p[j] = exp2_pair_fma(s[2 * j], s[2 * j + 1], (j & 1) ? c1 : c0);
      else if (AG) p[j] = pack_rz(ex2(s[2 * j]), ex2(s[2 * j + 1]));
      else { const float m = (j & 1) ? m1 : m0; p[j] = pack_rz(ex2(s[2 * j] - m), ex2(s[2 * j + 1] - m)); }
    }
  };
  auto pv = [&](int i) {
#pragma unroll
    for (int k = 0; k < 8; k++) wgmma_rs_n24_t1(o, p[4 * k], p[4 * k + 1], p[4 * k + 2], p[4 * k + 3], dv + i * 128 + k * 16, i + k);
    wg_commit();
  };
#pragma unroll 1
  for (int i = 0; i < 15; i++) {
    softmax();
    if (first && (i & 3) == 3) mbar_wait(bars + 2 * (i + 1), 0);
    wg_fence();
    if (AG) wgmma_rs_n128_t0(s, am0, am1, 0, 0, d1, 0);
    wgmma_rs_n128_t0(s, q[0], q[1], q[2], q[3], dk + (i + 1) * 128, AG);
    pv(i);
  }
  softmax();
  wg_fence();
  pv(15);
  wg_wait<0>();
  reg_fence(o);
}
__device__ __forceinline__ void attn_safe(float (&o)[12], const uint32_t (&q)[4], uint32_t sK) {
  const uint64_t dk = mk_desc(sK, 32768, 128, 0);
  float m0 = -INFINITY, m1 = -INFINITY;
#pragma unroll 1
  for (int i = 0; i < 16; i++) {
    float s[64];
    wg_fence();
    wgmma_rs_n128_t0(s, q[0], q[1], q[2], q[3], dk + i * 128, 0);
    wg_commit();
    wg_wait<0>();
    reg_fence(s);
#pragma unroll
    for (int j = 0; j < 16; j++) { m0 = fmaxf(m0, fmaxf(s[4 * j], s[4 * j + 1])); m1 = fmaxf(m1, fmaxf(s[4 * j + 2], s[4 * j + 3])); }
  }
  m0 = fmaxf(m0, __shfl_xor_sync(~0u, m0, 1)); m0 = fmaxf(m0, __shfl_xor_sync(~0u, m0, 2));
  m1 = fmaxf(m1, __shfl_xor_sync(~0u, m1, 1)); m1 = fmaxf(m1, __shfl_xor_sync(~0u, m1, 2));
  attn_pass<0u, false>(o, q, m0, m1, sK, 0, false);
}
__global__ void __launch_bounds__(512, 1) k_attn(const bf16* wo, const bf16* w1, const bf16* w3, const bf16* w2) {
  extern __shared__ __align__(1024) uint8_t smem[];
  const uint32_t sK = smem_u32(smem), bars = sK + 5 * 32768;
  const int tid = threadIdx.x, warp = tid >> 5, lane = tid & 31, g = lane >> 2, t = lane & 3, wg = warp >> 2;
  const int h = blockIdx.x >> 2, qb = blockIdx.x & 3;
  pdl_launch();
  if (tid == 0) { for (int i = 0; i < 4; i++) mbar_init(bars + 8 * i, 1); fence_init(); }
#pragma unroll
  for (int i = 0; i < 4; i++) *(uint4*)(smem + 131072 + i * 8192 + tid * 16) = make_uint4(0x3F803F80u, 0x3F803F80u, 0x3F803F80u, 0x3F803F80u);
  fence_async();
  __syncthreads();
  pdl_wait();
  if (tid == 0) {
    for (int c = 0; c < 4; c++) {
      mbar_expect(bars + 8 * c, 32768);
      for (int pl = 0; pl < 4; pl++)
        bulk_load(sK + pl * 32768 + c * 8192, g_qkv + ((64 + (pl >> 1) * 64 + h * 2 + (pl & 1)) * 2048 + c * 512) * 8, 8192, bars + 8 * c);
    }
  }
  if (tid == 32) {
    l2_prefetch((const char*)wo + blockIdx.x * 4096, 4096);
    l2_prefetch((const char*)w1 + blockIdx.x * 11008, 11008);
    l2_prefetch((const char*)w3 + blockIdx.x * 11008, 11008);
    l2_prefetch((const char*)w2 + blockIdx.x * 11008, 11008);
  }
  const uint4 km4 = *(const uint4*)(g_kmax + h * 128 + lane * 4);
  const float kmax = __uint_as_float(__reduce_max_sync(~0u, max(max(km4.x, km4.y), max(km4.z, km4.w))));
#pragma unroll 1
  for (int tile = 0; tile < 2; tile++) {
    const int row = qb * 512 + tile * 256 + warp * 16 + g;
    const uint32_t* qp = (const uint32_t*)g_qkv + (h * 2 * 2048 + row) * 4 + t;
    uint32_t q[4] = {qp[0], qp[32], qp[8192], qp[8192 + 32]};
    const float n0 = qsum(blo(q[0]) * blo(q[0]) + bhi(q[0]) * bhi(q[0]) + blo(q[2]) * blo(q[2]) + bhi(q[2]) * bhi(q[2]));
    const float n1 = qsum(blo(q[1]) * blo(q[1]) + bhi(q[1]) * bhi(q[1]) + blo(q[3]) * blo(q[3]) + bhi(q[3]) * bhi(q[3]));
    const float b0 = sqrtf(n0 * kmax) * 1.001f, b1 = sqrtf(n1 * kmax) * 1.001f;
    float m0 = ceilf(b0 - 100.f), m1 = ceilf(b1 - 100.f);
    if (AUG) { m0 = __bfloat162float(__float2bfloat16_ru(m0)); m1 = __bfloat162float(__float2bfloat16_ru(m1)); }
    float o[12];
    attn_pass<POLYMASK, AUG>(o, q, m0, m1, sK, bars, tile == 0);
    bool ok = b0 < 1e4f && b1 < 1e4f && o[8] >= 0x1p-90f && o[10] >= 0x1p-90f;
#pragma unroll
    for (int i = 0; i < 12; i++) ok = ok && fabsf(o[i]) < INFINITY;
    uint32_t all;
    asm volatile("{\n.reg .pred p,r;\nsetp.ne.b32 p,%1,0;\nbar.red.and.pred r,%2,128,p;\nselp.u32 %0,1,0,r;\n}\n" : "=r"(all) : "r"((uint32_t)ok), "r"(wg + 1) : "memory");
    if (!all) attn_safe(o, q, sK);
    const float r0 = 1.f / o[8], r1 = 1.f / o[10];
    uint32_t* op = (uint32_t*)g_o + (((row >> 7) * 64 + h * 2) * 128 + (row & 127)) * 4 + t;
    op[0] = pack_rn(o[0] * r0, o[1] * r0); op[32] = pack_rn(o[2] * r1, o[3] * r1);
    op[512] = pack_rn(o[4] * r0, o[5] * r0); op[512 + 32] = pack_rn(o[6] * r1, o[7] * r1);
  }
}

constexpr int WO_SMEM = 131072 + 65536 + 256;
__global__ void __launch_bounds__(256, 1) k_wo(const __grid_constant__ CUtensorMap mW, const bf16* __restrict__ x) {
  extern __shared__ __align__(1024) uint8_t smem[];
  const uint32_t sA = smem_u32(smem), sB = sA + 131072, bars = sB + 65536;
  const int tid = threadIdx.x, warp = tid >> 5, lane = tid & 31, g = lane >> 2, t = lane & 3;
  const int rb = blockIdx.x >> 3, ct = blockIdx.x & 7;
  pdl_launch();
  if (tid == 0) {
    for (int i = 0; i < 8; i++) mbar_init(bars + 8 * i, 1);
    fence_init();
    for (int i = 0; i < 8; i++) { mbar_expect(bars + 8 * i, 24576); tma2d(sB + i * 8192, &mW, ct * 64, i * 64, bars + 8 * i); }
  }
  const int lrow = warp * 16 + g;
  uint32_t xr[16];
  const uint32_t* xp = (const uint32_t*)(x + (rb * 128 + lrow) * 512 + ct * 64) + t;
#pragma unroll
  for (int j = 0; j < 8; j++) { xr[2 * j] = __ldg(xp + j * 4); xr[2 * j + 1] = __ldg(xp + j * 4 + 8 * 256); }
  __syncthreads();
  pdl_wait();
  if (tid == 0) for (int i = 0; i < 8; i++) bulk_load(sA + i * 16384, g_o + (rb * 64 + i * 8) * 1024, 16384, bars + 8 * i);
  float2 ga[8];
#pragma unroll
  for (int j = 0; j < 8; j++) ga[j] = *(const float2*)(g_mod + 1024 + ct * 64 + j * 8 + t * 2);
  float acc[32];
  const uint64_t da = mk_desc(sA + (warp >> 2) * 1024, 2048, 128, 0), db = mk_desc(sB, 8192, 1024, 1);
#pragma unroll
  for (int c = 0; c < 8; c++) {
    mbar_wait(bars + 8 * c, 0);
    wg_fence();
#pragma unroll
    for (int k = 0; k < 4; k++) wgmma_ss_n64_t1(acc, da + (c * 4 + k) * 256, db + (c * 4 + k) * 128, c + k);
    wg_commit();
  }
  wg_wait<0>();
  reg_fence(acc);
  uint32_t* o = (uint32_t*)g_x1 + ((rb * 64 + ct * 8) * 128 + lrow) * 4 + t;
  float s0 = 0, s1 = 0;
#pragma unroll
  for (int j = 0; j < 8; j++) {
    xr[2 * j] = pack_rn(fmaf(ga[j].x, acc[4 * j], blo(xr[2 * j])), fmaf(ga[j].y, acc[4 * j + 1], bhi(xr[2 * j])));
    xr[2 * j + 1] = pack_rn(fmaf(ga[j].x, acc[4 * j + 2], blo(xr[2 * j + 1])), fmaf(ga[j].y, acc[4 * j + 3], bhi(xr[2 * j + 1])));
    o[j * 512] = xr[2 * j]; o[j * 512 + 32] = xr[2 * j + 1];
    s0 += blo(xr[2 * j]) + bhi(xr[2 * j]); s1 += blo(xr[2 * j + 1]) + bhi(xr[2 * j + 1]);
  }
  const float m0 = qsum(s0) * (1.f / 64), m1 = qsum(s1) * (1.f / 64);
  float v0 = 0, v1 = 0;
#pragma unroll
  for (int j = 0; j < 8; j++) {
    float d;
    d = blo(xr[2 * j]) - m0; v0 += d * d; d = bhi(xr[2 * j]) - m0; v0 += d * d;
    d = blo(xr[2 * j + 1]) - m1; v1 += d * d; d = bhi(xr[2 * j + 1]) - m1; v1 += d * d;
  }
  v0 = qsum(v0); v1 = qsum(v1);
  if (t == 0) g_st[(rb * 128 + lrow) * 8 + ct] = make_float2(m0, v0);
  if (t == 1) g_st[(rb * 128 + lrow + 8) * 8 + ct] = make_float2(m1, v1);
}

constexpr int W2_SMEM = 6 * 32768 + 32768 + 256;
__global__ void __cluster_dims__(2, 1, 1) __launch_bounds__(288, 1) k_w2(const __grid_constant__ CUtensorMap mW, bf16* __restrict__ out) {
  extern __shared__ __align__(1024) uint8_t smem[];
  const uint32_t sR = smem_u32(smem), sX = sR + 6 * 32768, bF = sX + 32768, bE = bF + 48;
  const int tid = threadIdx.x, warp = tid >> 5, lane = tid & 31, g = lane >> 2, t = lane & 3;
  const int kh = blockIdx.x & 1, ct = (blockIdx.x >> 1) & 3, rb = blockIdx.x >> 3;
  pdl_launch();
  if (tid == 256) {
    for (int i = 0; i < 6; i++) { mbar_init(bF + 8 * i, 1); mbar_init(bE + 8 * i, 8); }
    fence_init();
  }
  __syncthreads();
  asm volatile("barrier.cluster.arrive.relaxed.aligned;" ::: "memory");
  if (warp == 8) {
    if (lane == 0) {
      auto abytes = [&](int s) { return (kh == 1 && s == 10) ? 8192 : 16384; };
      auto loadB = [&](int s) {
        const int st = s % 6;
        mbar_expect(bF + 8 * st, 16384 + abytes(s));
        for (int j = 0; j < 2; j++) tma2d(sR + st * 32768 + 16384 + j * 8192, &mW, ct * 128 + j * 64, kh * 704 + s * 64, bF + 8 * st);
      };
      auto loadA = [&](int s) { bulk_load(sR + (s % 6) * 32768, g_h + (rb * 172 + kh * 88 + s * 8) * 1024, abytes(s), bF + 8 * (s % 6)); };
      for (int s = 0; s < 6; s++) loadB(s);
      pdl_wait();
      for (int s = 0; s < 6; s++) loadA(s);
      for (int s = 6; s < 11; s++) { mbar_wait(bE + 8 * (s - 6), 0); loadB(s); loadA(s); }
    }
    __syncwarp();
    asm volatile("barrier.cluster.wait.aligned;" ::: "memory");
    asm volatile("barrier.cluster.arrive.release.aligned;" ::: "memory");
    asm volatile("barrier.cluster.wait.acquire.aligned;" ::: "memory");
    return;
  }
  pdl_wait();
  const int lrow = warp * 16 + g;
  uint32_t xr[16];
  float2 gb[8];
  const uint32_t* xp = (const uint32_t*)g_x1 + ((rb * 64 + ct * 16 + kh * 8) * 128 + lrow) * 4 + t;
#pragma unroll
  for (int j = 0; j < 8; j++) {
    xr[2 * j] = xp[j * 512]; xr[2 * j + 1] = xp[j * 512 + 32];
    gb[j] = *(const float2*)(g_mod + 2560 + ct * 128 + kh * 64 + j * 8 + t * 2);
  }
  float acc[64];
#pragma unroll 1
  for (int s = 0; s < 11; s++) {
    const int st = s % 6;
    mbar_wait(bF + 8 * st, s >= 6);
    const uint64_t da = mk_desc(sR + st * 32768 + (warp >> 2) * 1024, 2048, 128, 0), db = mk_desc(sR + st * 32768 + 16384, 8192, 1024, 1);
    wg_fence();
    wgmma_ss_n128_t1(acc, da, db, s);
    wgmma_ss_n128_t1(acc, da + 256, db + 128, 1);
    wgmma_ss_n128_t1(acc, da + 512, db + 256, 1);
    wgmma_ss_n128_t1(acc, da + 768, db + 384, 1);
    wg_commit();
    wg_wait<1>();
    if (s > 0 && s < 6 && lane == 0) mbar_arrive(bE + 8 * (s - 1));
  }
  wg_wait<0>();
  reg_fence(acc);
  asm volatile("barrier.cluster.wait.aligned;" ::: "memory");
  uint32_t rem;
  asm("mapa.shared::cluster.u32 %0,%1,%2;" : "=r"(rem) : "r"(sX + tid * 16), "r"(kh ^ 1));
#pragma unroll
  for (int j = 0; j < 8; j++) {
    float v[4];
#pragma unroll
    for (int i = 0; i < 4; i++) { v[i] = kh ? acc[4 * j + i] : acc[32 + 4 * j + i]; acc[4 * j + i] = kh ? acc[32 + 4 * j + i] : acc[4 * j + i]; }
    asm volatile("st.shared::cluster.v4.f32 [%0],{%1,%2,%3,%4};" ::"r"(rem + j * 4096), "f"(v[0]), "f"(v[1]), "f"(v[2]), "f"(v[3]) : "memory");
  }
  asm volatile("barrier.cluster.arrive.release.aligned;" ::: "memory");
  asm volatile("barrier.cluster.wait.acquire.aligned;" ::: "memory");
  uint32_t* o = (uint32_t*)(out + (rb * 128 + lrow) * 512 + ct * 128 + kh * 64) + t;
#pragma unroll
  for (int j = 0; j < 8; j++) {
    const float4 p = *(const float4*)(smem + 6 * 32768 + j * 4096 + tid * 16);
    o[j * 4] = pack_rn(fmaf(gb[j].x, acc[4 * j] + p.x, blo(xr[2 * j])), fmaf(gb[j].y, acc[4 * j + 1] + p.y, bhi(xr[2 * j])));
    o[j * 4 + 2048] = pack_rn(fmaf(gb[j].x, acc[4 * j + 2] + p.z, blo(xr[2 * j + 1])), fmaf(gb[j].y, acc[4 * j + 3] + p.w, bhi(xr[2 * j + 1])));
  }
}

typedef CUresult (*EncFn)(CUtensorMap*, CUtensorMapDataType, cuuint32_t, void*, const cuuint64_t*, const cuuint64_t*, const cuuint32_t*,
                          const cuuint32_t*, CUtensorMapInterleave, CUtensorMapSwizzle, CUtensorMapL2promotion, CUtensorMapFloatOOBfill);
static void mk_map(EncFn f, CUtensorMap* m, const void* p, int rows, int cols, int box_rows) {
  cuuint64_t dim[2] = {(cuuint64_t)cols, (cuuint64_t)rows}, str[1] = {(cuuint64_t)cols * 2};
  cuuint32_t box[2] = {64, (cuuint32_t)box_rows}, es[2] = {1, 1};
  f(m, CU_TENSOR_MAP_DATA_TYPE_BFLOAT16, 2, (void*)p, dim, str, box, es, CU_TENSOR_MAP_INTERLEAVE_NONE, CU_TENSOR_MAP_SWIZZLE_128B,
    CU_TENSOR_MAP_L2_PROMOTION_L2_128B, CU_TENSOR_MAP_FLOAT_OOB_FILL_NONE);
}
template <typename... KA, typename... A>
static void launch(void (*k)(KA...), int grid, int block, int smem, bool pdl, A... args) {
  cudaLaunchConfig_t cfg = {};
  cfg.gridDim = dim3(grid); cfg.blockDim = dim3(block); cfg.dynamicSmemBytes = smem; cfg.stream = cudaStreamPerThread;
  cudaLaunchAttribute at[1];
  at[0].id = cudaLaunchAttributeProgrammaticStreamSerialization; at[0].val.programmaticStreamSerializationAllowed = 1;
  cfg.attrs = at; cfg.numAttrs = pdl ? 1 : 0;
  cudaLaunchKernelEx(&cfg, k, args...);
}
extern "C" void kernel_launch(void* const* d_in, const int* in_sizes, int n_in, void* d_out, int out_size) {
  const bf16 *x = (const bf16*)d_in[0], *wqkv = (const bf16*)d_in[1], *wo = (const bf16*)d_in[2], *w1 = (const bf16*)d_in[4],
             *w3 = (const bf16*)d_in[5], *w2 = (const bf16*)d_in[6], *c = (const bf16*)d_in[7], *wmod = (const bf16*)d_in[8];
  void* fp = nullptr;
  cudaDriverEntryPointQueryResult qr;
  cudaGetDriverEntryPoint("cuTensorMapEncodeTiled", &fp, cudaEnableDefault, &qr);
  EncFn f = (EncFn)fp;
  CUtensorMap mX, mQ, mO, m1, m3, m2;
  mk_map(f, &mX, x, S_, D_, 128); mk_map(f, &mQ, wqkv, D_, 3 * D_, 64); mk_map(f, &mO, wo, D_, D_, 64);
  mk_map(f, &m1, w1, D_, F_, 32); mk_map(f, &m3, w3, D_, F_, 32); mk_map(f, &m2, w2, F_, D_, 64);
  cudaFuncSetAttribute(k_lngemm<false>, cudaFuncAttributeMaxDynamicSharedMemorySize, LN_SMEM);
  cudaFuncSetAttribute(k_lngemm<true>, cudaFuncAttributeMaxDynamicSharedMemorySize, LN_SMEM);
  cudaFuncSetAttribute(k_attn, cudaFuncAttributeMaxDynamicSharedMemorySize, AT_SMEM);
  cudaFuncSetAttribute(k_wo, cudaFuncAttributeMaxDynamicSharedMemorySize, WO_SMEM);
  cudaFuncSetAttribute(k_w2, cudaFuncAttributeMaxDynamicSharedMemorySize, W2_SMEM);
  launch(k_mod, 96, 256, 0, false, c, wmod);
  launch(k_lngemm<false>, 128, 384, LN_SMEM, true, mX, mQ, mQ);
  launch(k_attn, 128, 512, AT_SMEM, true, wo, w1, w3, w2);
  launch(k_wo, 128, 256, WO_SMEM, true, mO, x);
  launch(k_lngemm<true>, 128, 384, LN_SMEM, true, mX, m1, m3);
  launch(k_w2, 128, 288, W2_SMEM, true, m2, (bf16*)d_out);
}
```

```cpp
#include <cuda_runtime.h>
#include <cuda_bf16.h>
#include <cuda.h>
#include <stdint.h>
typedef __nv_bfloat16 bf16;
constexpr int S_ = 2048, D_ = 512, F_ = 1376;
__device__ __align__(1024) float g_mod[3072];
__device__ __align__(1024) bf16 g_qkv[192 * 2048 * 8];
__device__ __align__(1024) float g_kmax[32 * 128];
__device__ __align__(1024) bf16 g_o[16 * 64 * 128 * 8];
__device__ __align__(1024) bf16 g_x1[16 * 64 * 128 * 8];
__device__ __align__(1024) float2 g_st[2048 * 8];
__device__ __align__(1024) bf16 g_h[16 * 172 * 128 * 8];

__device__ __forceinline__ uint32_t smem_u32(const void* p) { return (uint32_t)__cvta_generic_to_shared(p); }
__device__ __forceinline__ void mbar_init(uint32_t b, int n) { asm volatile("mbarrier.init.shared::cta.b64 [%0],%1;" ::"r"(b), "r"(n) : "memory"); }
__device__ __forceinline__ void mbar_expect(uint32_t b, int bytes) { asm volatile("mbarrier.arrive.expect_tx.shared::cta.b64 _,[%0],%1;" ::"r"(b), "r"(bytes) : "memory"); }
__device__ __forceinline__ void mbar_arrive(uint32_t b) { asm volatile("mbarrier.arrive.shared::cta.b64 _,[%0];" ::"r"(b) : "memory"); }
__device__ __forceinline__ void mbar_wait(uint32_t b, int parity) {
  asm volatile("{\n.reg .pred p;\n.reg .u32 n;\nmov.u32 n,0;\nLW:\nmbarrier.try_wait.parity.shared::cta.b64 p,[%0],%1;\n@p bra LD;\n"
               "add.u32 n,n,1;\nsetp.lt.u32 p,n,4194304;\n@p bra LW;\nLD:\n}\n" ::"r"(b), "r"(parity) : "memory");
}
__device__ __forceinline__ void fence_init() { asm volatile("fence.mbarrier_init.release.cluster;" ::: "memory"); }
__device__ __forceinline__ void fence_async() { asm volatile("fence.proxy.async.shared::cta;" ::: "memory"); }
__device__ __forceinline__ void bulk_load(uint32_t dst, const void* src, int bytes, uint32_t bar) {
  asm volatile("cp.async.bulk.shared::cluster.global.mbarrier::complete_tx::bytes [%0],[%1],%2,[%3];" ::"r"(dst), "l"(src), "r"(bytes), "r"(bar) : "memory");
}
__device__ __forceinline__ void tma2d(uint32_t dst, const CUtensorMap* m, int c0, int c1, uint32_t bar) {
  asm volatile("cp.async.bulk.tensor.2d.shared::cluster.global.mbarrier::complete_tx::bytes [%0],[%1,{%3,%4}],[%2];" ::"r"(dst), "l"(m), "r"(bar), "r"(c0), "r"(c1) : "memory");
}
__device__ __forceinline__ void l2_prefetch(const void* p, int bytes) { asm volatile("cp.async.bulk.prefetch.L2.global [%0],%1;" ::"l"(p), "r"(bytes) : "memory"); }
__device__ __forceinline__ void pdl_launch() { asm volatile("griddepcontrol.launch_dependents;" ::: "memory"); }
__device__ __forceinline__ void pdl_wait() { asm volatile("griddepcontrol.wait;" ::: "memory"); }
__device__ __forceinline__ void wg_fence() { asm volatile("wgmma.fence.sync.aligned;" ::: "memory"); }
__device__ __forceinline__ void wg_commit() { asm volatile("wgmma.commit_group.sync.aligned;" ::: "memory"); }
template <int N> __device__ __forceinline__ void wg_wait() { asm volatile("wgmma.wait_group.sync.aligned %0;" ::"n"(N) : "memory"); }
template <int N> __device__ __forceinline__ void reg_fence(float (&d)[N]) {
#pragma unroll
  for (int i = 0; i < N; i++) asm volatile("" : "+f"(d[i])::"memory");
}
__device__ __forceinline__ uint64_t mk_desc(uint32_t addr, uint32_t lbo, uint32_t sbo, uint32_t mode) {
  return (uint64_t)((addr >> 4) & 0x3FFF) | ((uint64_t)(lbo >> 4) << 16) | ((uint64_t)(sbo >> 4) << 32) | ((uint64_t)mode << 62);
}
__device__ __forceinline__ void ldsm4(uint32_t a, uint32_t (&r)[4]) {
  asm volatile("ldmatrix.sync.aligned.m8n8.x4.shared.b16 {%0,%1,%2,%3},[%4];" : "=r"(r[0]), "=r"(r[1]), "=r"(r[2]), "=r"(r[3]) : "r"(a) : "memory");
}
__device__ __forceinline__ uint32_t pack_rn(float lo, float hi) { uint32_t r; asm("cvt.rn.bf16x2.f32 %0,%1,%2;" : "=r"(r) : "f"(hi), "f"(lo)); return r; }
__device__ __forceinline__ uint32_t pack_rz(float lo, float hi) { uint32_t r; asm("cvt.rz.bf16x2.f32 %0,%1,%2;" : "=r"(r) : "f"(hi), "f"(lo)); return r; }
__device__ __forceinline__ float blo(uint32_t u) { return __uint_as_float(u << 16); }
__device__ __forceinline__ float bhi(uint32_t u) { return __uint_as_float(u & 0xFFFF0000u); }
__device__ __forceinline__ float rbf(float x) { return __bfloat162float(__float2bfloat16_rn(x)); }
__device__ __forceinline__ float qsum(float v) { v += __shfl_xor_sync(~0u, v, 1); return v + __shfl_xor_sync(~0u, v, 2); }
__device__ __forceinline__ float ex2(float x) { float r; asm("ex2.approx.ftz.f32 %0,%1;" : "=f"(r) : "f"(x)); return r; }
__device__ __forceinline__ void wgmma_rs_n128_t0(float (&d)[64],uint32_t a0,uint32_t a1,uint32_t a2,uint32_t a3,uint64_t db,int sc){
  asm volatile("{\n.reg .pred p;\nsetp.ne.b32 p,%69,0;\n"
    "wgmma.mma_async.sync.aligned.m64n128k16.f32.bf16.bf16 {%0,%1,%2,%3,%4,%5,%6,%7,%8,%9,%10,%11,%12,%13,%14,%15,%16,%17,%18,%19,%20,%21,%22,%23,%24,%25,%26,%27,%28,%29,%30,%31,%32,%33,%34,%35,%36,%37,%38,%39,%40,%41,%42,%43,%44,%45,%46,%47,%48,%49,%50,%51,%52,%53,%54,%55,%56,%57,%58,%59,%60,%61,%62,%63},{%64,%65,%66,%67},%68,p,1,1,0;\n}\n"
    :"+f"(d[0]),"+f"(d[1]),"+f"(d[2]),"+f"(d[3]),"+f"(d[4]),"+f"(d[5]),"+f"(d[6]),"+f"(d[7]),"+f"(d[8]),"+f"(d[9]),"+f"(d[10]),"+f"(d[11]),"+f"(d[12]),"+f"(d[13]),"+f"(d[14]),"+f"(d[15]),"+f"(d[16]),"+f"(d[17]),"+f"(d[18]),"+f"(d[19]),"+f"(d[20]),"+f"(d[21]),"+f"(d[22]),"+f"(d[23]),"+f"(d[24]),"+f"(d[25]),"+f"(d[26]),"+f"(d[27]),"+f"(d[28]),"+f"(d[29]),"+f"(d[30]),"+f"(d[31]),"+f"(d[32]),"+f"(d[33]),"+f"(d[34]),"+f"(d[35]),"+f"(d[36]),"+f"(d[37]),"+f"(d[38]),"+f"(d[39]),"+f"(d[40]),"+f"(d[41]),"+f"(d[42]),"+f"(d[43]),"+f"(d[44]),"+f"(d[45]),"+f"(d[46]),"+f"(d[47]),"+f"(d[48]),"+f"(d[49]),"+f"(d[50]),"+f"(d[51]),"+f"(d[52]),"+f"(d[53]),"+f"(d[54]),"+f"(d[55]),"+f"(d[56]),"+f"(d[57]),"+f"(d[58]),"+f"(d[59]),"+f"(d[60]),"+f"(d[61]),"+f"(d[62]),"+f"(d[63])
    :"r"(a0),"r"(a1),"r"(a2),"r"(a3),"l"(db),"r"(sc));
}
__device__ __forceinline__ void wgmma_rs_n176_t1(float (&d)[88],uint32_t a0,uint32_t a1,uint32_t a2,uint32_t a3,uint64_t db,int sc){
  asm volatile("{\n.reg .pred p;\nsetp.ne.b32 p,%93,0;\n"
    "wgmma.mma_async.sync.aligned.m64n176k16.f32.bf16.bf16 {%0,%1,%2,%3,%4,%5,%6,%7,%8,%9,%10,%11,%12,%13,%14,%15,%16,%17,%18,%19,%20,%21,%22,%23,%24,%25,%26,%27,%28,%29,%30,%31,%32,%33,%34,%35,%36,%37,%38,%39,%40,%41,%42,%43,%44,%45,%46,%47,%48,%49,%50,%51,%52,%53,%54,%55,%56,%57,%58,%59,%60,%61,%62,%63,%64,%65,%66,%67,%68,%69,%70,%71,%72,%73,%74,%75,%76,%77,%78,%79,%80,%81,%82,%83,%84,%85,%86,%87},{%88,%89,%90,%91},%92,p,1,1,1;\n}\n"
    :"+f"(d[0]),"+f"(d[1]),"+f"(d[2]),"+f"(d[3]),"+f"(d[4]),"+f"(d[5]),"+f"(d[6]),"+f"(d[7]),"+f"(d[8]),"+f"(d[9]),"+f"(d[10]),"+f"(d[11]),"+f"(d[12]),"+f"(d[13]),"+f"(d[14]),"+f"(d[15]),"+f"(d[16]),"+f"(d[17]),"+f"(d[18]),"+f"(d[19]),"+f"(d[20]),"+f"(d[21]),"+f"(d[22]),"+f"(d[23]),"+f"(d[24]),"+f"(d[25]),"+f"(d[26]),"+f"(d[27]),"+f"(d[28]),"+f"(d[29]),"+f"(d[30]),"+f"(d[31]),"+f"(d[32]),"+f"(d[33]),"+f"(d[34]),"+f"(d[35]),"+f"(d[36]),"+f"(d[37]),"+f"(d[38]),"+f"(d[39]),"+f"(d[40]),"+f"(d[41]),"+f"(d[42]),"+f"(d[43]),"+f"(d[44]),"+f"(d[45]),"+f"(d[46]),"+f"(d[47]),"+f"(d[48]),"+f"(d[49]),"+f"(d[50]),"+f"(d[51]),"+f"(d[52]),"+f"(d[53]),"+f"(d[54]),"+f"(d[55]),"+f"(d[56]),"+f"(d[57]),"+f"(d[58]),"+f"(d[59]),"+f"(d[60]),"+f"(d[61]),"+f"(d[62]),"+f"(d[63]),"+f"(d[64]),"+f"(d[65]),"+f"(d[66]),"+f"(d[67]),"+f"(d[68]),"+f"(d[69]),"+f"(d[70]),"+f"(d[71]),"+f"(d[72]),"+f"(d[73]),"+f"(d[74]),"+f"(d[75]),"+f"(d[76]),"+f"(d[77]),"+f"(d[78]),"+f"(d[79]),"+f"(d[80]),"+f"(d[81]),"+f"(d[82]),"+f"(d[83]),"+f"(d[84]),"+f"(d[85]),"+f"(d[86]),"+f"(d[87])
    :"r"(a0),"r"(a1),"r"(a2),"r"(a3),"l"(db),"r"(sc));
}
__device__ __forceinline__ void wgmma_rs_n192_t1(float (&d)[96],uint32_t a0,uint32_t a1,uint32_t a2,uint32_t a3,uint64_t db,int sc){
  asm volatile("{\n.reg .pred p;\nsetp.ne.b32 p,%101,0;\n"
    "wgmma.mma_async.sync.aligned.m64n192k16.f32.bf16.bf16 {%0,%1,%2,%3,%4,%5,%6,%7,%8,%9,%10,%11,%12,%13,%14,%15,%16,%17,%18,%19,%20,%21,%22,%23,%24,%25,%26,%27,%28,%29,%30,%31,%32,%33,%34,%35,%36,%37,%38,%39,%40,%41,%42,%43,%44,%45,%46,%47,%48,%49,%50,%51,%52,%53,%54,%55,%56,%57,%58,%59,%60,%61,%62,%63,%64,%65,%66,%67,%68,%69,%70,%71,%72,%73,%74,%75,%76,%77,%78,%79,%80,%81,%82,%83,%84,%85,%86,%87,%88,%89,%90,%91,%92,%93,%94,%95},{%96,%97,%98,%99},%100,p,1,1,1;\n}\n"
    :"+f"(d[0]),"+f"(d[1]),"+f"(d[2]),"+f"(d[3]),"+f"(d[4]),"+f"(d[5]),"+f"(d[6]),"+f"(d[7]),"+f"(d[8]),"+f"(d[9]),"+f"(d[10]),"+f"(d[11]),"+f"(d[12]),"+f"(d[13]),"+f"(d[14]),"+f"(d[15]),"+f"(d[16]),"+f"(d[17]),"+f"(d[18]),"+f"(d[19]),"+f"(d[20]),"+f"(d[21]),"+f"(d[22]),"+f"(d[23]),"+f"(d[24]),"+f"(d[25]),"+f"(d[26]),"+f"(d[27]),"+f"(d[28]),"+f"(d[29]),"+f"(d[30]),"+f"(d[31]),"+f"(d[32]),"+f"(d[33]),"+f"(d[34]),"+f"(d[35]),"+f"(d[36]),"+f"(d[37]),"+f"(d[38]),"+f"(d[39]),"+f"(d[40]),"+f"(d[41]),"+f"(d[42]),"+f"(d[43]),"+f"(d[44]),"+f"(d[45]),"+f"(d[46]),"+f"(d[47]),"+f"(d[48]),"+f"(d[49]),"+f"(d[50]),"+f"(d[51]),"+f"(d[52]),"+f"(d[53]),"+f"(d[54]),"+f"(d[55]),"+f"(d[56]),"+f"(d[57]),"+f"(d[58]),"+f"(d[59]),"+f"(d[60]),"+f"(d[61]),"+f"(d[62]),"+f"(d[63]),"+f"(d[64]),"+f"(d[65]),"+f"(d[66]),"+f"(d[67]),"+f"(d[68]),"+f"(d[69]),"+f"(d[70]),"+f"(d[71]),"+f"(d[72]),"+f"(d[73]),"+f"(d[74]),"+f"(d[75]),"+f"(d[76]),"+f"(d[77]),"+f"(d[78]),"+f"(d[79]),"+f"(d[80]),"+f"(d[81]),"+f"(d[82]),"+f"(d[83]),"+f"(d[84]),"+f"(d[85]),"+f"(d[86]),"+f"(d[87]),"+f"(d[88]),"+f"(d[89]),"+f"(d[90]),"+f"(d[91]),"+f"(d[92]),"+f"(d[93]),"+f"(d[94]),"+f"(d[95])
    :"r"(a0),"r"(a1),"r"(a2),"r"(a3),"l"(db),"r"(sc));
}
__device__ __forceinline__ void wgmma_rs_n24_t1(float (&d)[12],uint32_t a0,uint32_t a1,uint32_t a2,uint32_t a3,uint64_t db,int sc){
  asm volatile("{\n.reg .pred p;\nsetp.ne.b32 p,%17,0;\n"
    "wgmma.mma_async.sync.aligned.m64n24k16.f32.bf16.bf16 {%0,%1,%2,%3,%4,%5,%6,%7,%8,%9,%10,%11},{%12,%13,%14,%15},%16,p,1,1,1;\n}\n"
    :"+f"(d[0]),"+f"(d[1]),"+f"(d[2]),"+f"(d[3]),"+f"(d[4]),"+f"(d[5]),"+f"(d[6]),"+f"(d[7]),"+f"(d[8]),"+f"(d[9]),"+f"(d[10]),"+f"(d[11])
    :"r"(a0),"r"(a1),"r"(a2),"r"(a3),"l"(db),"r"(sc));
}
__device__ __forceinline__ void wgmma_rs_n64_t0(float (&d)[32],uint32_t a0,uint32_t a1,uint32_t a2,uint32_t a3,uint64_t db,int sc){
  asm volatile("{\n.reg .pred p;\nsetp.ne.b32 p,%37,0;\n"
    "wgmma.mma_async.sync.aligned.m64n64k16.f32.bf16.bf16 {%0,%1,%2,%3,%4,%5,%6,%7,%8,%9,%10,%11,%12,%13,%14,%15,%16,%17,%18,%19,%20,%21,%22,%23,%24,%25,%26,%27,%28,%29,%30,%31},{%32,%33,%34,%35},%36,p,1,1,0;\n}\n"
    :"+f"(d[0]),"+f"(d[1]),"+f"(d[2]),"+f"(d[3]),"+f"(d[4]),"+f"(d[5]),"+f"(d[6]),"+f"(d[7]),"+f"(d[8]),"+f"(d[9]),"+f"(d[10]),"+f"(d[11]),"+f"(d[12]),"+f"(d[13]),"+f"(d[14]),"+f"(d[15]),"+f"(d[16]),"+f"(d[17]),"+f"(d[18]),"+f"(d[19]),"+f"(d[20]),"+f"(d[21]),"+f"(d[22]),"+f"(d[23]),"+f"(d[24]),"+f"(d[25]),"+f"(d[26]),"+f"(d[27]),"+f"(d[28]),"+f"(d[29]),"+f"(d[30]),"+f"(d[31])
    :"r"(a0),"r"(a1),"r"(a2),"r"(a3),"l"(db),"r"(sc));
}
__device__ __forceinline__ void wgmma_ss_n128_t1(float (&d)[64],uint64_t da,uint64_t db,int sc){
  asm volatile("{\n.reg .pred p;\nsetp.ne.b32 p,%66,0;\n"
    "wgmma.mma_async.sync.aligned.m64n128k16.f32.bf16.bf16 {%0,%1,%2,%3,%4,%5,%6,%7,%8,%9,%10,%11,%12,%13,%14,%15,%16,%17,%18,%19,%20,%21,%22,%23,%24,%25,%26,%27,%28,%29,%30,%31,%32,%33,%34,%35,%36,%37,%38,%39,%40,%41,%42,%43,%44,%45,%46,%47,%48,%49,%50,%51,%52,%53,%54,%55,%56,%57,%58,%59,%60,%61,%62,%63},%64,%65,p,1,1,0,1;\n}\n"
    :"+f"(d[0]),"+f"(d[1]),"+f"(d[2]),"+f"(d[3]),"+f"(d[4]),"+f"(d[5]),"+f"(d[6]),"+f"(d[7]),"+f"(d[8]),"+f"(d[9]),"+f"(d[10]),"+f"(d[11]),"+f"(d[12]),"+f"(d[13]),"+f"(d[14]),"+f"(d[15]),"+f"(d[16]),"+f"(d[17]),"+f"(d[18]),"+f"(d[19]),"+f"(d[20]),"+f"(d[21]),"+f"(d[22]),"+f"(d[23]),"+f"(d[24]),"+f"(d[25]),"+f"(d[26]),"+f"(d[27]),"+f"(d[28]),"+f"(d[29]),"+f"(d[30]),"+f"(d[31]),"+f"(d[32]),"+f"(d[33]),"+f"(d[34]),"+f"(d[35]),"+f"(d[36]),"+f"(d[37]),"+f"(d[38]),"+f"(d[39]),"+f"(d[40]),"+f"(d[41]),"+f"(d[42]),"+f"(d[43]),"+f"(d[44]),"+f"(d[45]),"+f"(d[46]),"+f"(d[47]),"+f"(d[48]),"+f"(d[49]),"+f"(d[50]),"+f"(d[51]),"+f"(d[52]),"+f"(d[53]),"+f"(d[54]),"+f"(d[55]),"+f"(d[56]),"+f"(d[57]),"+f"(d[58]),"+f"(d[59]),"+f"(d[60]),"+f"(d[61]),"+f"(d[62]),"+f"(d[63])
    :"l"(da),"l"(db),"r"(sc));
}
__device__ __forceinline__ void wgmma_ss_n64_t1(float (&d)[32],uint64_t da,uint64_t db,int sc){
  asm volatile("{\n.reg .pred p;\nsetp.ne.b32 p,%34,0;\n"
    "wgmma.mma_async.sync.aligned.m64n64k16.f32.bf16.bf16 {%0,%1,%2,%3,%4,%5,%6,%7,%8,%9,%10,%11,%12,%13,%14,%15,%16,%17,%18,%19,%20,%21,%22,%23,%24,%25,%26,%27,%28,%29,%30,%31},%32,%33,p,1,1,0,1;\n}\n"
    :"+f"(d[0]),"+f"(d[1]),"+f"(d[2]),"+f"(d[3]),"+f"(d[4]),"+f"(d[5]),"+f"(d[6]),"+f"(d[7]),"+f"(d[8]),"+f"(d[9]),"+f"(d[10]),"+f"(d[11]),"+f"(d[12]),"+f"(d[13]),"+f"(d[14]),"+f"(d[15]),"+f"(d[16]),"+f"(d[17]),"+f"(d[18]),"+f"(d[19]),"+f"(d[20]),"+f"(d[21]),"+f"(d[22]),"+f"(d[23]),"+f"(d[24]),"+f"(d[25]),"+f"(d[26]),"+f"(d[27]),"+f"(d[28]),"+f"(d[29]),"+f"(d[30]),"+f"(d[31])
    :"l"(da),"l"(db),"r"(sc));
}

__global__ void __launch_bounds__(256) k_mod(const bf16* __restrict__ c, const bf16* __restrict__ w) {
  pdl_launch();
  __shared__ float red[8][32];
  const int t = threadIdx.x, n0 = blockIdx.x * 32 + (t & 3) * 8, r0 = t >> 2;
  uint4 v[8];
  float cs[8];
#pragma unroll
  for (int i = 0; i < 8; i++) v[i] = __ldg((const uint4*)(w + (size_t)(r0 + i * 64) * 3072 + n0));
#pragma unroll
  for (int i = 0; i < 8; i++) { float x = __bfloat162float(c[r0 + i * 64]); cs[i] = rbf(x / (1.f + __expf(-x))); }
  float a[8] = {0, 0, 0, 0, 0, 0, 0, 0};
#pragma unroll
  for (int i = 0; i < 8; i++) {
    a[0] += cs[i] * blo(v[i].x); a[1] += cs[i] * bhi(v[i].x); a[2] += cs[i] * blo(v[i].y); a[3] += cs[i] * bhi(v[i].y);
    a[4] += cs[i] * blo(v[i].z); a[5] += cs[i] * bhi(v[i].z); a[6] += cs[i] * blo(v[i].w); a[7] += cs[i] * bhi(v[i].w);
  }
#pragma unroll
  for (int j = 0; j < 8; j++) {
    a[j] += __shfl_xor_sync(~0u, a[j], 4); a[j] += __shfl_xor_sync(~0u, a[j], 8); a[j] += __shfl_xor_sync(~0u, a[j], 16);
  }
  if ((t & 31) < 4) {
#pragma unroll
    for (int j = 0; j < 8; j++) red[t >> 5][(t & 3) * 8 + j] = a[j];
  }
  __syncthreads();
  if (t < 32) {
    float s = 0;
#pragma unroll
    for (int i = 0; i < 8; i++) s += red[i][t];
    const int n = blockIdx.x * 32 + t, seg = n >> 9;
    s = rbf(s);
    if (seg == 1 || seg == 4) s = rbf(1.f + s);
    g_mod[n] = s;
  }
}

constexpr int LN_SMEM = 131072 + 4 * 24576 + 2048 + 256;
template <bool FFN>
__global__ void __launch_bounds__(384, 1) k_lngemm(const __grid_constant__ CUtensorMap mX, const __grid_constant__ CUtensorMap mB0,
                                                   const __grid_constant__ CUtensorMap mB1) {
  extern __shared__ __align__(1024) uint8_t smem[];
  const uint32_t sA = smem_u32(smem), sB = sA + 131072, sM = sB + 4 * 24576, bars = sM + 2048;
  const uint32_t bA = bars, bF = bars + 64, bE = bars + 96;
  const int tid = threadIdx.x, warp = tid >> 5, lane = tid & 31;
  const int rb = blockIdx.x >> 3, ct = blockIdx.x & 7;
  constexpr int NST = FFN ? 16 : 8, KS = FFN ? 2 : 4, BOX = FFN ? 4096 : 8192;
  pdl_launch();
  if (tid == 256) {
    for (int i = 0; i < 8; i++) mbar_init(bA + 8 * i, 1);
    for (int i = 0; i < 4; i++) { mbar_init(bF + 8 * i, 1); mbar_init(bE + 8 * i, 8); }
    fence_init();
  }
  __syncthreads();
  if (warp >= 8) {
    asm volatile("setmaxnreg.dec.sync.aligned.u32 40;");
    if (tid == 256) {
      auto loadB = [&](int s) {
        const uint32_t d = sB + (s & 3) * 24576, b = bF + (s & 3) * 8;
        mbar_expect(b, 24576);
        for (int j = 0; j < 3; j++) {
          if (FFN) { tma2d(d + j * BOX, &mB0, ct * 176 + j * 64, s * 32, b); tma2d(d + (3 + j) * BOX, &mB1, ct * 176 + j * 64, s * 32, b); }
          else tma2d(d + j * BOX, &mB0, ct * 192 + j * 64, s * 64, b);
        }
      };
      if (!FFN) for (int i = 0; i < 8; i++) { mbar_expect(bA + 8 * i, 16384); tma2d(sA + i * 16384, &mX, i * 64, rb * 128, bA + 8 * i); }
      for (int s = 0; s < 4; s++) loadB(s);
      if (FFN) {
        pdl_wait();
        for (int i = 0; i < 8; i++) { mbar_expect(bA + 8 * i, 16384); bulk_load(sA + i * 16384, g_x1 + (rb * 64 + i * 8) * 1024, 16384, bA + 8 * i); }
      }
      for (int s = 4; s < NST; s++) { mbar_wait(bE + (s & 3) * 8, ((s >> 2) - 1) & 1); loadB(s); }
    }
  } else {
  asm volatile("setmaxnreg.inc.sync.aligned.u32 232;");
  const int g = lane >> 2, t = lane & 3;
  const int lr = warp * 16 + (lane & 7) + ((lane >> 3) & 1) * 8;
  auto aaddr = [&](int ks) -> uint32_t {
    if (FFN) return sA + (ks * 2 + (lane >> 4)) * 2048 + lr * 16;
    return sA + (ks >> 2) * 16384 + lr * 128 + ((((ks & 3) * 2 + (lane >> 4)) ^ (lr & 7)) << 4);
  };
  const int row0 = rb * 128 + warp * 16 + g;
  float rs0, rs1, nm0, nm1;
  if (!FFN) {
    float s0 = 0, s1 = 0;
#pragma unroll 4
    for (int ks = 0; ks < 32; ks++) {
      if ((ks & 3) == 0) mbar_wait(bA + 2 * ks, 0);
      uint32_t r[4]; ldsm4(aaddr(ks), r);
      s0 += (blo(r[0]) + bhi(r[0])) + (blo(r[2]) + bhi(r[2]));
      s1 += (blo(r[1]) + bhi(r[1])) + (blo(r[3]) + bhi(r[3]));
    }
    const float m0 = qsum(s0) * (1.f / 512), m1 = qsum(s1) * (1.f / 512);
    float v0 = 0, v1 = 0, v2 = 0, v3 = 0;
#pragma unroll 4
    for (int ks = 0; ks < 32; ks++) {
      uint32_t r[4]; ldsm4(aaddr(ks), r);
      float d;
      d = blo(r[0]) - m0; v0 += d * d; d = bhi(r[0]) - m0; v2 += d * d; d = blo(r[2]) - m0; v0 += d * d; d = bhi(r[2]) - m0; v2 += d * d;
      d = blo(r[1]) - m1; v1 += d * d; d = bhi(r[1]) - m1; v3 += d * d; d = blo(r[3]) - m1; v1 += d * d; d = bhi(r[3]) - m1; v3 += d * d;
    }
    rs0 = rsqrtf(qsum(v0 + v2) * (1.f / 512) + 1e-5f); rs1 = rsqrtf(qsum(v1 + v3) * (1.f / 512) + 1e-5f);
    nm0 = -m0 * rs0; nm1 = -m1 * rs1;
    pdl_wait();
  } else {
    pdl_wait();
    const float4 p0 = *(const float4*)(g_st + row0 * 8 + t * 2), p1 = *(const float4*)(g_st + (row0 + 8) * 8 + t * 2);
    const float m0 = qsum(p0.x + p0.z) * 0.125f, m1 = qsum(p1.x + p1.z) * 0.125f;
    const float v0 = qsum(p0.y + p0.w + 64.f * ((p0.x - m0) * (p0.x - m0) + (p0.z - m0) * (p0.z - m0)));
    const float v1 = qsum(p1.y + p1.w + 64.f * ((p1.x - m1) * (p1.x - m1) + (p1.z - m1) * (p1.z - m1)));
    rs0 = rsqrtf(v0 * (1.f / 512) + 1e-5f); rs1 = rsqrtf(v1 * (1.f / 512) + 1e-5f);
    nm0 = -m0 * rs0; nm1 = -m1 * rs1;
  }
  {
    const float2 sh = *(const float2*)(g_mod + (FFN ? 1536 : 0) + tid * 2), sc = *(const float2*)(g_mod + (FFN ? 2048 : 512) + tid * 2);
    uint32_t* m = (uint32_t*)(smem + (sM - sA)) + (tid >> 3) * 16 + (tid & 3) * 4 + ((tid >> 2) & 1);
    m[0] = pack_rn(sc.x, sc.y); m[2] = pack_rn(sh.x, sh.y);
    asm volatile("bar.sync 1,256;" ::: "memory");
  }
  constexpr int NA = FFN ? 88 : 96;
  float acc0[NA], acc1[FFN ? 88 : 1];
  uint32_t a[2][4];
  auto prep = [&](int ks, uint32_t(&o)[4]) {
    if (FFN && (ks & 3) == 0) mbar_wait(bA + 2 * ks, 0);
    uint32_t r[4]; ldsm4(aaddr(ks), r);
    const uint4 m = *(const uint4*)(smem + (sM - sA) + ks * 64 + t * 16);
#pragma unroll
    for (int i = 0; i < 4; i++) {
      const float rs = (i & 1) ? rs1 : rs0, nm = (i & 1) ? nm1 : nm0;
      const uint32_t n = pack_rn(fmaf(blo(r[i]), rs, nm), fmaf(bhi(r[i]), rs, nm));
      asm("fma.rn.bf16x2 %0,%1,%2,%3;" : "=r"(o[i]) : "r"(n), "r"(i < 2 ? m.x : m.y), "r"(i < 2 ? m.z : m.w));
    }
  };
  prep(0, a[0]);
#pragma unroll 1
  for (int s = 0; s < NST; s++) {
    mbar_wait(bF + (s & 3) * 8, (s >> 2) & 1);
    const uint64_t db = mk_desc(sB + (s & 3) * 24576, BOX, 1024, 1);
#pragma unroll
    for (int k = 0; k < KS; k++) {
      const int ks = s * KS + k;
      uint32_t(&c)[4] = a[k & 1];
      wg_fence();
      if constexpr (FFN) {
        wgmma_rs_n176_t1(acc0, c[0], c[1], c[2], c[3], db + k * 128, ks);
        wgmma_rs_n176_t1(acc1, c[0], c[1], c[2], c[3], db + k * 128 + 3 * BOX / 16, ks);
      } else {
        wgmma_rs_n192_t1(acc0, c[0], c[1], c[2], c[3], db + k * 128, ks);
      }
      wg_commit();
      wg_wait<1>();
      if (k == 0 && s > 0 && lane == 0) mbar_arrive(bE + ((s - 1) & 3) * 8);
      if (ks < 31) prep(ks + 1, a[(k + 1) & 1]);
    }
  }
  wg_wait<0>();
  reg_fence(acc0);
  if constexpr (FFN) {
    reg_fence(acc1);
    uint32_t* o = (uint32_t*)g_h + ((rb * 172 + ct * 22) * 128 + warp * 16 + g) * 4 + t;
#pragma unroll
    for (int j = 0; j < 22; j++) {
      if (ct * 22 + j < 172) {
        float h[4];
#pragma unroll
        for (int i = 0; i < 4; i++) { const float x = acc0[4 * j + i]; h[i] = __fdividef(x, 1.f + ex2(-1.4426950408889634f * x)) * acc1[4 * j + i]; }
        o[j * 512] = pack_rn(h[0], h[1]);
        o[j * 512 + 32] = pack_rn(h[2], h[3]);
      }
    }
  } else {
    uint32_t* o = (uint32_t*)g_qkv + (ct * 24 * 2048 + row0) * 4 + t;
#pragma unroll
    for (int j = 0; j < 24; j += 2) {
      const int G = ct * 24 + j;
      const float sc = G < 64 ? 0.25f * 1.4426950408889634f : 1.f;
      uint32_t p[4];
#pragma unroll
      for (int i = 0; i < 4; i++) p[i] = pack_rn(acc0[4 * j + 2 * i] * sc, acc0[4 * j + 2 * i + 1] * sc);
      o[j * 8192] = p[0]; o[j * 8192 + 32] = p[1]; o[(j + 1) * 8192] = p[2]; o[(j + 1) * 8192 + 32] = p[3];
      if (G >= 64 && G < 128) {
        float n0 = blo(p[0]) * blo(p[0]) + bhi(p[0]) * bhi(p[0]) + blo(p[2]) * blo(p[2]) + bhi(p[2]) * bhi(p[2]);
        float n1 = blo(p[1]) * blo(p[1]) + bhi(p[1]) * bhi(p[1]) + blo(p[3]) * blo(p[3]) + bhi(p[3]) * bhi(p[3]);
        n0 = qsum(n0); n1 = qsum(n1);
        const uint32_t mx = __reduce_max_sync(~0u, max(__float_as_uint(n0), __float_as_uint(n1)));
        if (lane == 0) g_kmax[((G - 64) >> 1) * 128 + rb * 8 + warp] = __uint_as_float(mx);
      }
    }
  }
}
}

#define POLYMASK 0x52A552A5u
#define AUG 0
constexpr int AT_SMEM = 5 * 32768 + 256;
__device__ __forceinline__ uint32_t exp2_pair_fma(float s0, float s1, float c) {
  float y0, y1;
  asm("fma.rn.sat.f32 %0,%1,0f00008000,%2;" : "=f"(y0) : "f"(s0), "f"(c));
  asm("fma.rn.sat.f32 %0,%1,0f00008000,%2;" : "=f"(y1) : "f"(s1), "f"(c));
  const float u0 = __uint_as_float((__float_as_uint(y0) & 0x7FFFu) | 0x43800000u), u1 = __uint_as_float((__float_as_uint(y1) & 0x7FFFu) | 0x43800000u);
  const float l0 = fmaf(u0, 0.427682191f, -109.07412f), l1 = fmaf(u1, 0.427682191f, -109.07412f);
  const float p0 = fmaf(fmaf(l0, l0, 1.11545753f), l0, 0.469651312f), p1 = fmaf(fmaf(l1, l1, 1.11545753f), l1, 0.469651312f);
  const uint32_t e = __byte_perm(__float_as_uint(y0), __float_as_uint(y1), 0x6521), m = pack_rz(p0, p1);
  return (e & 0x7F807F80u) | (m & 0x807F807Fu);
}
#define PP 0
template <uint32_t MASK, bool AG>
__device__ __forceinline__ void attn_pass(float (&o)[12], const uint32_t (&q)[4], float m0, float m1, uint32_t sK, uint32_t bars, bool first) {
  const uint64_t dk = mk_desc(sK, 32768, 128, 0), dv = mk_desc(sK + 65536, 128, 32768, 0), d1 = mk_desc(sK + 131072, 128, 128, 0);
  const float c0 = (AG ? 127.f : 127.f - m0) * __uint_as_float(0x8000u), c1 = (AG ? 127.f : 127.f - m1) * __uint_as_float(0x8000u);
  const uint32_t am0 = (threadIdx.x & 3) ? 0u : (__float_as_uint(-m0) >> 16), am1 = (threadIdx.x & 3) ? 0u : (__float_as_uint(-m1) >> 16);
  auto qk = [&](float (&s)[32], int i) {
    if (AG) wgmma_rs_n64_t0(s, am0, am1, 0, 0, d1, 0);
    wgmma_rs_n64_t0(s, q[0], q[1], q[2], q[3], dk + i * 64, AG);
  };
  auto softmax = [&](float (&s)[32], uint32_t (&p)[16], uint32_t mask) {
    reg_fence(s);
#pragma unroll
    for (int j = 0; j < 16; j++) {
      if ((mask >> j) & 1) p[j] = exp2_pair_fma(s[2 * j], s[2 * j + 1], (j & 1) ? c1 : c0);
      else if (AG) p[j] = pack_rz(ex2(s[2 * j]), ex2(s[2 * j + 1]));
      else { const float m = (j & 1) ? m1 : m0; p[j] = pack_rz(ex2(s[2 * j] - m), ex2(s[2 * j + 1] - m)); }
    }
  };
  auto pv = [&](uint32_t (&p)[16], int i) {
#pragma unroll
    for (int k = 0; k < 4; k++) wgmma_rs_n24_t1(o, p[4 * k], p[4 * k + 1], p[4 * k + 2], p[4 * k + 3], dv + i * 64 + k * 16, i + k);
  };
  if (first) mbar_wait(bars, 0);
  float s[32];
  uint32_t p[16];
  wg_fence(); qk(s, 0); wg_commit();
#pragma unroll 1
  for (int i = 0; i < 30; i += 2) {
    wg_wait<0>(); softmax(s, p, MASK);
    wg_fence(); qk(s, i + 1); pv(p, i); wg_commit();
    wg_wait<0>(); softmax(s, p, MASK >> 16);
    if (first && (i & 7) == 6) mbar_wait(bars + i + 2, 0);
    wg_fence(); qk(s, i + 2); pv(p, i + 1); wg_commit();
  }
  wg_wait<0>(); softmax(s, p, MASK);
  wg_fence(); qk(s, 31); pv(p, 30); wg_commit();
  wg_wait<0>(); softmax(s, p, MASK >> 16);
  wg_fence(); pv(p, 31); wg_commit();
  wg_wait<0>();
  reg_fence(o);
}
__device__ __forceinline__ void attn_safe(float (&o)[12], const uint32_t (&q)[4], uint32_t sK) {
  const uint64_t dk = mk_desc(sK, 32768, 128, 0);
  float m0 = -INFINITY, m1 = -INFINITY;
#pragma unroll 1
  for (int i = 0; i < 16; i++) {
    float s[64];
    wg_fence();
    wgmma_rs_n128_t0(s, q[0], q[1], q[2], q[3], dk + i * 128, 0);
    wg_commit();
    wg_wait<0>();
    reg_fence(s);
#pragma unroll
    for (int j = 0; j < 16; j++) { m0 = fmaxf(m0, fmaxf(s[4 * j], s[4 * j + 1])); m1 = fmaxf(m1, fmaxf(s[4 * j + 2], s[4 * j + 3])); }
  }
  m0 = fmaxf(m0, __shfl_xor_sync(~0u, m0, 1)); m0 = fmaxf(m0, __shfl_xor_sync(~0u, m0, 2));
  m1 = fmaxf(m1, __shfl_xor_sync(~0u, m1, 1)); m1 = fmaxf(m1, __shfl_xor_sync(~0u, m1, 2));
  attn_pass<0u, false>(o, q, m0, m1, sK, 0, false);
}
__global__ void __launch_bounds__(512, 1) k_attn(const bf16* wo, const bf16* w1, const bf16* w3, const bf16* w2) {
  extern __shared__ __align__(1024) uint8_t smem[];
  const uint32_t sK = smem_u32(smem), bars = sK + 5 * 32768;
  const int tid = threadIdx.x, warp = tid >> 5, lane = tid & 31, g = lane >> 2, t = lane & 3, wg = warp >> 2;
  const int h = blockIdx.x >> 2, qb = blockIdx.x & 3;
  pdl_launch();
  if (tid == 0) { for (int i = 0; i < 4; i++) mbar_init(bars + 8 * i, 1); fence_init(); }
#pragma unroll
  for (int i = 0; i < 4; i++) *(uint4*)(smem + 131072 + i * 8192 + tid * 16) = make_uint4(0x3F803F80u, 0x3F803F80u, 0x3F803F80u, 0x3F803F80u);
  fence_async();
  __syncthreads();
  pdl_wait();
  if (tid == 0) {
    for (int c = 0; c < 4; c++) {
      mbar_expect(bars + 8 * c, 32768);
      for (int pl = 0; pl < 4; pl++)
        bulk_load(sK + pl * 32768 + c * 8192, g_qkv + ((64 + (pl >> 1) * 64 + h * 2 + (pl & 1)) * 2048 + c * 512) * 8, 8192, bars + 8 * c);
    }
  }
  if (tid == 32) {
    l2_prefetch((const char*)wo + blockIdx.x * 4096, 4096);
    l2_prefetch((const char*)w1 + blockIdx.x * 11008, 11008);
    l2_prefetch((const char*)w3 + blockIdx.x * 11008, 11008);
    l2_prefetch((const char*)w2 + blockIdx.x * 11008, 11008);
  }
  const uint4 km4 = *(const uint4*)(g_kmax + h * 128 + lane * 4);
  const float kmax = __uint_as_float(__reduce_max_sync(~0u, max(max(km4.x, km4.y), max(km4.z, km4.w))));
#pragma unroll 1
  for (int tile = 0; tile < 2; tile++) {
    const int row = qb * 512 + tile * 256 + warp * 16 + g;
    const uint32_t* qp = (const uint32_t*)g_qkv + (h * 2 * 2048 + row) * 4 + t;
    uint32_t q[4] = {qp[0], qp[32], qp[8192], qp[8192 + 32]};
    const float n0 = qsum(blo(q[0]) * blo(q[0]) + bhi(q[0]) * bhi(q[0]) + blo(q[2]) * blo(q[2]) + bhi(q[2]) * bhi(q[2]));
    const float n1 = qsum(blo(q[1]) * blo(q[1]) + bhi(q[1]) * bhi(q[1]) + blo(q[3]) * blo(q[3]) + bhi(q[3]) * bhi(q[3]));
    const float b0 = sqrtf(n0 * kmax) * 1.001f, b1 = sqrtf(n1 * kmax) * 1.001f;
    float m0 = ceilf(b0 - 100.f), m1 = ceilf(b1 - 100.f);
    if (AUG) { m0 = __bfloat162float(__float2bfloat16_ru(m0)); m1 = __bfloat162float(__float2bfloat16_ru(m1)); }
    float o[12];
    attn_pass<POLYMASK, AUG>(o, q, m0, m1, sK, bars, tile == 0);
    bool ok = b0 < 1e4f && b1 < 1e4f && o[8] >= 0x1p-90f && o[10] >= 0x1p-90f;
#pragma unroll
    for (int i = 0; i < 12; i++) ok = ok && fabsf(o[i]) < INFINITY;
    uint32_t all;
    asm volatile("{\n.reg .pred p,r;\nsetp.ne.b32 p,%1,0;\nbar.red.and.pred r,%2,128,p;\nselp.u32 %0,1,0,r;\n}\n" : "=r"(all) : "r"((uint32_t)ok), "r"(wg + 1) : "memory");
    if (!all) attn_safe(o, q, sK);
    const float r0 = 1.f / o[8], r1 = 1.f / o[10];
    uint32_t* op = (uint32_t*)g_o + (((row >> 7) * 64 + h * 2) * 128 + (row & 127)) * 4 + t;
    op[0] = pack_rn(o[0] * r0, o[1] * r0); op[32] = pack_rn(o[2] * r1, o[3] * r1);
    op[512] = pack_rn(o[4] * r0, o[5] * r0); op[512 + 32] = pack_rn(o[6] * r1, o[7] * r1);
  }
}

constexpr int WO_SMEM = 131072 + 65536 + 256;
__global__ void __launch_bounds__(256, 1) k_wo(const __grid_constant__ CUtensorMap mW, const bf16* __restrict__ x) {
  extern __shared__ __align__(1024) uint8_t smem[];
  const uint32_t sA = smem_u32(smem), sB = sA + 131072, bars = sB + 65536;
  const int tid = threadIdx.x, warp = tid >> 5, lane = tid & 31, g = lane >> 2, t = lane & 3;
  const int rb = blockIdx.x >> 3, ct = blockIdx.x & 7;
  pdl_launch();
  if (tid == 0) {
    for (int i = 0; i < 8; i++) mbar_init(bars + 8 * i, 1);
    fence_init();
    for (int i = 0; i < 8; i++) { mbar_expect(bars + 8 * i, 24576); tma2d(sB + i * 8192, &mW, ct * 64, i * 64, bars + 8 * i); }
  }
  const int lrow = warp * 16 + g;
  uint32_t xr[16];
  const uint32_t* xp = (const uint32_t*)(x + (rb * 128 + lrow) * 512 + ct * 64) + t;
#pragma unroll
  for (int j = 0; j < 8; j++) { xr[2 * j] = __ldg(xp + j * 4); xr[2 * j + 1] = __ldg(xp + j * 4 + 8 * 256); }
  __syncthreads();
  pdl_wait();
  if (tid == 0) for (int i = 0; i < 8; i++) bulk_load(sA + i * 16384, g_o + (rb * 64 + i * 8) * 1024, 16384, bars + 8 * i);
  float2 ga[8];
#pragma unroll
  for (int j = 0; j < 8; j++) ga[j] = *(const float2*)(g_mod + 1024 + ct * 64 + j * 8 + t * 2);
  float acc[32];
  const uint64_t da = mk_desc(sA + (warp >> 2) * 1024, 2048, 128, 0), db = mk_desc(sB, 8192, 1024, 1);
#pragma unroll
  for (int c = 0; c < 8; c++) {
    mbar_wait(bars + 8 * c, 0);
    wg_fence();
#pragma unroll
    for (int k = 0; k < 4; k++) wgmma_ss_n64_t1(acc, da + (c * 4 + k) * 256, db + (c * 4 + k) * 128, c + k);
    wg_commit();
  }
  wg_wait<0>();
  reg_fence(acc);
  uint32_t* o = (uint32_t*)g_x1 + ((rb * 64 + ct * 8) * 128 + lrow) * 4 + t;
  float s0 = 0, s1 = 0;
#pragma unroll
  for (int j = 0; j < 8; j++) {
    xr[2 * j] = pack_rn(fmaf(ga[j].x, acc[4 * j], blo(xr[2 * j])), fmaf(ga[j].y, acc[4 * j + 1], bhi(xr[2 * j])));
    xr[2 * j + 1] = pack_rn(fmaf(ga[j].x, acc[4 * j + 2], blo(xr[2 * j + 1])), fmaf(ga[j].y, acc[4 * j + 3], bhi(xr[2 * j + 1])));
    o[j * 512] = xr[2 * j]; o[j * 512 + 32] = xr[2 * j + 1];
    s0 += blo(xr[2 * j]) + bhi(xr[2 * j]); s1 += blo(xr[2 * j + 1]) + bhi(xr[2 * j + 1]);
  }
  const float m0 = qsum(s0) * (1.f / 64), m1 = qsum(s1) * (1.f / 64);
  float v0 = 0, v1 = 0;
#pragma unroll
  for (int j = 0; j < 8; j++) {
    float d;
    d = blo(xr[2 * j]) - m0; v0 += d * d; d = bhi(xr[2 * j]) - m0; v0 += d * d;
    d = blo(xr[2 * j + 1]) - m1; v1 += d * d; d = bhi(xr[2 * j + 1]) - m1; v1 += d * d;
  }
  v0 = qsum(v0); v1 = qsum(v1);
  if (t == 0) g_st[(rb * 128 + lrow) * 8 + ct] = make_float2(m0, v0);
  if (t == 1) g_st[(rb * 128 + lrow + 8) * 8 + ct] = make_float2(m1, v1);
}

constexpr int W2_SMEM = 6 * 32768 + 32768 + 256;
__global__ void __cluster_dims__(2, 1, 1) __launch_bounds__(288, 1) k_w2(const __grid_constant__ CUtensorMap mW, bf16* __restrict__ out) {
  extern __shared__ __align__(1024) uint8_t smem[];
  const uint32_t sR = smem_u32(smem), sX = sR + 6 * 32768, bF = sX + 32768, bE = bF + 48;
  const int tid = threadIdx.x, warp = tid >> 5, lane = tid & 31, g = lane >> 2, t = lane & 3;
  const int kh = blockIdx.x & 1, ct = (blockIdx.x >> 1) & 3, rb = blockIdx.x >> 3;
  pdl_launch();
  if (tid == 256) {
    for (int i = 0; i < 6; i++) { mbar_init(bF + 8 * i, 1); mbar_init(bE + 8 * i, 8); }
    fence_init();
  }
  __syncthreads();
  asm volatile("barrier.cluster.arrive.relaxed.aligned;" ::: "memory");
  if (warp == 8) {
    if (lane == 0) {
      auto abytes = [&](int s) { return (kh == 1 && s == 10) ? 8192 : 16384; };
      auto loadB = [&](int s) {
        const int st = s % 6;
        mbar_expect(bF + 8 * st, 16384 + abytes(s));
        for (int j = 0; j < 2; j++) tma2d(sR + st * 32768 + 16384 + j * 8192, &mW, ct * 128 + j * 64, kh * 704 + s * 64, bF + 8 * st);
      };
      auto loadA = [&](int s) { bulk_load(sR + (s % 6) * 32768, g_h + (rb * 172 + kh * 88 + s * 8) * 1024, abytes(s), bF + 8 * (s % 6)); };
      for (int s = 0; s < 6; s++) loadB(s);
      pdl_wait();
      for (int s = 0; s < 6; s++) loadA(s);
      for (int s = 6; s < 11; s++) { mbar_wait(bE + 8 * (s - 6), 0); loadB(s); loadA(s); }
    }
    __syncwarp();
    asm volatile("barrier.cluster.wait.aligned;" ::: "memory");
    asm volatile("barrier.cluster.arrive.release.aligned;" ::: "memory");
    asm volatile("barrier.cluster.wait.acquire.aligned;" ::: "memory");
    return;
  }
  pdl_wait();
  const int lrow = warp * 16 + g;
  uint32_t xr[16];
  float2 gb[8];
  const uint32_t* xp = (const uint32_t*)g_x1 + ((rb * 64 + ct * 16 + kh * 8) * 128 + lrow) * 4 + t;
#pragma unroll
  for (int j = 0; j < 8; j++) {
    xr[2 * j] = xp[j * 512]; xr[2 * j + 1] = xp[j * 512 + 32];
    gb[j] = *(const float2*)(g_mod + 2560 + ct * 128 + kh * 64 + j * 8 + t * 2);
  }
  float acc[64];
#pragma unroll 1
  for (int s = 0; s < 11; s++) {
    const int st = s % 6;
    mbar_wait(bF + 8 * st, s >= 6);
    const uint64_t da = mk_desc(sR + st * 32768 + (warp >> 2) * 1024, 2048, 128, 0), db = mk_desc(sR + st * 32768 + 16384, 8192, 1024, 1);
    wg_fence();
    wgmma_ss_n128_t1(acc, da, db, s);
    wgmma_ss_n128_t1(acc, da + 256, db + 128, 1);
    wgmma_ss_n128_t1(acc, da + 512, db + 256, 1);
    wgmma_ss_n128_t1(acc, da + 768, db + 384, 1);
    wg_commit();
    wg_wait<1>();
    if (s > 0 && s < 6 && lane == 0) mbar_arrive(bE + 8 * (s - 1));
  }
  wg_wait<0>();
  reg_fence(acc);
  asm volatile("barrier.cluster.wait.aligned;" ::: "memory");
  uint32_t rem;
  asm("mapa.shared::cluster.u32 %0,%1,%2;" : "=r"(rem) : "r"(sX + tid * 16), "r"(kh ^ 1));
#pragma unroll
  for (int j = 0; j < 8; j++) {
    float v[4];
#pragma unroll
    for (int i = 0; i < 4; i++) { v[i] = kh ? acc[4 * j + i] : acc[32 + 4 * j + i]; acc[4 * j + i] = kh ? acc[32 + 4 * j + i] : acc[4 * j + i]; }
    asm volatile("st.shared::cluster.v4.f32 [%0],{%1,%2,%3,%4};" ::"r"(rem + j * 4096), "f"(v[0]), "f"(v[1]), "f"(v[2]), "f"(v[3]) : "memory");
  }
  asm volatile("barrier.cluster.arrive.release.aligned;" ::: "memory");
  asm volatile("barrier.cluster.wait.acquire.aligned;" ::: "memory");
  uint32_t* o = (uint32_t*)(out + (rb * 128 + lrow) * 512 + ct * 128 + kh * 64) + t;
#pragma unroll
  for (int j = 0; j < 8; j++) {
    const float4 p = *(const float4*)(smem + 6 * 32768 + j * 4096 + tid * 16);
    o[j * 4] = pack_rn(fmaf(gb[j].x, acc[4 * j] + p.x, blo(xr[2 * j])), fmaf(gb[j].y, acc[4 * j + 1] + p.y, bhi(xr[2 * j])));
    o[j * 4 + 2048] = pack_rn(fmaf(gb[j].x, acc[4 * j + 2] + p.z, blo(xr[2 * j + 1])), fmaf(gb[j].y, acc[4 * j + 3] + p.w, bhi(xr[2 * j + 1])));
  }
}

typedef CUresult (*EncFn)(CUtensorMap*, CUtensorMapDataType, cuuint32_t, void*, const cuuint64_t*, const cuuint64_t*, const cuuint32_t*,
                          const cuuint32_t*, CUtensorMapInterleave, CUtensorMapSwizzle, CUtensorMapL2promotion, CUtensorMapFloatOOBfill);
static void mk_map(EncFn f, CUtensorMap* m, const void* p, int rows, int cols, int box_rows) {
  cuuint64_t dim[2] = {(cuuint64_t)cols, (cuuint64_t)rows}, str[1] = {(cuuint64_t)cols * 2};
  cuuint32_t box[2] = {64, (cuuint32_t)box_rows}, es[2] = {1, 1};
  f(m, CU_TENSOR_MAP_DATA_TYPE_BFLOAT16, 2, (void*)p, dim, str, box, es, CU_TENSOR_MAP_INTERLEAVE_NONE, CU_TENSOR_MAP_SWIZZLE_128B,
    CU_TENSOR_MAP_L2_PROMOTION_L2_128B, CU_TENSOR_MAP_FLOAT_OOB_FILL_NONE);
}
template <typename... KA, typename... A>
static void launch(void (*k)(KA...), int grid, int block, int smem, bool pdl, A... args) {
  cudaLaunchConfig_t cfg = {};
  cfg.gridDim = dim3(grid); cfg.blockDim = dim3(block); cfg.dynamicSmemBytes = smem; cfg.stream = cudaStreamPerThread;
  cudaLaunchAttribute at[1];
  at[0].id = cudaLaunchAttributeProgrammaticStreamSerialization; at[0].val.programmaticStreamSerializationAllowed = 1;
  cfg.attrs = at; cfg.numAttrs = pdl ? 1 : 0;
  cudaLaunchKernelEx(&cfg, k, args...);
}
extern "C" void kernel_launch(void* const* d_in, const int* in_sizes, int n_in, void* d_out, int out_size) {
  const bf16 *x = (const bf16*)d_in[0], *wqkv = (const bf16*)d_in[1], *wo = (const bf16*)d_in[2], *w1 = (const bf16*)d_in[4],
             *w3 = (const bf16*)d_in[5], *w2 = (const bf16*)d_in[6], *c = (const bf16*)d_in[7], *wmod = (const bf16*)d_in[8];
  void* fp = nullptr;
  cudaDriverEntryPointQueryResult qr;
  cudaGetDriverEntryPoint("cuTensorMapEncodeTiled", &fp, cudaEnableDefault, &qr);
  EncFn f = (EncFn)fp;
  CUtensorMap mX, mQ, mO, m1, m3, m2;
  mk_map(f, &mX, x, S_, D_, 128); mk_map(f, &mQ, wqkv, D_, 3 * D_, 64); mk_map(f, &mO, wo, D_, D_, 64);
  mk_map(f, &m1, w1, D_, F_, 32); mk_map(f, &m3, w3, D_, F_, 32); mk_map(f, &m2, w2, F_, D_, 64);
  cudaFuncSetAttribute(k_lngemm<false>, cudaFuncAttributeMaxDynamicSharedMemorySize, LN_SMEM);
  cudaFuncSetAttribute(k_lngemm<true>, cudaFuncAttributeMaxDynamicSharedMemorySize, LN_SMEM);
  cudaFuncSetAttribute(k_attn, cudaFuncAttributeMaxDynamicSharedMemorySize, AT_SMEM);
  cudaFuncSetAttribute(k_wo, cudaFuncAttributeMaxDynamicSharedMemorySize, WO_SMEM);
  cudaFuncSetAttribute(k_w2, cudaFuncAttributeMaxDynamicSharedMemorySize, W2_SMEM);
  launch(k_mod, 96, 256, 0, false, c, wmod);
  launch(k_lngemm<false>, 128, 384, LN_SMEM, true, mX, mQ, mQ);
  launch(k_attn, 128, 512, AT_SMEM, true, wo, w1, w3, w2);
  launch(k_wo, 128, 256, WO_SMEM, true, mO, x);
  launch(k_lngemm<true>, 128, 384, LN_SMEM, true, mX, m1, m3);
  launch(k_w2, 128, 288, W2_SMEM, true, m2, (bf16*)d_out);
}
```

```cpp
#include <cuda_runtime.h>
#include <cuda_bf16.h>
#include <cuda.h>
#include <stdint.h>
typedef __nv_bfloat16 bf16;
constexpr int S_ = 2048, D_ = 512, F_ = 1376;
__device__ __align__(1024) float g_mod[3072];
__device__ __align__(1024) bf16 g_qkv[192 * 2048 * 8];
__device__ __align__(1024) float g_kmax[32 * 128];
__device__ __align__(1024) bf16 g_o[16 * 64 * 128 * 8];
__device__ __align__(1024) bf16 g_x1[16 * 64 * 128 * 8];
__device__ __align__(1024) float2 g_st[2048 * 8];
__device__ __align__(1024) bf16 g_h[16 * 172 * 128 * 8];

__device__ __forceinline__ uint32_t smem_u32(const void* p) { return (uint32_t)__cvta_generic_to_shared(p); }
__device__ __forceinline__ void mbar_init(uint32_t b, int n) { asm volatile("mbarrier.init.shared::cta.b64 [%0],%1;" ::"r"(b), "r"(n) : "memory"); }
__device__ __forceinline__ void mbar_expect(uint32_t b, int bytes) { asm volatile("mbarrier.arrive.expect_tx.shared::cta.b64 _,[%0],%1;" ::"r"(b), "r"(bytes) : "memory"); }
__device__ __forceinline__ void mbar_arrive(uint32_t b) { asm volatile("mbarrier.arrive.shared::cta.b64 _,[%0];" ::"r"(b) : "memory"); }
__device__ __forceinline__ void mbar_wait(uint32_t b, int parity) {
  asm volatile("{\n.reg .pred p;\n.reg .u32 n;\nmov.u32 n,0;\nLW:\nmbarrier.try_wait.parity.shared::cta.b64 p,[%0],%1;\n@p bra LD;\n"
               "add.u32 n,n,1;\nsetp.lt.u32 p,n,4194304;\n@p bra LW;\nLD:\n}\n" ::"r"(b), "r"(parity) : "memory");
}
__device__ __forceinline__ void fence_init() { asm volatile("fence.mbarrier_init.release.cluster;" ::: "memory"); }
__device__ __forceinline__ void fence_async() { asm volatile("fence.proxy.async.shared::cta;" ::: "memory"); }
__device__ __forceinline__ void bulk_load(uint32_t dst, const void* src, int bytes, uint32_t bar) {
  asm volatile("cp.async.bulk.shared::cluster.global.mbarrier::complete_tx::bytes [%0],[%1],%2,[%3];" ::"r"(dst), "l"(src), "r"(bytes), "r"(bar) : "memory");
}
__device__ __forceinline__ void tma2d(uint32_t dst, const CUtensorMap* m, int c0, int c1, uint32_t bar) {
  asm volatile("cp.async.bulk.tensor.2d.shared::cluster.global.mbarrier::complete_tx::bytes [%0],[%1,{%3,%4}],[%2];" ::"r"(dst), "l"(m), "r"(bar), "r"(c0), "r"(c1) : "memory");
}
__device__ __forceinline__ void l2_prefetch(const void* p, int bytes) { asm volatile("cp.async.bulk.prefetch.L2.global [%0],%1;" ::"l"(p), "r"(bytes) : "memory"); }
__device__ __forceinline__ void pdl_launch() { asm volatile("griddepcontrol.launch_dependents;" ::: "memory"); }
__device__ __forceinline__ void pdl_wait() { asm volatile("griddepcontrol.wait;" ::: "memory"); }
__device__ __forceinline__ void wg_fence() { asm volatile("wgmma.fence.sync.aligned;" ::: "memory"); }
__device__ __forceinline__ void wg_commit() { asm volatile("wgmma.commit_group.sync.aligned;" ::: "memory"); }
template <int N> __device__ __forceinline__ void wg_wait() { asm volatile("wgmma.wait_group.sync.aligned %0;" ::"n"(N) : "memory"); }
template <int N> __device__ __forceinline__ void reg_fence(float (&d)[N]) {
#pragma unroll
  for (int i = 0; i < N; i++) asm volatile("" : "+f"(d[i])::"memory");
}
template <int N> __device__ __forceinline__ void zero(float (&d)[N]) {
#pragma unroll
  for (int i = 0; i < N; i++) d[i] = 0.f;
  reg_fence(d);
}
__device__ __forceinline__ uint64_t mk_desc(uint32_t addr, uint32_t lbo, uint32_t sbo, uint32_t mode) {
  return (uint64_t)((addr >> 4) & 0x3FFF) | ((uint64_t)(lbo >> 4) << 16) | ((uint64_t)(sbo >> 4) << 32) | ((uint64_t)mode << 62);
}
__device__ __forceinline__ void ldsm4(uint32_t a, uint32_t (&r)[4]) {
  asm volatile("ldmatrix.sync.aligned.m8n8.x4.shared.b16 {%0,%1,%2,%3},[%4];" : "=r"(r[0]), "=r"(r[1]), "=r"(r[2]), "=r"(r[3]) : "r"(a) : "memory");
}
__device__ __forceinline__ uint32_t pack_rn(float lo, float hi) { uint32_t r; asm("cvt.rn.bf16x2.f32 %0,%1,%2;" : "=r"(r) : "f"(hi), "f"(lo)); return r; }
__device__ __forceinline__ uint32_t pack_rz(float lo, float hi) { uint32_t r; asm("cvt.rz.bf16x2.f32 %0,%1,%2;" : "=r"(r) : "f"(hi), "f"(lo)); return r; }
__device__ __forceinline__ float blo(uint32_t u) { return __uint_as_float(u << 16); }
__device__ __forceinline__ float bhi(uint32_t u) { return __uint_as_float(u & 0xFFFF0000u); }
__device__ __forceinline__ float rbf(float x) { return __bfloat162float(__float2bfloat16_rn(x)); }
__device__ __forceinline__ float qsum(float v) { v += __shfl_xor_sync(~0u, v, 1); return v + __shfl_xor_sync(~0u, v, 2); }
__device__ __forceinline__ float ex2(float x) { float r; asm("ex2.approx.ftz.f32 %0,%1;" : "=f"(r) : "f"(x)); return r; }
__device__ __forceinline__ void wgmma_rs_n128_t0(float (&d)[64],uint32_t a0,uint32_t a1,uint32_t a2,uint32_t a3,uint64_t db,int sc){
  asm volatile("{\n.reg .pred p;\nsetp.ne.b32 p,%69,0;\n"
    "wgmma.mma_async.sync.aligned.m64n128k16.f32.bf16.bf16 {%0,%1,%2,%3,%4,%5,%6,%7,%8,%9,%10,%11,%12,%13,%14,%15,%16,%17,%18,%19,%20,%21,%22,%23,%24,%25,%26,%27,%28,%29,%30,%31,%32,%33,%34,%35,%36,%37,%38,%39,%40,%41,%42,%43,%44,%45,%46,%47,%48,%49,%50,%51,%52,%53,%54,%55,%56,%57,%58,%59,%60,%61,%62,%63},{%64,%65,%66,%67},%68,p,1,1,0;\n}\n"
    :"+f"(d[0]),"+f"(d[1]),"+f"(d[2]),"+f"(d[3]),"+f"(d[4]),"+f"(d[5]),"+f"(d[6]),"+f"(d[7]),"+f"(d[8]),"+f"(d[9]),"+f"(d[10]),"+f"(d[11]),"+f"(d[12]),"+f"(d[13]),"+f"(d[14]),"+f"(d[15]),"+f"(d[16]),"+f"(d[17]),"+f"(d[18]),"+f"(d[19]),"+f"(d[20]),"+f"(d[21]),"+f"(d[22]),"+f"(d[23]),"+f"(d[24]),"+f"(d[25]),"+f"(d[26]),"+f"(d[27]),"+f"(d[28]),"+f"(d[29]),"+f"(d[30]),"+f"(d[31]),"+f"(d[32]),"+f"(d[33]),"+f"(d[34]),"+f"(d[35]),"+f"(d[36]),"+f"(d[37]),"+f"(d[38]),"+f"(d[39]),"+f"(d[40]),"+f"(d[41]),"+f"(d[42]),"+f"(d[43]),"+f"(d[44]),"+f"(d[45]),"+f"(d[46]),"+f"(d[47]),"+f"(d[48]),"+f"(d[49]),"+f"(d[50]),"+f"(d[51]),"+f"(d[52]),"+f"(d[53]),"+f"(d[54]),"+f"(d[55]),"+f"(d[56]),"+f"(d[57]),"+f"(d[58]),"+f"(d[59]),"+f"(d[60]),"+f"(d[61]),"+f"(d[62]),"+f"(d[63])
    :"r"(a0),"r"(a1),"r"(a2),"r"(a3),"l"(db),"r"(sc));
}
__device__ __forceinline__ void wgmma_rs_n176_t1(float (&d)[88],uint32_t a0,uint32_t a1,uint32_t a2,uint32_t a3,uint64_t db,int sc){
  asm volatile("{\n.reg .pred p;\nsetp.ne.b32 p,%93,0;\n"
    "wgmma.mma_async.sync.aligned.m64n176k16.f32.bf16.bf16 {%0,%1,%2,%3,%4,%5,%6,%7,%8,%9,%10,%11,%12,%13,%14,%15,%16,%17,%18,%19,%20,%21,%22,%23,%24,%25,%26,%27,%28,%29,%30,%31,%32,%33,%34,%35,%36,%37,%38,%39,%40,%41,%42,%43,%44,%45,%46,%47,%48,%49,%50,%51,%52,%53,%54,%55,%56,%57,%58,%59,%60,%61,%62,%63,%64,%65,%66,%67,%68,%69,%70,%71,%72,%73,%74,%75,%76,%77,%78,%79,%80,%81,%82,%83,%84,%85,%86,%87},{%88,%89,%90,%91},%92,p,1,1,1;\n}\n"
    :"+f"(d[0]),"+f"(d[1]),"+f"(d[2]),"+f"(d[3]),"+f"(d[4]),"+f"(d[5]),"+f"(d[6]),"+f"(d[7]),"+f"(d[8]),"+f"(d[9]),"+f"(d[10]),"+f"(d[11]),"+f"(d[12]),"+f"(d[13]),"+f"(d[14]),"+f"(d[15]),"+f"(d[16]),"+f"(d[17]),"+f"(d[18]),"+f"(d[19]),"+f"(d[20]),"+f"(d[21]),"+f"(d[22]),"+f"(d[23]),"+f"(d[24]),"+f"(d[25]),"+f"(d[26]),"+f"(d[27]),"+f"(d[28]),"+f"(d[29]),"+f"(d[30]),"+f"(d[31]),"+f"(d[32]),"+f"(d[33]),"+f"(d[34]),"+f"(d[35]),"+f"(d[36]),"+f"(d[37]),"+f"(d[38]),"+f"(d[39]),"+f"(d[40]),"+f"(d[41]),"+f"(d[42]),"+f"(d[43]),"+f"(d[44]),"+f"(d[45]),"+f"(d[46]),"+f"(d[47]),"+f"(d[48]),"+f"(d[49]),"+f"(d[50]),"+f"(d[51]),"+f"(d[52]),"+f"(d[53]),"+f"(d[54]),"+f"(d[55]),"+f"(d[56]),"+f"(d[57]),"+f"(d[58]),"+f"(d[59]),"+f"(d[60]),"+f"(d[61]),"+f"(d[62]),"+f"(d[63]),"+f"(d[64]),"+f"(d[65]),"+f"(d[66]),"+f"(d[67]),"+f"(d[68]),"+f"(d[69]),"+f"(d[70]),"+f"(d[71]),"+f"(d[72]),"+f"(d[73]),"+f"(d[74]),"+f"(d[75]),"+f"(d[76]),"+f"(d[77]),"+f"(d[78]),"+f"(d[79]),"+f"(d[80]),"+f"(d[81]),"+f"(d[82]),"+f"(d[83]),"+f"(d[84]),"+f"(d[85]),"+f"(d[86]),"+f"(d[87])
    :"r"(a0),"r"(a1),"r"(a2),"r"(a3),"l"(db),"r"(sc));
}
__device__ __forceinline__ void wgmma_rs_n192_t1(float (&d)[96],uint32_t a0,uint32_t a1,uint32_t a2,uint32_t a3,uint64_t db,int sc){
  asm volatile("{\n.reg .pred p;\nsetp.ne.b32 p,%101,0;\n"
    "wgmma.mma_async.sync.aligned.m64n192k16.f32.bf16.bf16 {%0,%1,%2,%3,%4,%5,%6,%7,%8,%9,%10,%11,%12,%13,%14,%15,%16,%17,%18,%19,%20,%21,%22,%23,%24,%25,%26,%27,%28,%29,%30,%31,%32,%33,%34,%35,%36,%37,%38,%39,%40,%41,%42,%43,%44,%45,%46,%47,%48,%49,%50,%51,%52,%53,%54,%55,%56,%57,%58,%59,%60,%61,%62,%63,%64,%65,%66,%67,%68,%69,%70,%71,%72,%73,%74,%75,%76,%77,%78,%79,%80,%81,%82,%83,%84,%85,%86,%87,%88,%89,%90,%91,%92,%93,%94,%95},{%96,%97,%98,%99},%100,p,1,1,1;\n}\n"
    :"+f"(d[0]),"+f"(d[1]),"+f"(d[2]),"+f"(d[3]),"+f"(d[4]),"+f"(d[5]),"+f"(d[6]),"+f"(d[7]),"+f"(d[8]),"+f"(d[9]),"+f"(d[10]),"+f"(d[11]),"+f"(d[12]),"+f"(d[13]),"+f"(d[14]),"+f"(d[15]),"+f"(d[16]),"+f"(d[17]),"+f"(d[18]),"+f"(d[19]),"+f"(d[20]),"+f"(d[21]),"+f"(d[22]),"+f"(d[23]),"+f"(d[24]),"+f"(d[25]),"+f"(d[26]),"+f"(d[27]),"+f"(d[28]),"+f"(d[29]),"+f"(d[30]),"+f"(d[31]),"+f"(d[32]),"+f"(d[33]),"+f"(d[34]),"+f"(d[35]),"+f"(d[36]),"+f"(d[37]),"+f"(d[38]),"+f"(d[39]),"+f"(d[40]),"+f"(d[41]),"+f"(d[42]),"+f"(d[43]),"+f"(d[44]),"+f"(d[45]),"+f"(d[46]),"+f"(d[47]),"+f"(d[48]),"+f"(d[49]),"+f"(d[50]),"+f"(d[51]),"+f"(d[52]),"+f"(d[53]),"+f"(d[54]),"+f"(d[55]),"+f"(d[56]),"+f"(d[57]),"+f"(d[58]),"+f"(d[59]),"+f"(d[60]),"+f"(d[61]),"+f"(d[62]),"+f"(d[63]),"+f"(d[64]),"+f"(d[65]),"+f"(d[66]),"+f"(d[67]),"+f"(d[68]),"+f"(d[69]),"+f"(d[70]),"+f"(d[71]),"+f"(d[72]),"+f"(d[73]),"+f"(d[74]),"+f"(d[75]),"+f"(d[76]),"+f"(d[77]),"+f"(d[78]),"+f"(d[79]),"+f"(d[80]),"+f"(d[81]),"+f"(d[82]),"+f"(d[83]),"+f"(d[84]),"+f"(d[85]),"+f"(d[86]),"+f"(d[87]),"+f"(d[88]),"+f"(d[89]),"+f"(d[90]),"+f"(d[91]),"+f"(d[92]),"+f"(d[93]),"+f"(d[94]),"+f"(d[95])
    :"r"(a0),"r"(a1),"r"(a2),"r"(a3),"l"(db),"r"(sc));
}
__device__ __forceinline__ void wgmma_rs_n24_t1(float (&d)[12],uint32_t a0,uint32_t a1,uint32_t a2,uint32_t a3,uint64_t db,int sc){
  asm volatile("{\n.reg .pred p;\nsetp.ne.b32 p,%17,0;\n"
    "wgmma.mma_async.sync.aligned.m64n24k16.f32.bf16.bf16 {%0,%1,%2,%3,%4,%5,%6,%7,%8,%9,%10,%11},{%12,%13,%14,%15},%16,p,1,1,1;\n}\n"
    :"+f"(d[0]),"+f"(d[1]),"+f"(d[2]),"+f"(d[3]),"+f"(d[4]),"+f"(d[5]),"+f"(d[6]),"+f"(d[7]),"+f"(d[8]),"+f"(d[9]),"+f"(d[10]),"+f"(d[11])
    :"r"(a0),"r"(a1),"r"(a2),"r"(a3),"l"(db),"r"(sc));
}
__device__ __forceinline__ void wgmma_rs_n32_t0(float (&d)[16],uint32_t a0,uint32_t a1,uint32_t a2,uint32_t a3,uint64_t db,int sc){
  asm volatile("{\n.reg .pred p;\nsetp.ne.b32 p,%21,0;\n"
    "wgmma.mma_async.sync.aligned.m64n32k16.f32.bf16.bf16 {%0,%1,%2,%3,%4,%5,%6,%7,%8,%9,%10,%11,%12,%13,%14,%15},{%16,%17,%18,%19},%20,p,1,1,0;\n}\n"
    :"+f"(d[0]),"+f"(d[1]),"+f"(d[2]),"+f"(d[3]),"+f"(d[4]),"+f"(d[5]),"+f"(d[6]),"+f"(d[7]),"+f"(d[8]),"+f"(d[9]),"+f"(d[10]),"+f"(d[11]),"+f"(d[12]),"+f"(d[13]),"+f"(d[14]),"+f"(d[15])
    :"r"(a0),"r"(a1),"r"(a2),"r"(a3),"l"(db),"r"(sc));
}
__device__ __forceinline__ void wgmma_rs_n64_t0(float (&d)[32],uint32_t a0,uint32_t a1,uint32_t a2,uint32_t a3,uint64_t db,int sc){
  asm volatile("{\n.reg .pred p;\nsetp.ne.b32 p,%37,0;\n"
    "wgmma.mma_async.sync.aligned.m64n64k16.f32.bf16.bf16 {%0,%1,%2,%3,%4,%5,%6,%7,%8,%9,%10,%11,%12,%13,%14,%15,%16,%17,%18,%19,%20,%21,%22,%23,%24,%25,%26,%27,%28,%29,%30,%31},{%32,%33,%34,%35},%36,p,1,1,0;\n}\n"
    :"+f"(d[0]),"+f"(d[1]),"+f"(d[2]),"+f"(d[3]),"+f"(d[4]),"+f"(d[5]),"+f"(d[6]),"+f"(d[7]),"+f"(d[8]),"+f"(d[9]),"+f"(d[10]),"+f"(d[11]),"+f"(d[12]),"+f"(d[13]),"+f"(d[14]),"+f"(d[15]),"+f"(d[16]),"+f"(d[17]),"+f"(d[18]),"+f"(d[19]),"+f"(d[20]),"+f"(d[21]),"+f"(d[22]),"+f"(d[23]),"+f"(d[24]),"+f"(d[25]),"+f"(d[26]),"+f"(d[27]),"+f"(d[28]),"+f"(d[29]),"+f"(d[30]),"+f"(d[31])
    :"r"(a0),"r"(a1),"r"(a2),"r"(a3),"l"(db),"r"(sc));
}
__device__ __forceinline__ void wgmma_ss_n128_t1(float (&d)[64],uint64_t da,uint64_t db,int sc){
  asm volatile("{\n.reg .pred p;\nsetp.ne.b32 p,%66,0;\n"
    "wgmma.mma_async.sync.aligned.m64n128k16.f32.bf16.bf16 {%0,%1,%2,%3,%4,%5,%6,%7,%8,%9,%10,%11,%12,%13,%14,%15,%16,%17,%18,%19,%20,%21,%22,%23,%24,%25,%26,%27,%28,%29,%30,%31,%32,%33,%34,%35,%36,%37,%38,%39,%40,%41,%42,%43,%44,%45,%46,%47,%48,%49,%50,%51,%52,%53,%54,%55,%56,%57,%58,%59,%60,%61,%62,%63},%64,%65,p,1,1,0,1;\n}\n"
    :"+f"(d[0]),"+f"(d[1]),"+f"(d[2]),"+f"(d[3]),"+f"(d[4]),"+f"(d[5]),"+f"(d[6]),"+f"(d[7]),"+f"(d[8]),"+f"(d[9]),"+f"(d[10]),"+f"(d[11]),"+f"(d[12]),"+f"(d[13]),"+f"(d[14]),"+f"(d[15]),"+f"(d[16]),"+f"(d[17]),"+f"(d[18]),"+f"(d[19]),"+f"(d[20]),"+f"(d[21]),"+f"(d[22]),"+f"(d[23]),"+f"(d[24]),"+f"(d[25]),"+f"(d[26]),"+f"(d[27]),"+f"(d[28]),"+f"(d[29]),"+f"(d[30]),"+f"(d[31]),"+f"(d[32]),"+f"(d[33]),"+f"(d[34]),"+f"(d[35]),"+f"(d[36]),"+f"(d[37]),"+f"(d[38]),"+f"(d[39]),"+f"(d[40]),"+f"(d[41]),"+f"(d[42]),"+f"(d[43]),"+f"(d[44]),"+f"(d[45]),"+f"(d[46]),"+f"(d[47]),"+f"(d[48]),"+f"(d[49]),"+f"(d[50]),"+f"(d[51]),"+f"(d[52]),"+f"(d[53]),"+f"(d[54]),"+f"(d[55]),"+f"(d[56]),"+f"(d[57]),"+f"(d[58]),"+f"(d[59]),"+f"(d[60]),"+f"(d[61]),"+f"(d[62]),"+f"(d[63])
    :"l"(da),"l"(db),"r"(sc));
}
__device__ __forceinline__ void wgmma_ss_n64_t1(float (&d)[32],uint64_t da,uint64_t db,int sc){
  asm volatile("{\n.reg .pred p;\nsetp.ne.b32 p,%34,0;\n"
    "wgmma.mma_async.sync.aligned.m64n64k16.f32.bf16.bf16 {%0,%1,%2,%3,%4,%5,%6,%7,%8,%9,%10,%11,%12,%13,%14,%15,%16,%17,%18,%19,%20,%21,%22,%23,%24,%25,%26,%27,%28,%29,%30,%31},%32,%33,p,1,1,0,1;\n}\n"
    :"+f"(d[0]),"+f"(d[1]),"+f"(d[2]),"+f"(d[3]),"+f"(d[4]),"+f"(d[5]),"+f"(d[6]),"+f"(d[7]),"+f"(d[8]),"+f"(d[9]),"+f"(d[10]),"+f"(d[11]),"+f"(d[12]),"+f"(d[13]),"+f"(d[14]),"+f"(d[15]),"+f"(d[16]),"+f"(d[17]),"+f"(d[18]),"+f"(d[19]),"+f"(d[20]),"+f"(d[21]),"+f"(d[22]),"+f"(d[23]),"+f"(d[24]),"+f"(d[25]),"+f"(d[26]),"+f"(d[27]),"+f"(d[28]),"+f"(d[29]),"+f"(d[30]),"+f"(d[31])
    :"l"(da),"l"(db),"r"(sc));
}

__global__ void __launch_bounds__(256) k_mod(const bf16* __restrict__ c, const bf16* __restrict__ w) {
  pdl_launch();
  __shared__ float red[8][32];
  const int t = threadIdx.x, n0 = blockIdx.x * 32 + (t & 3) * 8, r0 = t >> 2;
  uint4 v[8];
  float cs[8];
#pragma unroll
  for (int i = 0; i < 8; i++) v[i] = __ldg((const uint4*)(w + (size_t)(r0 + i * 64) * 3072 + n0));
#pragma unroll
  for (int i = 0; i < 8; i++) { float x = __bfloat162float(c[r0 + i * 64]); cs[i] = rbf(x / (1.f + __expf(-x))); }
  float a[8] = {0, 0, 0, 0, 0, 0, 0, 0};
#pragma unroll
  for (int i = 0; i < 8; i++) {
    a[0] += cs[i] * blo(v[i].x); a[1] += cs[i] * bhi(v[i].x); a[2] += cs[i] * blo(v[i].y); a[3] += cs[i] * bhi(v[i].y);
    a[4] += cs[i] * blo(v[i].z); a[5] += cs[i] * bhi(v[i].z); a[6] += cs[i] * blo(v[i].w); a[7] += cs[i] * bhi(v[i].w);
  }
#pragma unroll
  for (int j = 0; j < 8; j++) {
    a[j] += __shfl_xor_sync(~0u, a[j], 4); a[j] += __shfl_xor_sync(~0u, a[j], 8); a[j] += __shfl_xor_sync(~0u, a[j], 16);
  }
  if ((t & 31) < 4) {
#pragma unroll
    for (int j = 0; j < 8; j++) red[t >> 5][(t & 3) * 8 + j] = a[j];
  }
  __syncthreads();
  if (t < 32) {
    float s = 0;
#pragma unroll
    for (int i = 0; i < 8; i++) s += red[i][t];
    const int n = blockIdx.x * 32 + t, seg = n >> 9;
    s = rbf(s);
    if (seg == 1 || seg == 4) s = rbf(1.f + s);
    g_mod[n] = s;
  }
}

constexpr int LN_SMEM = 131072 + 4 * 24576 + 2048 + 256;
template <bool FFN>
__global__ void __launch_bounds__(384, 1) k_lngemm(const __grid_constant__ CUtensorMap mX, const __grid_constant__ CUtensorMap mB0,
                                                   const __grid_constant__ CUtensorMap mB1) {
  extern __shared__ __align__(1024) uint8_t smem[];
  const uint32_t sA = smem_u32(smem), sB = sA + 131072, sM = sB + 4 * 24576, bars = sM + 2048;
  const uint32_t bA = bars, bF = bars + 64, bE = bars + 96;
  const int tid = threadIdx.x, warp = tid >> 5, lane = tid & 31;
  const int rb = blockIdx.x >> 3, ct = blockIdx.x & 7;
  constexpr int NST = FFN ? 16 : 8, KS = FFN ? 2 : 4, BOX = FFN ? 4096 : 8192;
  pdl_launch();
  if (tid == 256) {
    for (int i = 0; i < 8; i++) mbar_init(bA + 8 * i, 1);
    for (int i = 0; i < 4; i++) { mbar_init(bF + 8 * i, 1); mbar_init(bE + 8 * i, 8); }
    fence_init();
  }
  __syncthreads();
  if (warp >= 8) {
    asm volatile("setmaxnreg.dec.sync.aligned.u32 40;");
    if (tid == 256) {
      auto loadB = [&](int s) {
        const uint32_t d = sB + (s & 3) * 24576, b = bF + (s & 3) * 8;
        mbar_expect(b, 24576);
        for (int j = 0; j < 3; j++) {
          if (FFN) { tma2d(d + j * BOX, &mB0, ct * 176 + j * 64, s * 32, b); tma2d(d + (3 + j) * BOX, &mB1, ct * 176 + j * 64, s * 32, b); }
          else tma2d(d + j * BOX, &mB0, ct * 192 + j * 64, s * 64, b);
        }
      };
      if (!FFN) for (int i = 0; i < 8; i++) { mbar_expect(bA + 8 * i, 16384); tma2d(sA + i * 16384, &mX, i * 64, rb * 128, bA + 8 * i); }
      for (int s = 0; s < 4; s++) loadB(s);
      if (FFN) {
        pdl_wait();
        for (int i = 0; i < 8; i++) { mbar_expect(bA + 8 * i, 16384); bulk_load(sA + i * 16384, g_x1 + (rb * 64 + i * 8) * 1024, 16384, bA + 8 * i); }
      }
      for (int s = 4; s < NST; s++) { mbar_wait(bE + (s & 3) * 8, ((s >> 2) - 1) & 1); loadB(s); }
    }
  } else {
  asm volatile("setmaxnreg.inc.sync.aligned.u32 232;");
  const int g = lane >> 2, t = lane & 3;
  const int lr = warp * 16 + (lane & 7) + ((lane >> 3) & 1) * 8;
  auto aaddr = [&](int ks) -> uint32_t {
    if (FFN) return sA + (ks * 2 + (lane >> 4)) * 2048 + lr * 16;
    return sA + (ks >> 2) * 16384 + lr * 128 + ((((ks & 3) * 2 + (lane >> 4)) ^ (lr & 7)) << 4);
  };
  const int row0 = rb * 128 + warp * 16 + g;
  float rs0, rs1, nm0, nm1;
  if (!FFN) {
    float s0 = 0, s1 = 0;
#pragma unroll 4
    for (int ks = 0; ks < 32; ks++) {
      if ((ks & 3) == 0) mbar_wait(bA + 2 * ks, 0);
      uint32_t r[4]; ldsm4(aaddr(ks), r);
      s0 += (blo(r[0]) + bhi(r[0])) + (blo(r[2]) + bhi(r[2]));
      s1 += (blo(r[1]) + bhi(r[1])) + (blo(r[3]) + bhi(r[3]));
    }
    const float m0 = qsum(s0) * (1.f / 512), m1 = qsum(s1) * (1.f / 512);
    float v0 = 0, v1 = 0, v2 = 0, v3 = 0;
#pragma unroll 4
    for (int ks = 0; ks < 32; ks++) {
      uint32_t r[4]; ldsm4(aaddr(ks), r);
      float d;
      d = blo(r[0]) - m0; v0 += d * d; d = bhi(r[0]) - m0; v2 += d * d; d = blo(r[2]) - m0; v0 += d * d; d = bhi(r[2]) - m0; v2 += d * d;
      d = blo(r[1]) - m1; v1 += d * d; d = bhi(r[1]) - m1; v3 += d * d; d = blo(r[3]) - m1; v1 += d * d; d = bhi(r[3]) - m1; v3 += d * d;
    }
    rs0 = rsqrtf(qsum(v0 + v2) * (1.f / 512) + 1e-5f); rs1 = rsqrtf(qsum(v1 + v3) * (1.f / 512) + 1e-5f);
    nm0 = -m0 * rs0; nm1 = -m1 * rs1;
    pdl_wait();
  } else {
    pdl_wait();
    const float4 p0 = *(const float4*)(g_st + row0 * 8 + t * 2), p1 = *(const float4*)(g_st + (row0 + 8) * 8 + t * 2);
    const float m0 = qsum(p0.x + p0.z) * 0.125f, m1 = qsum(p1.x + p1.z) * 0.125f;
    const float v0 = qsum(p0.y + p0.w + 64.f * ((p0.x - m0) * (p0.x - m0) + (p0.z - m0) * (p0.z - m0)));
    const float v1 = qsum(p1.y + p1.w + 64.f * ((p1.x - m1) * (p1.x - m1) + (p1.z - m1) * (p1.z - m1)));
    rs0 = rsqrtf(v0 * (1.f / 512) + 1e-5f); rs1 = rsqrtf(v1 * (1.f / 512) + 1e-5f);
    nm0 = -m0 * rs0; nm1 = -m1 * rs1;
  }
  {
    const float2 sh = *(const float2*)(g_mod + (FFN ? 1536 : 0) + tid * 2), sc = *(const float2*)(g_mod + (FFN ? 2048 : 512) + tid * 2);
    uint32_t* m = (uint32_t*)(smem + (sM - sA)) + (tid >> 3) * 16 + (tid & 3) * 4 + ((tid >> 2) & 1);
    m[0] = pack_rn(sc.x, sc.y); m[2] = pack_rn(sh.x, sh.y);
    asm volatile("bar.sync 1,256;" ::: "memory");
  }
  constexpr int NA = FFN ? 88 : 96;
  float acc0[NA], acc1[FFN ? 88 : 1];
  uint32_t a[2][4];
  auto prep = [&](int ks, uint32_t(&o)[4]) {
    if (FFN && (ks & 3) == 0) mbar_wait(bA + 2 * ks, 0);
    uint32_t r[4]; ldsm4(aaddr(ks), r);
    const uint4 m = *(const uint4*)(smem + (sM - sA) + ks * 64 + t * 16);
#pragma unroll
    for (int i = 0; i < 4; i++) {
      const float rs = (i & 1) ? rs1 : rs0, nm = (i & 1) ? nm1 : nm0;
      const uint32_t n = pack_rn(fmaf(blo(r[i]), rs, nm), fmaf(bhi(r[i]), rs, nm));
      asm("fma.rn.bf16x2 %0,%1,%2,%3;" : "=r"(o[i]) : "r"(n), "r"(i < 2 ? m.x : m.y), "r"(i < 2 ? m.z : m.w));
    }
  };
  prep(0, a[0]);
#pragma unroll 1
  for (int s = 0; s < NST; s++) {
    mbar_wait(bF + (s & 3) * 8, (s >> 2) & 1);
    const uint64_t db = mk_desc(sB + (s & 3) * 24576, BOX, 1024, 1);
#pragma unroll
    for (int k = 0; k < KS; k++) {
      const int ks = s * KS + k;
      uint32_t(&c)[4] = a[k & 1];
      wg_fence();
      if constexpr (FFN) {
        wgmma_rs_n176_t1(acc0, c[0], c[1], c[2], c[3], db + k * 128, ks);
        wgmma_rs_n176_t1(acc1, c[0], c[1], c[2], c[3], db + k * 128 + 3 * BOX / 16, ks);
      } else {
        wgmma_rs_n192_t1(acc0, c[0], c[1], c[2], c[3], db + k * 128, ks);
      }
      wg_commit();
      wg_wait<1>();
      if (k == 0 && s > 0 && lane == 0) mbar_arrive(bE + ((s - 1) & 3) * 8);
      if (ks < 31) prep(ks + 1, a[(k + 1) & 1]);
    }
  }
  wg_wait<0>();
  reg_fence(acc0);
  if constexpr (FFN) {
    reg_fence(acc1);
    uint32_t* o = (uint32_t*)g_h + ((rb * 172 + ct * 22) * 128 + warp * 16 + g) * 4 + t;
#pragma unroll
    for (int j = 0; j < 22; j++) {
      if (ct * 22 + j < 172) {
        float h[4];
#pragma unroll
        for (int i = 0; i < 4; i++) { const float x = acc0[4 * j + i]; h[i] = __fdividef(x, 1.f + ex2(-1.4426950408889634f * x)) * acc1[4 * j + i]; }
        o[j * 512] = pack_rn(h[0], h[1]);
        o[j * 512 + 32] = pack_rn(h[2], h[3]);
      }
    }
  } else {
    uint32_t* o = (uint32_t*)g_qkv + (ct * 24 * 2048 + row0) * 4 + t;
#pragma unroll
    for (int j = 0; j < 24; j += 2) {
      const int G = ct * 24 + j;
      const float sc = G < 64 ? 0.25f * 1.4426950408889634f : 1.f;
      uint32_t p[4];
#pragma unroll
      for (int i = 0; i < 4; i++) p[i] = pack_rn(acc0[4 * j + 2 * i] * sc, acc0[4 * j + 2 * i + 1] * sc);
      o[j * 8192] = p[0]; o[j * 8192 + 32] = p[1]; o[(j + 1) * 8192] = p[2]; o[(j + 1) * 8192 + 32] = p[3];
      if (G >= 64 && G < 128) {
        float n0 = blo(p[0]) * blo(p[0]) + bhi(p[0]) * bhi(p[0]) + blo(p[2]) * blo(p[2]) + bhi(p[2]) * bhi(p[2]);
        float n1 = blo(p[1]) * blo(p[1]) + bhi(p[1]) * bhi(p[1]) + blo(p[3]) * blo(p[3]) + bhi(p[3]) * bhi(p[3]);
        n0 = qsum(n0); n1 = qsum(n1);
        const uint32_t mx = __reduce_max_sync(~0u, max(__float_as_uint(n0), __float_as_uint(n1)));
        if (lane == 0) g_kmax[((G - 64) >> 1) * 128 + rb * 8 + warp] = __uint_as_float(mx);
      }
    }
  }
}
}

#define POLYMASK 0x52A552A5u
#define AUG 0
constexpr int AT_SMEM = 5 * 32768 + 256;
__device__ __forceinline__ uint32_t exp2_pair_fma(float s0, float s1, float c) {
  float y0, y1;
  asm("fma.rn.sat.f32 %0,%1,0f00008000,%2;" : "=f"(y0) : "f"(s0), "f"(c));
  asm("fma.rn.sat.f32 %0,%1,0f00008000,%2;" : "=f"(y1) : "f"(s1), "f"(c));
  const float u0 = __uint_as_float((__float_as_uint(y0) & 0x7FFFu) | 0x43800000u), u1 = __uint_as_float((__float_as_uint(y1) & 0x7FFFu) | 0x43800000u);
  const float l0 = fmaf(u0, 0.427682191f, -109.07412f), l1 = fmaf(u1, 0.427682191f, -109.07412f);
  const float p0 = fmaf(fmaf(l0, l0, 1.11545753f), l0, 0.469651312f), p1 = fmaf(fmaf(l1, l1, 1.11545753f), l1, 0.469651312f);
  const uint32_t e = __byte_perm(__float_as_uint(y0), __float_as_uint(y1), 0x6521), m = pack_rz(p0, p1);
  return (e & 0x7F807F80u) | (m & 0x807F807Fu);
}
#define NK 64
#define PP 0
template <uint32_t MASK, bool AG>
__device__ __forceinline__ void attn_pass(float (&o)[12], const uint32_t (&q)[4], float m0, float m1, uint32_t sK, uint32_t bars, bool first) {
  const uint64_t dk = mk_desc(sK, 32768, 128, 0), dv = mk_desc(sK + 65536, 128, 32768, 0), d1 = mk_desc(sK + 131072, 128, 128, 0);
  const float c0 = (AG ? 127.f : 127.f - m0) * __uint_as_float(0x8000u), c1 = (AG ? 127.f : 127.f - m1) * __uint_as_float(0x8000u);
  const uint32_t am0 = (threadIdx.x & 3) ? 0u : (__float_as_uint(-m0) >> 16), am1 = (threadIdx.x & 3) ? 0u : (__float_as_uint(-m1) >> 16);
  constexpr int NS = NK / 2, NP = NK / 4, NI = 2048 / NK;
  auto qk = [&](float (&s)[NS], int i) {
    if (AG) wgmma_rs_n64_t0(s, am0, am1, 0, 0, d1, 0);
    wgmma_rs_n64_t0(s, q[0], q[1], q[2], q[3], dk + i * NK, AG);
  };
  auto softmax = [&](float (&s)[NS], uint32_t (&p)[NP], uint32_t mask) {
    reg_fence(s);
#pragma unroll
    for (int j = 0; j < NP; j++) {
      if ((mask >> j) & 1) p[j] = exp2_pair_fma(s[2 * j], s[2 * j + 1], (j & 1) ? c1 : c0);
      else if (AG) p[j] = pack_rz(ex2(s[2 * j]), ex2(s[2 * j + 1]));
      else { const float m = (j & 1) ? m1 : m0; p[j] = pack_rz(ex2(s[2 * j] - m), ex2(s[2 * j + 1] - m)); }
    }
#pragma unroll
    for (int j = 0; j < NP; j++) asm volatile("" : "+r"(p[j])::"memory");
  };
  auto pv = [&](uint32_t (&p)[NP], int i) {
#pragma unroll
    for (int k = 0; k < NK / 16; k++) wgmma_rs_n24_t1(o, p[4 * k], p[4 * k + 1], p[4 * k + 2], p[4 * k + 3], dv + i * NK + k * 16, 1);
  };
  auto ld = [&](int i) { if (first && (i & (NI / 4 - 1)) == 0) mbar_wait(bars + i / (NI / 4) * 8, 0); };
  constexpr uint32_t M0 = MASK, M1 = NK == 128 ? MASK : MASK >> NP;
  zero(o);
  ld(0);
  float s[NS];
  zero(s);
  uint32_t p[NP];
  wg_fence(); qk(s, 0); wg_commit(); wg_wait<0>(); softmax(s, p, M0);
#pragma unroll 1
  for (int i = 0; i < NI - 2; i += 2) {
    wg_fence(); qk(s, i + 1); pv(p, i); wg_commit(); wg_wait<0>(); softmax(s, p, M1);
    ld(i + 2);
    wg_fence(); qk(s, i + 2); pv(p, i + 1); wg_commit(); wg_wait<0>(); softmax(s, p, M0);
  }
  wg_fence(); qk(s, NI - 1); pv(p, NI - 2); wg_commit(); wg_wait<0>(); softmax(s, p, M1);
  wg_fence(); pv(p, NI - 1); wg_commit();
  wg_wait<0>();
  reg_fence(o);
}
__device__ __forceinline__ void attn_safe(float (&o)[12], const uint32_t (&q)[4], uint32_t sK) {
  const uint64_t dk = mk_desc(sK, 32768, 128, 0);
  float m0 = -INFINITY, m1 = -INFINITY, s[64];
  zero(s);
#pragma unroll 1
  for (int i = 0; i < 16; i++) {
    wg_fence();
    wgmma_rs_n128_t0(s, q[0], q[1], q[2], q[3], dk + i * 128, 0);
    wg_commit();
    wg_wait<0>();
    reg_fence(s);
#pragma unroll
    for (int j = 0; j < 16; j++) { m0 = fmaxf(m0, fmaxf(s[4 * j], s[4 * j + 1])); m1 = fmaxf(m1, fmaxf(s[4 * j + 2], s[4 * j + 3])); }
  }
  m0 = fmaxf(m0, __shfl_xor_sync(~0u, m0, 1)); m0 = fmaxf(m0, __shfl_xor_sync(~0u, m0, 2));
  m1 = fmaxf(m1, __shfl_xor_sync(~0u, m1, 1)); m1 = fmaxf(m1, __shfl_xor_sync(~0u, m1, 2));
  attn_pass<0u, false>(o, q, m0, m1, sK, 0, false);
}
__global__ void __launch_bounds__(512, 1) k_attn(const bf16* wo, const bf16* w1, const bf16* w3, const bf16* w2) {
  extern __shared__ __align__(1024) uint8_t smem[];
  const uint32_t sK = smem_u32(smem), bars = sK + 5 * 32768;
  const int tid = threadIdx.x, warp = tid >> 5, lane = tid & 31, g = lane >> 2, t = lane & 3, wg = warp >> 2;
  const int h = blockIdx.x >> 2, qb = blockIdx.x & 3;
  pdl_launch();
  if (tid == 0) { for (int i = 0; i < 4; i++) mbar_init(bars + 8 * i, 1); fence_init(); }
#pragma unroll
  for (int i = 0; i < 4; i++) *(uint4*)(smem + 131072 + i * 8192 + tid * 16) = make_uint4(0x3F803F80u, 0x3F803F80u, 0x3F803F80u, 0x3F803F80u);
  fence_async();
  __syncthreads();
  pdl_wait();
  if (tid == 0) {
    for (int c = 0; c < 4; c++) {
      mbar_expect(bars + 8 * c, 32768);
      for (int pl = 0; pl < 4; pl++)
        bulk_load(sK + pl * 32768 + c * 8192, g_qkv + ((64 + (pl >> 1) * 64 + h * 2 + (pl & 1)) * 2048 + c * 512) * 8, 8192, bars + 8 * c);
    }
  }
  if (tid == 32) {
    l2_prefetch((const char*)wo + blockIdx.x * 4096, 4096);
    l2_prefetch((const char*)w1 + blockIdx.x * 11008, 11008);
    l2_prefetch((const char*)w3 + blockIdx.x * 11008, 11008);
    l2_prefetch((const char*)w2 + blockIdx.x * 11008, 11008);
  }
  const uint4 km4 = *(const uint4*)(g_kmax + h * 128 + lane * 4);
  const float kmax = __uint_as_float(__reduce_max_sync(~0u, max(max(km4.x, km4.y), max(km4.z, km4.w))));
#pragma unroll 1
  for (int tile = 0; tile < 2; tile++) {
    const int row = qb * 512 + tile * 256 + warp * 16 + g;
    const uint32_t* qp = (const uint32_t*)g_qkv + (h * 2 * 2048 + row) * 4 + t;
    uint32_t q[4] = {qp[0], qp[32], qp[8192], qp[8192 + 32]};
    const float n0 = qsum(blo(q[0]) * blo(q[0]) + bhi(q[0]) * bhi(q[0]) + blo(q[2]) * blo(q[2]) + bhi(q[2]) * bhi(q[2]));
    const float n1 = qsum(blo(q[1]) * blo(q[1]) + bhi(q[1]) * bhi(q[1]) + blo(q[3]) * blo(q[3]) + bhi(q[3]) * bhi(q[3]));
    const float b0 = sqrtf(n0 * kmax) * 1.001f, b1 = sqrtf(n1 * kmax) * 1.001f;
    float m0 = ceilf(b0 - 100.f), m1 = ceilf(b1 - 100.f);
    if (AUG) { m0 = __bfloat162float(__float2bfloat16_ru(m0)); m1 = __bfloat162float(__float2bfloat16_ru(m1)); }
    float o[12];
    attn_pass<POLYMASK, AUG>(o, q, m0, m1, sK, bars, tile == 0);
    bool ok = b0 < 1e4f && b1 < 1e4f && o[8] >= 0x1p-90f && o[10] >= 0x1p-90f;
#pragma unroll
    for (int i = 0; i < 12; i++) ok = ok && fabsf(o[i]) < INFINITY;
    uint32_t all;
    asm volatile("{\n.reg .pred p,r;\nsetp.ne.b32 p,%1,0;\nbar.red.and.pred r,%2,128,p;\nselp.u32 %0,1,0,r;\n}\n" : "=r"(all) : "r"((uint32_t)ok), "r"(wg + 1) : "memory");
    if (!all) attn_safe(o, q, sK);
    const float r0 = 1.f / o[8], r1 = 1.f / o[10];
    uint32_t* op = (uint32_t*)g_o + (((row >> 7) * 64 + h * 2) * 128 + (row & 127)) * 4 + t;
    op[0] = pack_rn(o[0] * r0, o[1] * r0); op[32] = pack_rn(o[2] * r1, o[3] * r1);
    op[512] = pack_rn(o[4] * r0, o[5] * r0); op[512 + 32] = pack_rn(o[6] * r1, o[7] * r1);
  }
}

constexpr int WO_SMEM = 131072 + 65536 + 256;
__global__ void __launch_bounds__(256, 1) k_wo(const __grid_constant__ CUtensorMap mW, const bf16* __restrict__ x) {
  extern __shared__ __align__(1024) uint8_t smem[];
  const uint32_t sA = smem_u32(smem), sB = sA + 131072, bars = sB + 65536;
  const int tid = threadIdx.x, warp = tid >> 5, lane = tid & 31, g = lane >> 2, t = lane & 3;
  const int rb = blockIdx.x >> 3, ct = blockIdx.x & 7;
  pdl_launch();
  if (tid == 0) {
    for (int i = 0; i < 8; i++) mbar_init(bars + 8 * i, 1);
    fence_init();
    for (int i = 0; i < 8; i++) { mbar_expect(bars + 8 * i, 24576); tma2d(sB + i * 8192, &mW, ct * 64, i * 64, bars + 8 * i); }
  }
  const int lrow = warp * 16 + g;
  uint32_t xr[16];
  const uint32_t* xp = (const uint32_t*)(x + (rb * 128 + lrow) * 512 + ct * 64) + t;
#pragma unroll
  for (int j = 0; j < 8; j++) { xr[2 * j] = __ldg(xp + j * 4); xr[2 * j + 1] = __ldg(xp + j * 4 + 8 * 256); }
  __syncthreads();
  pdl_wait();
  if (tid == 0) for (int i = 0; i < 8; i++) bulk_load(sA + i * 16384, g_o + (rb * 64 + i * 8) * 1024, 16384, bars + 8 * i);
  float2 ga[8];
#pragma unroll
  for (int j = 0; j < 8; j++) ga[j] = *(const float2*)(g_mod + 1024 + ct * 64 + j * 8 + t * 2);
  float acc[32];
  const uint64_t da = mk_desc(sA + (warp >> 2) * 1024, 2048, 128, 0), db = mk_desc(sB, 8192, 1024, 1);
#pragma unroll
  for (int c = 0; c < 8; c++) {
    mbar_wait(bars + 8 * c, 0);
    wg_fence();
#pragma unroll
    for (int k = 0; k < 4; k++) wgmma_ss_n64_t1(acc, da + (c * 4 + k) * 256, db + (c * 4 + k) * 128, c + k);
    wg_commit();
  }
  wg_wait<0>();
  reg_fence(acc);
  uint32_t* o = (uint32_t*)g_x1 + ((rb * 64 + ct * 8) * 128 + lrow) * 4 + t;
  float s0 = 0, s1 = 0;
#pragma unroll
  for (int j = 0; j < 8; j++) {
    xr[2 * j] = pack_rn(fmaf(ga[j].x, acc[4 * j], blo(xr[2 * j])), fmaf(ga[j].y, acc[4 * j + 1], bhi(xr[2 * j])));
    xr[2 * j + 1] = pack_rn(fmaf(ga[j].x, acc[4 * j + 2], blo(xr[2 * j + 1])), fmaf(ga[j].y, acc[4 * j + 3], bhi(xr[2 * j + 1])));
    o[j * 512] = xr[2 * j]; o[j * 512 + 32] = xr[2 * j + 1];
    s0 += blo(xr[2 * j]) + bhi(xr[2 * j]); s1 += blo(xr[2 * j + 1]) + bhi(xr[2 * j + 1]);
  }
  const float m0 = qsum(s0) * (1.f / 64), m1 = qsum(s1) * (1.f / 64);
  float v0 = 0, v1 = 0;
#pragma unroll
  for (int j = 0; j < 8; j++) {
    float d;
    d = blo(xr[2 * j]) - m0; v0 += d * d; d = bhi(xr[2 * j]) - m0; v0 += d * d;
    d = blo(xr[2 * j + 1]) - m1; v1 += d * d; d = bhi(xr[2 * j + 1]) - m1; v1 += d * d;
  }
  v0 = qsum(v0); v1 = qsum(v1);
  if (t == 0) g_st[(rb * 128 + lrow) * 8 + ct] = make_float2(m0, v0);
  if (t == 1) g_st[(rb * 128 + lrow + 8) * 8 + ct] = make_float2(m1, v1);
}

constexpr int W2_SMEM = 6 * 32768 + 32768 + 256;
__global__ void __cluster_dims__(2, 1, 1) __launch_bounds__(288, 1) k_w2(const __grid_constant__ CUtensorMap mW, bf16* __restrict__ out) {
  extern __shared__ __align__(1024) uint8_t smem[];
  const uint32_t sR = smem_u32(smem), sX = sR + 6 * 32768, bF = sX + 32768, bE = bF + 48;
  const int tid = threadIdx.x, warp = tid >> 5, lane = tid & 31, g = lane >> 2, t = lane & 3;
  const int kh = blockIdx.x & 1, ct = (blockIdx.x >> 1) & 3, rb = blockIdx.x >> 3;
  pdl_launch();
  if (tid == 256) {
    for (int i = 0; i < 6; i++) { mbar_init(bF + 8 * i, 1); mbar_init(bE + 8 * i, 8); }
    fence_init();
  }
  __syncthreads();
  asm volatile("barrier.cluster.arrive.relaxed.aligned;" ::: "memory");
  if (warp == 8) {
    if (lane == 0) {
      auto abytes = [&](int s) { return (kh == 1 && s == 10) ? 8192 : 16384; };
      auto loadB = [&](int s) {
        const int st = s % 6;
        mbar_expect(bF + 8 * st, 16384 + abytes(s));
        for (int j = 0; j < 2; j++) tma2d(sR + st * 32768 + 16384 + j * 8192, &mW, ct * 128 + j * 64, kh * 704 + s * 64, bF + 8 * st);
      };
      auto loadA = [&](int s) { bulk_load(sR + (s % 6) * 32768, g_h + (rb * 172 + kh * 88 + s * 8) * 1024, abytes(s), bF + 8 * (s % 6)); };
      for (int s = 0; s < 6; s++) loadB(s);
      pdl_wait();
      for (int s = 0; s < 6; s++) loadA(s);
      for (int s = 6; s < 11; s++) { mbar_wait(bE + 8 * (s - 6), 0); loadB(s); loadA(s); }
    }
    __syncwarp();
    asm volatile("barrier.cluster.wait.aligned;" ::: "memory");
    asm volatile("barrier.cluster.arrive.release.aligned;" ::: "memory");
    asm volatile("barrier.cluster.wait.acquire.aligned;" ::: "memory");
    return;
  }
  pdl_wait();
  const int lrow = warp * 16 + g;
  uint32_t xr[16];
  float2 gb[8];
  const uint32_t* xp = (const uint32_t*)g_x1 + ((rb * 64 + ct * 16 + kh * 8) * 128 + lrow) * 4 + t;
#pragma unroll
  for (int j = 0; j < 8; j++) {
    xr[2 * j] = xp[j * 512]; xr[2 * j + 1] = xp[j * 512 + 32];
    gb[j] = *(const float2*)(g_mod + 2560 + ct * 128 + kh * 64 + j * 8 + t * 2);
  }
  float acc[64];
#pragma unroll 1
  for (int s = 0; s < 11; s++) {
    const int st = s % 6;
    mbar_wait(bF + 8 * st, s >= 6);
    const uint64_t da = mk_desc(sR + st * 32768 + (warp >> 2) * 1024, 2048, 128, 0), db = mk_desc(sR + st * 32768 + 16384, 8192, 1024, 1);
    wg_fence();
    wgmma_ss_n128_t1(acc, da, db, s);
    wgmma_ss_n128_t1(acc, da + 256, db + 128, 1);
    wgmma_ss_n128_t1(acc, da + 512, db + 256, 1);
    wgmma_ss_n128_t1(acc, da + 768, db + 384, 1);
    wg_commit();
    wg_wait<1>();
    if (s > 0 && s < 6 && lane == 0) mbar_arrive(bE + 8 * (s - 1));
  }
  wg_wait<0>();
  reg_fence(acc);
  asm volatile("barrier.cluster.wait.aligned;" ::: "memory");
  uint32_t rem;
  asm("mapa.shared::cluster.u32 %0,%1,%2;" : "=r"(rem) : "r"(sX + tid * 16), "r"(kh ^ 1));
#pragma unroll
  for (int j = 0; j < 8; j++) {
    float v[4];
#pragma unroll
    for (int i = 0; i < 4; i++) { v[i] = kh ? acc[4 * j + i] : acc[32 + 4 * j + i]; acc[4 * j + i] = kh ? acc[32 + 4 * j + i] : acc[4 * j + i]; }
    asm volatile("st.shared::cluster.v4.f32 [%0],{%1,%2,%3,%4};" ::"r"(rem + j * 4096), "f"(v[0]), "f"(v[1]), "f"(v[2]), "f"(v[3]) : "memory");
  }
  asm volatile("barrier.cluster.arrive.release.aligned;" ::: "memory");
  asm volatile("barrier.cluster.wait.acquire.aligned;" ::: "memory");
  uint32_t* o = (uint32_t*)(out + (rb * 128 + lrow) * 512 + ct * 128 + kh * 64) + t;
#pragma unroll
  for (int j = 0; j < 8; j++) {
    const float4 p = *(const float4*)(smem + 6 * 32768 + j * 4096 + tid * 16);
    o[j * 4] = pack_rn(fmaf(gb[j].x, acc[4 * j] + p.x, blo(xr[2 * j])), fmaf(gb[j].y, acc[4 * j + 1] + p.y, bhi(xr[2 * j])));
    o[j * 4 + 2048] = pack_rn(fmaf(gb[j].x, acc[4 * j + 2] + p.z, blo(xr[2 * j + 1])), fmaf(gb[j].y, acc[4 * j + 3] + p.w, bhi(xr[2 * j + 1])));
  }
}

typedef CUresult (*EncFn)(CUtensorMap*, CUtensorMapDataType, cuuint32_t, void*, const cuuint64_t*, const cuuint64_t*, const cuuint32_t*,
                          const cuuint32_t*, CUtensorMapInterleave, CUtensorMapSwizzle, CUtensorMapL2promotion, CUtensorMapFloatOOBfill);
static void mk_map(EncFn f, CUtensorMap* m, const void* p, int rows, int cols, int box_rows) {
  cuuint64_t dim[2] = {(cuuint64_t)cols, (cuuint64_t)rows}, str[1] = {(cuuint64_t)cols * 2};
  cuuint32_t box[2] = {64, (cuuint32_t)box_rows}, es[2] = {1, 1};
  f(m, CU_TENSOR_MAP_DATA_TYPE_BFLOAT16, 2, (void*)p, dim, str, box, es, CU_TENSOR_MAP_INTERLEAVE_NONE, CU_TENSOR_MAP_SWIZZLE_128B,
    CU_TENSOR_MAP_L2_PROMOTION_L2_128B, CU_TENSOR_MAP_FLOAT_OOB_FILL_NONE);
}
template <typename... KA, typename... A>
static void launch(void (*k)(KA...), int grid, int block, int smem, bool pdl, A... args) {
  cudaLaunchConfig_t cfg = {};
  cfg.gridDim = dim3(grid); cfg.blockDim = dim3(block); cfg.dynamicSmemBytes = smem; cfg.stream = cudaStreamPerThread;
  cudaLaunchAttribute at[1];
  at[0].id = cudaLaunchAttributeProgrammaticStreamSerialization; at[0].val.programmaticStreamSerializationAllowed = 1;
  cfg.attrs = at; cfg.numAttrs = pdl ? 1 : 0;
  cudaLaunchKernelEx(&cfg, k, args...);
}
extern "C" void kernel_launch(void* const* d_in, const int* in_sizes, int n_in, void* d_out, int out_size) {
  const bf16 *x = (const bf16*)d_in[0], *wqkv = (const bf16*)d_in[1], *wo = (const bf16*)d_in[2], *w1 = (const bf16*)d_in[4],
             *w3 = (const bf16*)d_in[5], *w2 = (const bf16*)d_in[6], *c = (const bf16*)d_in[7], *wmod = (const bf16*)d_in[8];
  void* fp = nullptr;
  cudaDriverEntryPointQueryResult qr;
  cudaGetDriverEntryPoint("cuTensorMapEncodeTiled", &fp, cudaEnableDefault, &qr);
  EncFn f = (EncFn)fp;
  CUtensorMap mX, mQ, mO, m1, m3, m2;
  mk_map(f, &mX, x, S_, D_, 128); mk_map(f, &mQ, wqkv, D_, 3 * D_, 64); mk_map(f, &mO, wo, D_, D_, 64);
  mk_map(f, &m1, w1, D_, F_, 32); mk_map(f, &m3, w3, D_, F_, 32); mk_map(f, &m2, w2, F_, D_, 64);
  cudaFuncSetAttribute(k_lngemm<false>, cudaFuncAttributeMaxDynamicSharedMemorySize, LN_SMEM);
  cudaFuncSetAttribute(k_lngemm<true>, cudaFuncAttributeMaxDynamicSharedMemorySize, LN_SMEM);
  cudaFuncSetAttribute(k_attn, cudaFuncAttributeMaxDynamicSharedMemorySize, AT_SMEM);
  cudaFuncSetAttribute(k_wo, cudaFuncAttributeMaxDynamicSharedMemorySize, WO_SMEM);
  cudaFuncSetAttribute(k_w2, cudaFuncAttributeMaxDynamicSharedMemorySize, W2_SMEM);
  launch(k_mod, 96, 256, 0, false, c, wmod);
  launch(k_lngemm<false>, 128, 384, LN_SMEM, true, mX, mQ, mQ);
  launch(k_attn, 128, 512, AT_SMEM, true, wo, w1, w3, w2);
  launch(k_wo, 128, 256, WO_SMEM, true, mO, x);
  launch(k_lngemm<true>, 128, 384, LN_SMEM, true, mX, m1, m3);
  launch(k_w2, 128, 288, W2_SMEM, true, m2, (bf16*)d_out);
}
```

```cpp
#include <cuda_runtime.h>
#include <cuda_bf16.h>
#include <cuda.h>
#include <stdint.h>
typedef __nv_bfloat16 bf16;
constexpr int S_ = 2048, D_ = 512, F_ = 1376;
__device__ __align__(1024) float g_mod[3072];
__device__ __align__(1024) bf16 g_qkv[192 * 2048 * 8];
__device__ __align__(1024) float g_kmax[32 * 128];
__device__ __align__(1024) bf16 g_o[16 * 64 * 128 * 8];
__device__ __align__(1024) bf16 g_x1[16 * 64 * 128 * 8];
__device__ __align__(1024) float2 g_st[2048 * 8];
__device__ __align__(1024) bf16 g_h[16 * 172 * 128 * 8];

__device__ __forceinline__ uint32_t smem_u32(const void* p) { return (uint32_t)__cvta_generic_to_shared(p); }
__device__ __forceinline__ void mbar_init(uint32_t b, int n) { asm volatile("mbarrier.init.shared::cta.b64 [%0],%1;" ::"r"(b), "r"(n) : "memory"); }
__device__ __forceinline__ void mbar_expect(uint32_t b, int bytes) { asm volatile("mbarrier.arrive.expect_tx.shared::cta.b64 _,[%0],%1;" ::"r"(b), "r"(bytes) : "memory"); }
__device__ __forceinline__ void mbar_arrive(uint32_t b) { asm volatile("mbarrier.arrive.shared::cta.b64 _,[%0];" ::"r"(b) : "memory"); }
__device__ __forceinline__ void mbar_wait(uint32_t b, int parity) {
  asm volatile("{\n.reg .pred p;\n.reg .u32 n;\nmov.u32 n,0;\nLW:\nmbarrier.try_wait.parity.shared::cta.b64 p,[%0],%1;\n@p bra LD;\n"
               "add.u32 n,n,1;\nsetp.lt.u32 p,n,4194304;\n@p bra LW;\nLD:\n}\n" ::"r"(b), "r"(parity) : "memory");
}
__device__ __forceinline__ void fence_init() { asm volatile("fence.mbarrier_init.release.cluster;" ::: "memory"); }
__device__ __forceinline__ void fence_async() { asm volatile("fence.proxy.async.shared::cta;" ::: "memory"); }
__device__ __forceinline__ void bulk_load(uint32_t dst, const void* src, int bytes, uint32_t bar) {
  asm volatile("cp.async.bulk.shared::cluster.global.mbarrier::complete_tx::bytes [%0],[%1],%2,[%3];" ::"r"(dst), "l"(src), "r"(bytes), "r"(bar) : "memory");
}
__device__ __forceinline__ void tma2d(uint32_t dst, const CUtensorMap* m, int c0, int c1, uint32_t bar) {
  asm volatile("cp.async.bulk.tensor.2d.shared::cluster.global.mbarrier::complete_tx::bytes [%0],[%1,{%3,%4}],[%2];" ::"r"(dst), "l"(m), "r"(bar), "r"(c0), "r"(c1) : "memory");
}
__device__ __forceinline__ void l2_prefetch(const void* p, int bytes) { asm volatile("cp.async.bulk.prefetch.L2.global [%0],%1;" ::"l"(p), "r"(bytes) : "memory"); }
__device__ __forceinline__ void pdl_launch() { asm volatile("griddepcontrol.launch_dependents;" ::: "memory"); }
__device__ __forceinline__ void pdl_wait() { asm volatile("griddepcontrol.wait;" ::: "memory"); }
__device__ __forceinline__ void wg_fence() { asm volatile("wgmma.fence.sync.aligned;" ::: "memory"); }
__device__ __forceinline__ void wg_commit() { asm volatile("wgmma.commit_group.sync.aligned;" ::: "memory"); }
template <int N> __device__ __forceinline__ void wg_wait() { asm volatile("wgmma.wait_group.sync.aligned %0;" ::"n"(N) : "memory"); }
template <int N> __device__ __forceinline__ void reg_fence(float (&d)[N]) {
#pragma unroll
  for (int i = 0; i < N; i++) asm volatile("" : "+f"(d[i])::"memory");
}
template <int N> __device__ __forceinline__ void zero(float (&d)[N]) {
#pragma unroll
  for (int i = 0; i < N; i++) d[i] = 0.f;
  reg_fence(d);
}
__device__ __forceinline__ uint64_t mk_desc(uint32_t addr, uint32_t lbo, uint32_t sbo, uint32_t mode) {
  return (uint64_t)((addr >> 4) & 0x3FFF) | ((uint64_t)(lbo >> 4) << 16) | ((uint64_t)(sbo >> 4) << 32) | ((uint64_t)mode << 62);
}
__device__ __forceinline__ void ldsm4(uint32_t a, uint32_t (&r)[4]) {
  asm volatile("ldmatrix.sync.aligned.m8n8.x4.shared.b16 {%0,%1,%2,%3},[%4];" : "=r"(r[0]), "=r"(r[1]), "=r"(r[2]), "=r"(r[3]) : "r"(a) : "memory");
}
__device__ __forceinline__ uint32_t pack_rn(float lo, float hi) { uint32_t r; asm("cvt.rn.bf16x2.f32 %0,%1,%2;" : "=r"(r) : "f"(hi), "f"(lo)); return r; }
__device__ __forceinline__ uint32_t pack_rz(float lo, float hi) { uint32_t r; asm("cvt.rz.bf16x2.f32 %0,%1,%2;" : "=r"(r) : "f"(hi), "f"(lo)); return r; }
__device__ __forceinline__ float blo(uint32_t u) { return __uint_as_float(u << 16); }
__device__ __forceinline__ float bhi(uint32_t u) { return __uint_as_float(u & 0xFFFF0000u); }
__device__ __forceinline__ float rbf(float x) { return __bfloat162float(__float2bfloat16_rn(x)); }
__device__ __forceinline__ float qsum(float v) { v += __shfl_xor_sync(~0u, v, 1); return v + __shfl_xor_sync(~0u, v, 2); }
__device__ __forceinline__ float ex2(float x) { float r; asm("ex2.approx.ftz.f32 %0,%1;" : "=f"(r) : "f"(x)); return r; }
__device__ __forceinline__ void wgmma_rs_n128_t0(float (&d)[64],uint32_t a0,uint32_t a1,uint32_t a2,uint32_t a3,uint64_t db,int sc){
  asm volatile("{\n.reg .pred p;\nsetp.ne.b32 p,%69,0;\n"
    "wgmma.mma_async.sync.aligned.m64n128k16.f32.bf16.bf16 {%0,%1,%2,%3,%4,%5,%6,%7,%8,%9,%10,%11,%12,%13,%14,%15,%16,%17,%18,%19,%20,%21,%22,%23,%24,%25,%26,%27,%28,%29,%30,%31,%32,%33,%34,%35,%36,%37,%38,%39,%40,%41,%42,%43,%44,%45,%46,%47,%48,%49,%50,%51,%52,%53,%54,%55,%56,%57,%58,%59,%60,%61,%62,%63},{%64,%65,%66,%67},%68,p,1,1,0;\n}\n"
    :"+f"(d[0]),"+f"(d[1]),"+f"(d[2]),"+f"(d[3]),"+f"(d[4]),"+f"(d[5]),"+f"(d[6]),"+f"(d[7]),"+f"(d[8]),"+f"(d[9]),"+f"(d[10]),"+f"(d[11]),"+f"(d[12]),"+f"(d[13]),"+f"(d[14]),"+f"(d[15]),"+f"(d[16]),"+f"(d[17]),"+f"(d[18]),"+f"(d[19]),"+f"(d[20]),"+f"(d[21]),"+f"(d[22]),"+f"(d[23]),"+f"(d[24]),"+f"(d[25]),"+f"(d[26]),"+f"(d[27]),"+f"(d[28]),"+f"(d[29]),"+f"(d[30]),"+f"(d[31]),"+f"(d[32]),"+f"(d[33]),"+f"(d[34]),"+f"(d[35]),"+f"(d[36]),"+f"(d[37]),"+f"(d[38]),"+f"(d[39]),"+f"(d[40]),"+f"(d[41]),"+f"(d[42]),"+f"(d[43]),"+f"(d[44]),"+f"(d[45]),"+f"(d[46]),"+f"(d[47]),"+f"(d[48]),"+f"(d[49]),"+f"(d[50]),"+f"(d[51]),"+f"(d[52]),"+f"(d[53]),"+f"(d[54]),"+f"(d[55]),"+f"(d[56]),"+f"(d[57]),"+f"(d[58]),"+f"(d[59]),"+f"(d[60]),"+f"(d[61]),"+f"(d[62]),"+f"(d[63])
    :"r"(a0),"r"(a1),"r"(a2),"r"(a3),"l"(db),"r"(sc));
}
__device__ __forceinline__ void wgmma_rs_n176_t1(float (&d)[88],uint32_t a0,uint32_t a1,uint32_t a2,uint32_t a3,uint64_t db,int sc){
  asm volatile("{\n.reg .pred p;\nsetp.ne.b32 p,%93,0;\n"
    "wgmma.mma_async.sync.aligned.m64n176k16.f32.bf16.bf16 {%0,%1,%2,%3,%4,%5,%6,%7,%8,%9,%10,%11,%12,%13,%14,%15,%16,%17,%18,%19,%20,%21,%22,%23,%24,%25,%26,%27,%28,%29,%30,%31,%32,%33,%34,%35,%36,%37,%38,%39,%40,%41,%42,%43,%44,%45,%46,%47,%48,%49,%50,%51,%52,%53,%54,%55,%56,%57,%58,%59,%60,%61,%62,%63,%64,%65,%66,%67,%68,%69,%70,%71,%72,%73,%74,%75,%76,%77,%78,%79,%80,%81,%82,%83,%84,%85,%86,%87},{%88,%89,%90,%91},%92,p,1,1,1;\n}\n"
    :"+f"(d[0]),"+f"(d[1]),"+f"(d[2]),"+f"(d[3]),"+f"(d[4]),"+f"(d[5]),"+f"(d[6]),"+f"(d[7]),"+f"(d[8]),"+f"(d[9]),"+f"(d[10]),"+f"(d[11]),"+f"(d[12]),"+f"(d[13]),"+f"(d[14]),"+f"(d[15]),"+f"(d[16]),"+f"(d[17]),"+f"(d[18]),"+f"(d[19]),"+f"(d[20]),"+f"(d[21]),"+f"(d[22]),"+f"(d[23]),"+f"(d[24]),"+f"(d[25]),"+f"(d[26]),"+f"(d[27]),"+f"(d[28]),"+f"(d[29]),"+f"(d[30]),"+f"(d[31]),"+f"(d[32]),"+f"(d[33]),"+f"(d[34]),"+f"(d[35]),"+f"(d[36]),"+f"(d[37]),"+f"(d[38]),"+f"(d[39]),"+f"(d[40]),"+f"(d[41]),"+f"(d[42]),"+f"(d[43]),"+f"(d[44]),"+f"(d[45]),"+f"(d[46]),"+f"(d[47]),"+f"(d[48]),"+f"(d[49]),"+f"(d[50]),"+f"(d[51]),"+f"(d[52]),"+f"(d[53]),"+f"(d[54]),"+f"(d[55]),"+f"(d[56]),"+f"(d[57]),"+f"(d[58]),"+f"(d[59]),"+f"(d[60]),"+f"(d[61]),"+f"(d[62]),"+f"(d[63]),"+f"(d[64]),"+f"(d[65]),"+f"(d[66]),"+f"(d[67]),"+f"(d[68]),"+f"(d[69]),"+f"(d[70]),"+f"(d[71]),"+f"(d[72]),"+f"(d[73]),"+f"(d[74]),"+f"(d[75]),"+f"(d[76]),"+f"(d[77]),"+f"(d[78]),"+f"(d[79]),"+f"(d[80]),"+f"(d[81]),"+f"(d[82]),"+f"(d[83]),"+f"(d[84]),"+f"(d[85]),"+f"(d[86]),"+f"(d[87])
    :"r"(a0),"r"(a1),"r"(a2),"r"(a3),"l"(db),"r"(sc));
}
__device__ __forceinline__ void wgmma_rs_n192_t1(float (&d)[96],uint32_t a0,uint32_t a1,uint32_t a2,uint32_t a3,uint64_t db,int sc){
  asm volatile("{\n.reg .pred p;\nsetp.ne.b32 p,%101,0;\n"
    "wgmma.mma_async.sync.aligned.m64n192k16.f32.bf16.bf16 {%0,%1,%2,%3,%4,%5,%6,%7,%8,%9,%10,%11,%12,%13,%14,%15,%16,%17,%18,%19,%20,%21,%22,%23,%24,%25,%26,%27,%28,%29,%30,%31,%32,%33,%34,%35,%36,%37,%38,%39,%40,%41,%42,%43,%44,%45,%46,%47,%48,%49,%50,%51,%52,%53,%54,%55,%56,%57,%58,%59,%60,%61,%62,%63,%64,%65,%66,%67,%68,%69,%70,%71,%72,%73,%74,%75,%76,%77,%78,%79,%80,%81,%82,%83,%84,%85,%86,%87,%88,%89,%90,%91,%92,%93,%94,%95},{%96,%97,%98,%99},%100,p,1,1,1;\n}\n"
    :"+f"(d[0]),"+f"(d[1]),"+f"(d[2]),"+f"(d[3]),"+f"(d[4]),"+f"(d[5]),"+f"(d[6]),"+f"(d[7]),"+f"(d[8]),"+f"(d[9]),"+f"(d[10]),"+f"(d[11]),"+f"(d[12]),"+f"(d[13]),"+f"(d[14]),"+f"(d[15]),"+f"(d[16]),"+f"(d[17]),"+f"(d[18]),"+f"(d[19]),"+f"(d[20]),"+f"(d[21]),"+f"(d[22]),"+f"(d[23]),"+f"(d[24]),"+f"(d[25]),"+f"(d[26]),"+f"(d[27]),"+f"(d[28]),"+f"(d[29]),"+f"(d[30]),"+f"(d[31]),"+f"(d[32]),"+f"(d[33]),"+f"(d[34]),"+f"(d[35]),"+f"(d[36]),"+f"(d[37]),"+f"(d[38]),"+f"(d[39]),"+f"(d[40]),"+f"(d[41]),"+f"(d[42]),"+f"(d[43]),"+f"(d[44]),"+f"(d[45]),"+f"(d[46]),"+f"(d[47]),"+f"(d[48]),"+f"(d[49]),"+f"(d[50]),"+f"(d[51]),"+f"(d[52]),"+f"(d[53]),"+f"(d[54]),"+f"(d[55]),"+f"(d[56]),"+f"(d[57]),"+f"(d[58]),"+f"(d[59]),"+f"(d[60]),"+f"(d[61]),"+f"(d[62]),"+f"(d[63]),"+f"(d[64]),"+f"(d[65]),"+f"(d[66]),"+f"(d[67]),"+f"(d[68]),"+f"(d[69]),"+f"(d[70]),"+f"(d[71]),"+f"(d[72]),"+f"(d[73]),"+f"(d[74]),"+f"(d[75]),"+f"(d[76]),"+f"(d[77]),"+f"(d[78]),"+f"(d[79]),"+f"(d[80]),"+f"(d[81]),"+f"(d[82]),"+f"(d[83]),"+f"(d[84]),"+f"(d[85]),"+f"(d[86]),"+f"(d[87]),"+f"(d[88]),"+f"(d[89]),"+f"(d[90]),"+f"(d[91]),"+f"(d[92]),"+f"(d[93]),"+f"(d[94]),"+f"(d[95])
    :"r"(a0),"r"(a1),"r"(a2),"r"(a3),"l"(db),"r"(sc));
}
__device__ __forceinline__ void wgmma_rs_n24_t1(float (&d)[12],uint32_t a0,uint32_t a1,uint32_t a2,uint32_t a3,uint64_t db,int sc){
  asm volatile("{\n.reg .pred p;\nsetp.ne.b32 p,%17,0;\n"
    "wgmma.mma_async.sync.aligned.m64n24k16.f32.bf16.bf16 {%0,%1,%2,%3,%4,%5,%6,%7,%8,%9,%10,%11},{%12,%13,%14,%15},%16,p,1,1,1;\n}\n"
    :"+f"(d[0]),"+f"(d[1]),"+f"(d[2]),"+f"(d[3]),"+f"(d[4]),"+f"(d[5]),"+f"(d[6]),"+f"(d[7]),"+f"(d[8]),"+f"(d[9]),"+f"(d[10]),"+f"(d[11])
    :"r"(a0),"r"(a1),"r"(a2),"r"(a3),"l"(db),"r"(sc));
}
__device__ __forceinline__ void wgmma_rs_n32_t0(float (&d)[16],uint32_t a0,uint32_t a1,uint32_t a2,uint32_t a3,uint64_t db,int sc){
  asm volatile("{\n.reg .pred p;\nsetp.ne.b32 p,%21,0;\n"
    "wgmma.mma_async.sync.aligned.m64n32k16.f32.bf16.bf16 {%0,%1,%2,%3,%4,%5,%6,%7,%8,%9,%10,%11,%12,%13,%14,%15},{%16,%17,%18,%19},%20,p,1,1,0;\n}\n"
    :"+f"(d[0]),"+f"(d[1]),"+f"(d[2]),"+f"(d[3]),"+f"(d[4]),"+f"(d[5]),"+f"(d[6]),"+f"(d[7]),"+f"(d[8]),"+f"(d[9]),"+f"(d[10]),"+f"(d[11]),"+f"(d[12]),"+f"(d[13]),"+f"(d[14]),"+f"(d[15])
    :"r"(a0),"r"(a1),"r"(a2),"r"(a3),"l"(db),"r"(sc));
}
__device__ __forceinline__ void wgmma_rs_n64_t0(float (&d)[32],uint32_t a0,uint32_t a1,uint32_t a2,uint32_t a3,uint64_t db,int sc){
  asm volatile("{\n.reg .pred p;\nsetp.ne.b32 p,%37,0;\n"
    "wgmma.mma_async.sync.aligned.m64n64k16.f32.bf16.bf16 {%0,%1,%2,%3,%4,%5,%6,%7,%8,%9,%10,%11,%12,%13,%14,%15,%16,%17,%18,%19,%20,%21,%22,%23,%24,%25,%26,%27,%28,%29,%30,%31},{%32,%33,%34,%35},%36,p,1,1,0;\n}\n"
    :"+f"(d[0]),"+f"(d[1]),"+f"(d[2]),"+f"(d[3]),"+f"(d[4]),"+f"(d[5]),"+f"(d[6]),"+f"(d[7]),"+f"(d[8]),"+f"(d[9]),"+f"(d[10]),"+f"(d[11]),"+f"(d[12]),"+f"(d[13]),"+f"(d[14]),"+f"(d[15]),"+f"(d[16]),"+f"(d[17]),"+f"(d[18]),"+f"(d[19]),"+f"(d[20]),"+f"(d[21]),"+f"(d[22]),"+f"(d[23]),"+f"(d[24]),"+f"(d[25]),"+f"(d[26]),"+f"(d[27]),"+f"(d[28]),"+f"(d[29]),"+f"(d[30]),"+f"(d[31])
    :"r"(a0),"r"(a1),"r"(a2),"r"(a3),"l"(db),"r"(sc));
}
__device__ __forceinline__ void wgmma_ss_n128_t1(float (&d)[64],uint64_t da,uint64_t db,int sc){
  asm volatile("{\n.reg .pred p;\nsetp.ne.b32 p,%66,0;\n"
    "wgmma.mma_async.sync.aligned.m64n128k16.f32.bf16.bf16 {%0,%1,%2,%3,%4,%5,%6,%7,%8,%9,%10,%11,%12,%13,%14,%15,%16,%17,%18,%19,%20,%21,%22,%23,%24,%25,%26,%27,%28,%29,%30,%31,%32,%33,%34,%35,%36,%37,%38,%39,%40,%41,%42,%43,%44,%45,%46,%47,%48,%49,%50,%51,%52,%53,%54,%55,%56,%57,%58,%59,%60,%61,%62,%63},%64,%65,p,1,1,0,1;\n}\n"
    :"+f"(d[0]),"+f"(d[1]),"+f"(d[2]),"+f"(d[3]),"+f"(d[4]),"+f"(d[5]),"+f"(d[6]),"+f"(d[7]),"+f"(d[8]),"+f"(d[9]),"+f"(d[10]),"+f"(d[11]),"+f"(d[12]),"+f"(d[13]),"+f"(d[14]),"+f"(d[15]),"+f"(d[16]),"+f"(d[17]),"+f"(d[18]),"+f"(d[19]),"+f"(d[20]),"+f"(d[21]),"+f"(d[22]),"+f"(d[23]),"+f"(d[24]),"+f"(d[25]),"+f"(d[26]),"+f"(d[27]),"+f"(d[28]),"+f"(d[29]),"+f"(d[30]),"+f"(d[31]),"+f"(d[32]),"+f"(d[33]),"+f"(d[34]),"+f"(d[35]),"+f"(d[36]),"+f"(d[37]),"+f"(d[38]),"+f"(d[39]),"+f"(d[40]),"+f"(d[41]),"+f"(d[42]),"+f"(d[43]),"+f"(d[44]),"+f"(d[45]),"+f"(d[46]),"+f"(d[47]),"+f"(d[48]),"+f"(d[49]),"+f"(d[50]),"+f"(d[51]),"+f"(d[52]),"+f"(d[53]),"+f"(d[54]),"+f"(d[55]),"+f"(d[56]),"+f"(d[57]),"+f"(d[58]),"+f"(d[59]),"+f"(d[60]),"+f"(d[61]),"+f"(d[62]),"+f"(d[63])
    :"l"(da),"l"(db),"r"(sc));
}
__device__ __forceinline__ void wgmma_ss_n64_t1(float (&d)[32],uint64_t da,uint64_t db,int sc){
  asm volatile("{\n.reg .pred p;\nsetp.ne.b32 p,%34,0;\n"
    "wgmma.mma_async.sync.aligned.m64n64k16.f32.bf16.bf16 {%0,%1,%2,%3,%4,%5,%6,%7,%8,%9,%10,%11,%12,%13,%14,%15,%16,%17,%18,%19,%20,%21,%22,%23,%24,%25,%26,%27,%28,%29,%30,%31},%32,%33,p,1,1,0,1;\n}\n"
    :"+f"(d[0]),"+f"(d[1]),"+f"(d[2]),"+f"(d[3]),"+f"(d[4]),"+f"(d[5]),"+f"(d[6]),"+f"(d[7]),"+f"(d[8]),"+f"(d[9]),"+f"(d[10]),"+f"(d[11]),"+f"(d[12]),"+f"(d[13]),"+f"(d[14]),"+f"(d[15]),"+f"(d[16]),"+f"(d[17]),"+f"(d[18]),"+f"(d[19]),"+f"(d[20]),"+f"(d[21]),"+f"(d[22]),"+f"(d[23]),"+f"(d[24]),"+f"(d[25]),"+f"(d[26]),"+f"(d[27]),"+f"(d[28]),"+f"(d[29]),"+f"(d[30]),"+f"(d[31])
    :"l"(da),"l"(db),"r"(sc));
}

__global__ void __launch_bounds__(256) k_mod(const bf16* __restrict__ c, const bf16* __restrict__ w) {
  pdl_launch();
  __shared__ float red[8][32];
  const int t = threadIdx.x, n0 = blockIdx.x * 32 + (t & 3) * 8, r0 = t >> 2;
  uint4 v[8];
  float cs[8];
#pragma unroll
  for (int i = 0; i < 8; i++) v[i] = __ldg((const uint4*)(w + (size_t)(r0 + i * 64) * 3072 + n0));
#pragma unroll
  for (int i = 0; i < 8; i++) { float x = __bfloat162float(c[r0 + i * 64]); cs[i] = rbf(x / (1.f + __expf(-x))); }
  float a[8] = {0, 0, 0, 0, 0, 0, 0, 0};
#pragma unroll
  for (int i = 0; i < 8; i++) {
    a[0] += cs[i] * blo(v[i].x); a[1] += cs[i] * bhi(v[i].x); a[2] += cs[i] * blo(v[i].y); a[3] += cs[i] * bhi(v[i].y);
    a[4] += cs[i] * blo(v[i].z); a[5] += cs[i] * bhi(v[i].z); a[6] += cs[i] * blo(v[i].w); a[7] += cs[i] * bhi(v[i].w);
  }
#pragma unroll
  for (int j = 0; j < 8; j++) {
    a[j] += __shfl_xor_sync(~0u, a[j], 4); a[j] += __shfl_xor_sync(~0u, a[j], 8); a[j] += __shfl_xor_sync(~0u, a[j], 16);
  }
  if ((t & 31) < 4) {
#pragma unroll
    for (int j = 0; j < 8; j++) red[t >> 5][(t & 3) * 8 + j] = a[j];
  }
  __syncthreads();
  if (t < 32) {
    float s = 0;
#pragma unroll
    for (int i = 0; i < 8; i++) s += red[i][t];
    const int n = blockIdx.x * 32 + t, seg = n >> 9;
    s = rbf(s);
    if (seg == 1 || seg == 4) s = rbf(1.f + s);
    g_mod[n] = s;
  }
}

constexpr int LN_SMEM = 131072 + 4 * 24576 + 2048 + 256;
template <bool FFN>
__global__ void __launch_bounds__(384, 1) k_lngemm(const __grid_constant__ CUtensorMap mX, const __grid_constant__ CUtensorMap mB0,
                                                   const __grid_constant__ CUtensorMap mB1) {
  extern __shared__ __align__(1024) uint8_t smem[];
  const uint32_t sA = smem_u32(smem), sB = sA + 131072, sM = sB + 4 * 24576, bars = sM + 2048;
  const uint32_t bA = bars, bF = bars + 64, bE = bars + 96;
  const int tid = threadIdx.x, warp = tid >> 5, lane = tid & 31;
  const int rb = blockIdx.x >> 3, ct = blockIdx.x & 7;
  constexpr int NST = FFN ? 16 : 8, KS = FFN ? 2 : 4, BOX = FFN ? 4096 : 8192;
  pdl_launch();
  if (tid == 256) {
    for (int i = 0; i < 8; i++) mbar_init(bA + 8 * i, 1);
    for (int i = 0; i < 4; i++) { mbar_init(bF + 8 * i, 1); mbar_init(bE + 8 * i, 8); }
    fence_init();
  }
  __syncthreads();
  if (warp >= 8) {
    asm volatile("setmaxnreg.dec.sync.aligned.u32 40;");
    if (tid == 256) {
      auto loadB = [&](int s) {
        const uint32_t d = sB + (s & 3) * 24576, b = bF + (s & 3) * 8;
        mbar_expect(b, 24576);
        for (int j = 0; j < 3; j++) {
          if (FFN) { tma2d(d + j * BOX, &mB0, ct * 176 + j * 64, s * 32, b); tma2d(d + (3 + j) * BOX, &mB1, ct * 176 + j * 64, s * 32, b); }
          else tma2d(d + j * BOX, &mB0, ct * 192 + j * 64, s * 64, b);
        }
      };
      if (!FFN) for (int i = 0; i < 8; i++) { mbar_expect(bA + 8 * i, 16384); tma2d(sA + i * 16384, &mX, i * 64, rb * 128, bA + 8 * i); }
      for (int s = 0; s < 4; s++) loadB(s);
      if (FFN) {
        pdl_wait();
        for (int i = 0; i < 8; i++) { mbar_expect(bA + 8 * i, 16384); bulk_load(sA + i * 16384, g_x1 + (rb * 64 + i * 8) * 1024, 16384, bA + 8 * i); }
      }
      for (int s = 4; s < NST; s++) { mbar_wait(bE + (s & 3) * 8, ((s >> 2) - 1) & 1); loadB(s); }
    }
  } else {
  asm volatile("setmaxnreg.inc.sync.aligned.u32 232;");
  const int g = lane >> 2, t = lane & 3;
  const int lr = warp * 16 + (lane & 7) + ((lane >> 3) & 1) * 8;
  auto aaddr = [&](int ks) -> uint32_t {
    if (FFN) return sA + (ks * 2 + (lane >> 4)) * 2048 + lr * 16;
    return sA + (ks >> 2) * 16384 + lr * 128 + ((((ks & 3) * 2 + (lane >> 4)) ^ (lr & 7)) << 4);
  };
  const int row0 = rb * 128 + warp * 16 + g;
  float rs0, rs1, nm0, nm1;
  if (!FFN) {
    float s0 = 0, s1 = 0;
#pragma unroll 4
    for (int ks = 0; ks < 32; ks++) {
      if ((ks & 3) == 0) mbar_wait(bA + 2 * ks, 0);
      uint32_t r[4]; ldsm4(aaddr(ks), r);
      s0 += (blo(r[0]) + bhi(r[0])) + (blo(r[2]) + bhi(r[2]));
      s1 += (blo(r[1]) + bhi(r[1])) + (blo(r[3]) + bhi(r[3]));
    }
    const float m0 = qsum(s0) * (1.f / 512), m1 = qsum(s1) * (1.f / 512);
    float v0 = 0, v1 = 0, v2 = 0, v3 = 0;
#pragma unroll 4
    for (int ks = 0; ks < 32; ks++) {
      uint32_t r[4]; ldsm4(aaddr(ks), r);
      float d;
      d = blo(r[0]) - m0; v0 += d * d; d = bhi(r[0]) - m0; v2 += d * d; d = blo(r[2]) - m0; v0 += d * d; d = bhi(r[2]) - m0; v2 += d * d;
      d = blo(r[1]) - m1; v1 += d * d; d = bhi(r[1]) - m1; v3 += d * d; d = blo(r[3]) - m1; v1 += d * d; d = bhi(r[3]) - m1; v3 += d * d;
    }
    rs0 = rsqrtf(qsum(v0 + v2) * (1.f / 512) + 1e-5f); rs1 = rsqrtf(qsum(v1 + v3) * (1.f / 512) + 1e-5f);
    nm0 = -m0 * rs0; nm1 = -m1 * rs1;
    pdl_wait();
  } else {
    pdl_wait();
    const float4 p0 = *(const float4*)(g_st + row0 * 8 + t * 2), p1 = *(const float4*)(g_st + (row0 + 8) * 8 + t * 2);
    const float m0 = qsum(p0.x + p0.z) * 0.125f, m1 = qsum(p1.x + p1.z) * 0.125f;
    const float v0 = qsum(p0.y + p0.w + 64.f * ((p0.x - m0) * (p0.x - m0) + (p0.z - m0) * (p0.z - m0)));
    const float v1 = qsum(p1.y + p1.w + 64.f * ((p1.x - m1) * (p1.x - m1) + (p1.z - m1) * (p1.z - m1)));
    rs0 = rsqrtf(v0 * (1.f / 512) + 1e-5f); rs1 = rsqrtf(v1 * (1.f / 512) + 1e-5f);
    nm0 = -m0 * rs0; nm1 = -m1 * rs1;
  }
  {
    const float2 sh = *(const float2*)(g_mod + (FFN ? 1536 : 0) + tid * 2), sc = *(const float2*)(g_mod + (FFN ? 2048 : 512) + tid * 2);
    uint32_t* m = (uint32_t*)(smem + (sM - sA)) + (tid >> 3) * 16 + (tid & 3) * 4 + ((tid >> 2) & 1);
    m[0] = pack_rn(sc.x, sc.y); m[2] = pack_rn(sh.x, sh.y);
    asm volatile("bar.sync 1,256;" ::: "memory");
  }
  constexpr int NA = FFN ? 88 : 96;
  float acc0[NA], acc1[FFN ? 88 : 1];
  uint32_t a[2][4];
  auto prep = [&](int ks, uint32_t(&o)[4]) {
    if (FFN && (ks & 3) == 0) mbar_wait(bA + 2 * ks, 0);
    uint32_t r[4]; ldsm4(aaddr(ks), r);
    const uint4 m = *(const uint4*)(smem + (sM - sA) + ks * 64 + t * 16);
#pragma unroll
    for (int i = 0; i < 4; i++) {
      const float rs = (i & 1) ? rs1 : rs0, nm = (i & 1) ? nm1 : nm0;
      const uint32_t n = pack_rn(fmaf(blo(r[i]), rs, nm), fmaf(bhi(r[i]), rs, nm));
      asm("fma.rn.bf16x2 %0,%1,%2,%3;" : "=r"(o[i]) : "r"(n), "r"(i < 2 ? m.x : m.y), "r"(i < 2 ? m.z : m.w));
    }
  };
  prep(0, a[0]);
#pragma unroll 1
  for (int s = 0; s < NST; s++) {
    mbar_wait(bF + (s & 3) * 8, (s >> 2) & 1);
    const uint64_t db = mk_desc(sB + (s & 3) * 24576, BOX, 1024, 1);
#pragma unroll
    for (int k = 0; k < KS; k++) {
      const int ks = s * KS + k;
      uint32_t(&c)[4] = a[k & 1];
      wg_fence();
      if constexpr (FFN) {
        wgmma_rs_n176_t1(acc0, c[0], c[1], c[2], c[3], db + k * 128, ks);
        wgmma_rs_n176_t1(acc1, c[0], c[1], c[2], c[3], db + k * 128 + 3 * BOX / 16, ks);
      } else {
        wgmma_rs_n192_t1(acc0, c[0], c[1], c[2], c[3], db + k * 128, ks);
      }
      wg_commit();
      wg_wait<1>();
      if (k == 0 && s > 0 && lane == 0) mbar_arrive(bE + ((s - 1) & 3) * 8);
      if (ks < 31) prep(ks + 1, a[(k + 1) & 1]);
    }
  }
  wg_wait<0>();
  reg_fence(acc0);
  if constexpr (FFN) {
    reg_fence(acc1);
    uint32_t* o = (uint32_t*)g_h + ((rb * 172 + ct * 22) * 128 + warp * 16 + g) * 4 + t;
#pragma unroll
    for (int j = 0; j < 22; j++) {
      if (ct * 22 + j < 172) {
        float h[4];
#pragma unroll
        for (int i = 0; i < 4; i++) { const float x = acc0[4 * j + i]; h[i] = __fdividef(x, 1.f + ex2(-1.4426950408889634f * x)) * acc1[4 * j + i]; }
        o[j * 512] = pack_rn(h[0], h[1]);
        o[j * 512 + 32] = pack_rn(h[2], h[3]);
      }
    }
  } else {
    uint32_t* o = (uint32_t*)g_qkv + (ct * 24 * 2048 + row0) * 4 + t;
#pragma unroll
    for (int j = 0; j < 24; j += 2) {
      const int G = ct * 24 + j;
      const float sc = G < 64 ? 0.25f * 1.4426950408889634f : 1.f;
      uint32_t p[4];
#pragma unroll
      for (int i = 0; i < 4; i++) p[i] = pack_rn(acc0[4 * j + 2 * i] * sc, acc0[4 * j + 2 * i + 1] * sc);
      o[j * 8192] = p[0]; o[j * 8192 + 32] = p[1]; o[(j + 1) * 8192] = p[2]; o[(j + 1) * 8192 + 32] = p[3];
      if (G >= 64 && G < 128) {
        float n0 = blo(p[0]) * blo(p[0]) + bhi(p[0]) * bhi(p[0]) + blo(p[2]) * blo(p[2]) + bhi(p[2]) * bhi(p[2]);
        float n1 = blo(p[1]) * blo(p[1]) + bhi(p[1]) * bhi(p[1]) + blo(p[3]) * blo(p[3]) + bhi(p[3]) * bhi(p[3]);
        n0 = qsum(n0); n1 = qsum(n1);
        const uint32_t mx = __reduce_max_sync(~0u, max(__float_as_uint(n0), __float_as_uint(n1)));
        if (lane == 0) g_kmax[((G - 64) >> 1) * 128 + rb * 8 + warp] = __uint_as_float(mx);
      }
    }
  }
}
}

#define POLYMASK 0x52A552A5u
#define AUG 0
constexpr int AT_SMEM = 5 * 32768 + 256;
__device__ __forceinline__ uint32_t exp2_pair_fma(float s0, float s1, float c) {
  float y0, y1;
  asm("fma.rn.sat.f32 %0,%1,0f00008000,%2;" : "=f"(y0) : "f"(s0), "f"(c));
  asm("fma.rn.sat.f32 %0,%1,0f00008000,%2;" : "=f"(y1) : "f"(s1), "f"(c));
  const float u0 = __uint_as_float((__float_as_uint(y0) & 0x7FFFu) | 0x43800000u), u1 = __uint_as_float((__float_as_uint(y1) & 0x7FFFu) | 0x43800000u);
  const float l0 = fmaf(u0, 0.427682191f, -109.07412f), l1 = fmaf(u1, 0.427682191f, -109.07412f);
  const float p0 = fmaf(fmaf(l0, l0, 1.11545753f), l0, 0.469651312f), p1 = fmaf(fmaf(l1, l1, 1.11545753f), l1, 0.469651312f);
  const uint32_t e = __byte_perm(__float_as_uint(y0), __float_as_uint(y1), 0x6521), m = pack_rz(p0, p1);
  return (e & 0x7F807F80u) | (m & 0x807F807Fu);
}
#define NK 64
#define PP 0
template <uint32_t MASK, bool AG>
__device__ __forceinline__ void attn_pass(float (&o)[12], const uint32_t (&q)[4], float m0, float m1, uint32_t sK, uint32_t bars, bool first) {
  const uint64_t dk = mk_desc(sK, 32768, 128, 0), dv = mk_desc(sK + 65536, 128, 32768, 0), d1 = mk_desc(sK + 131072, 128, 128, 0);
  const float c0 = (AG ? 127.f : 127.f - m0) * __uint_as_float(0x8000u), c1 = (AG ? 127.f : 127.f - m1) * __uint_as_float(0x8000u);
  const uint32_t am0 = (threadIdx.x & 3) ? 0u : (__float_as_uint(-m0) >> 16), am1 = (threadIdx.x & 3) ? 0u : (__float_as_uint(-m1) >> 16);
  constexpr int NS = NK / 2, NP = NK / 4, NI = 2048 / NK;
  auto qk = [&](float (&s)[NS], int i) {
    if (AG) wgmma_rs_n64_t0(s, am0, am1, 0, 0, d1, 0);
    wgmma_rs_n64_t0(s, q[0], q[1], q[2], q[3], dk + i * NK, AG);
  };
  auto softmax = [&](float (&s)[NS], uint32_t (&p)[NP], uint32_t mask) {
    reg_fence(s);
#pragma unroll
    for (int j = 0; j < NP; j++) {
      if ((mask >> j) & 1) p[j] = exp2_pair_fma(s[2 * j], s[2 * j + 1], (j & 1) ? c1 : c0);
      else if (AG) p[j] = pack_rz(ex2(s[2 * j]), ex2(s[2 * j + 1]));
      else { const float m = (j & 1) ? m1 : m0; p[j] = pack_rz(ex2(s[2 * j] - m), ex2(s[2 * j + 1] - m)); }
    }
#pragma unroll
    for (int j = 0; j < NP; j++) asm volatile("" : "+r"(p[j])::"memory");
  };
  auto pv = [&](uint32_t (&p)[NP], int i) {
#pragma unroll
    for (int k = 0; k < NK / 16; k++) wgmma_rs_n24_t1(o, p[4 * k], p[4 * k + 1], p[4 * k + 2], p[4 * k + 3], dv + i * NK + k * 16, 1);
  };
  auto ld = [&](int i) { if (first && (i & (NI / 4 - 1)) == 0) mbar_wait(bars + i / (NI / 4) * 8, 0); };
  constexpr uint32_t M0 = MASK, M1 = NK == 128 ? MASK : MASK >> NP;
  zero(o);
  ld(0);
  float s[NS];
  zero(s);
  uint32_t p[NP];
  wg_fence(); qk(s, 0); wg_commit(); wg_wait<0>(); softmax(s, p, M0);
#pragma unroll 1
  for (int i = 0; i < NI - 2; i += 2) {
    wg_fence(); qk(s, i + 1); pv(p, i); wg_commit(); wg_wait<0>(); softmax(s, p, M1);
    ld(i + 2);
    wg_fence(); qk(s, i + 2); pv(p, i + 1); wg_commit(); wg_wait<0>(); softmax(s, p, M0);
  }
  wg_fence(); qk(s, NI - 1); pv(p, NI - 2); wg_commit(); wg_wait<0>(); softmax(s, p, M1);
  wg_fence(); pv(p, NI - 1); wg_commit();
  wg_wait<0>();
  reg_fence(o);
}
__device__ __forceinline__ void mma16816(float (&d)[4], const uint32_t (&a)[4], uint32_t b0, uint32_t b1) {
  asm("mma.sync.aligned.m16n8k16.row.col.f32.bf16.bf16.f32 {%0,%1,%2,%3},{%4,%5,%6,%7},{%8,%9},{%0,%1,%2,%3};"
      : "+f"(d[0]), "+f"(d[1]), "+f"(d[2]), "+f"(d[3]) : "r"(a[0]), "r"(a[1]), "r"(a[2]), "r"(a[3]), "r"(b0), "r"(b1));
}
__device__ __forceinline__ void attn_safe(float (&o)[12], const uint32_t (&q)[4], uint32_t sK) {
  const int lane = threadIdx.x & 31;
  const uint32_t ka = sK + (lane >> 4) * 32768 + (lane & 15) * 16;
  float m0 = -INFINITY, m1 = -INFINITY;
#pragma unroll 2
  for (int i = 0; i < 128; i++) {
    uint32_t k[4]; ldsm4(ka + i * 256, k);
    float s0[4] = {0, 0, 0, 0}, s1[4] = {0, 0, 0, 0};
    mma16816(s0, q, k[0], k[2]); mma16816(s1, q, k[1], k[3]);
    m0 = fmaxf(fmaxf(m0, fmaxf(s0[0], s0[1])), fmaxf(s1[0], s1[1])); m1 = fmaxf(fmaxf(m1, fmaxf(s0[2], s0[3])), fmaxf(s1[2], s1[3]));
  }
  m0 = fmaxf(m0, __shfl_xor_sync(~0u, m0, 1)); m0 = fmaxf(m0, __shfl_xor_sync(~0u, m0, 2));
  m1 = fmaxf(m1, __shfl_xor_sync(~0u, m1, 1)); m1 = fmaxf(m1, __shfl_xor_sync(~0u, m1, 2));
  float o0[4] = {0, 0, 0, 0}, o1[4] = {0, 0, 0, 0}, o2[4] = {0, 0, 0, 0};
#pragma unroll 2
  for (int i = 0; i < 128; i++) {
    uint32_t k[4], v[4]; ldsm4(ka + i * 256, k);
    asm volatile("ldmatrix.sync.aligned.m8n8.x4.trans.shared.b16 {%0,%1,%2,%3},[%4];" : "=r"(v[0]), "=r"(v[1]), "=r"(v[2]), "=r"(v[3]) : "r"(ka + 65536 + i * 256) : "memory");
    float s0[4] = {0, 0, 0, 0}, s1[4] = {0, 0, 0, 0};
    mma16816(s0, q, k[0], k[2]); mma16816(s1, q, k[1], k[3]);
    const uint32_t p[4] = {pack_rn(ex2(s0[0] - m0), ex2(s0[1] - m0)), pack_rn(ex2(s0[2] - m1), ex2(s0[3] - m1)),
                           pack_rn(ex2(s1[0] - m0), ex2(s1[1] - m0)), pack_rn(ex2(s1[2] - m1), ex2(s1[3] - m1))};
    mma16816(o0, p, v[0], v[1]); mma16816(o1, p, v[2], v[3]); mma16816(o2, p, 0x3F803F80u, 0x3F803F80u);
  }
#pragma unroll
  for (int i = 0; i < 4; i++) { o[i] = o0[i]; o[4 + i] = o1[i]; o[8 + i] = o2[i]; }
}
__global__ void __launch_bounds__(512, 1) k_attn(const bf16* wo, const bf16* w1, const bf16* w3, const bf16* w2) {
  extern __shared__ __align__(1024) uint8_t smem[];
  const uint32_t sK = smem_u32(smem), bars = sK + 5 * 32768;
  const int tid = threadIdx.x, warp = tid >> 5, lane = tid & 31, g = lane >> 2, t = lane & 3;
  const int h = blockIdx.x >> 2, qb = blockIdx.x & 3;
  pdl_launch();
  if (tid == 0) { for (int i = 0; i < 4; i++) mbar_init(bars + 8 * i, 1); fence_init(); }
#pragma unroll
  for (int i = 0; i < 4; i++) *(uint4*)(smem + 131072 + i * 8192 + tid * 16) = make_uint4(0x3F803F80u, 0x3F803F80u, 0x3F803F80u, 0x3F803F80u);
  fence_async();
  __syncthreads();
  pdl_wait();
  if (tid == 0) {
    for (int c = 0; c < 4; c++) {
      mbar_expect(bars + 8 * c, 32768);
      for (int pl = 0; pl < 4; pl++)
        bulk_load(sK + pl * 32768 + c * 8192, g_qkv + ((64 + (pl >> 1) * 64 + h * 2 + (pl & 1)) * 2048 + c * 512) * 8, 8192, bars + 8 * c);
    }
  }
  if (tid == 32) {
    l2_prefetch((const char*)wo + blockIdx.x * 4096, 4096);
    l2_prefetch((const char*)w1 + blockIdx.x * 11008, 11008);
    l2_prefetch((const char*)w3 + blockIdx.x * 11008, 11008);
    l2_prefetch((const char*)w2 + blockIdx.x * 11008, 11008);
  }
  const uint4 km4 = *(const uint4*)(g_kmax + h * 128 + lane * 4);
  const float kmax = __uint_as_float(__reduce_max_sync(~0u, max(max(km4.x, km4.y), max(km4.z, km4.w))));
#pragma unroll 1
  for (int tile = 0; tile < 2; tile++) {
    const int row = qb * 512 + tile * 256 + warp * 16 + g;
    const uint32_t* qp = (const uint32_t*)g_qkv + (h * 2 * 2048 + row) * 4 + t;
    uint32_t q[4] = {qp[0], qp[32], qp[8192], qp[8192 + 32]};
    const float n0 = qsum(blo(q[0]) * blo(q[0]) + bhi(q[0]) * bhi(q[0]) + blo(q[2]) * blo(q[2]) + bhi(q[2]) * bhi(q[2]));
    const float n1 = qsum(blo(q[1]) * blo(q[1]) + bhi(q[1]) * bhi(q[1]) + blo(q[3]) * blo(q[3]) + bhi(q[3]) * bhi(q[3]));
    const float b0 = sqrtf(n0 * kmax) * 1.001f, b1 = sqrtf(n1 * kmax) * 1.001f;
    float m0 = ceilf(b0 - 100.f), m1 = ceilf(b1 - 100.f);
    if (AUG) { m0 = __bfloat162float(__float2bfloat16_ru(m0)); m1 = __bfloat162float(__float2bfloat16_ru(m1)); }
    float o[12];
    attn_pass<POLYMASK, AUG>(o, q, m0, m1, sK, bars, tile == 0);
    bool ok = b0 < 1e4f && b1 < 1e4f && o[8] >= 0x1p-90f && o[10] >= 0x1p-90f;
#pragma unroll
    for (int i = 0; i < 12; i++) ok = ok && fabsf(o[i]) < INFINITY;
    if (!__all_sync(~0u, ok)) attn_safe(o, q, sK);
    const float r0 = 1.f / o[8], r1 = 1.f / o[10];
    uint32_t* op = (uint32_t*)g_o + (((row >> 7) * 64 + h * 2) * 128 + (row & 127)) * 4 + t;
    op[0] = pack_rn(o[0] * r0, o[1] * r0); op[32] = pack_rn(o[2] * r1, o[3] * r1);
    op[512] = pack_rn(o[4] * r0, o[5] * r0); op[512 + 32] = pack_rn(o[6] * r1, o[7] * r1);
  }
}

constexpr int WO_SMEM = 131072 + 65536 + 256;
__global__ void __launch_bounds__(256, 1) k_wo(const __grid_constant__ CUtensorMap mW, const bf16* __restrict__ x) {
  extern __shared__ __align__(1024) uint8_t smem[];
  const uint32_t sA = smem_u32(smem), sB = sA + 131072, bars = sB + 65536;
  const int tid = threadIdx.x, warp = tid >> 5, lane = tid & 31, g = lane >> 2, t = lane & 3;
  const int rb = blockIdx.x >> 3, ct = blockIdx.x & 7;
  pdl_launch();
  if (tid == 0) {
    for (int i = 0; i < 8; i++) mbar_init(bars + 8 * i, 1);
    fence_init();
    for (int i = 0; i < 8; i++) { mbar_expect(bars + 8 * i, 24576); tma2d(sB + i * 8192, &mW, ct * 64, i * 64, bars + 8 * i); }
  }
  const int lrow = warp * 16 + g;
  uint32_t xr[16];
  const uint32_t* xp = (const uint32_t*)(x + (rb * 128 + lrow) * 512 + ct * 64) + t;
#pragma unroll
  for (int j = 0; j < 8; j++) { xr[2 * j] = __ldg(xp + j * 4); xr[2 * j + 1] = __ldg(xp + j * 4 + 8 * 256); }
  __syncthreads();
  pdl_wait();
  if (tid == 0) for (int i = 0; i < 8; i++) bulk_load(sA + i * 16384, g_o + (rb * 64 + i * 8) * 1024, 16384, bars + 8 * i);
  float2 ga[8];
#pragma unroll
  for (int j = 0; j < 8; j++) ga[j] = *(const float2*)(g_mod + 1024 + ct * 64 + j * 8 + t * 2);
  float acc[32];
  const uint64_t da = mk_desc(sA + (warp >> 2) * 1024, 2048, 128, 0), db = mk_desc(sB, 8192, 1024, 1);
#pragma unroll
  for (int c = 0; c < 8; c++) {
    mbar_wait(bars + 8 * c, 0);
    wg_fence();
#pragma unroll
    for (int k = 0; k < 4; k++) wgmma_ss_n64_t1(acc, da + (c * 4 + k) * 256, db + (c * 4 + k) * 128, c + k);
    wg_commit();
  }
  wg_wait<0>();
  reg_fence(acc);
  uint32_t* o = (uint32_t*)g_x1 + ((rb * 64 + ct * 8) * 128 + lrow) * 4 + t;
  float s0 = 0, s1 = 0;
#pragma unroll
  for (int j = 0; j < 8; j++) {
    xr[2 * j] = pack_rn(fmaf(ga[j].x, acc[4 * j], blo(xr[2 * j])), fmaf(ga[j].y, acc[4 * j + 1], bhi(xr[2 * j])));
    xr[2 * j + 1] = pack_rn(fmaf(ga[j].x, acc[4 * j + 2], blo(xr[2 * j + 1])), fmaf(ga[j].y, acc[4 * j + 3], bhi(xr[2 * j + 1])));
    o[j * 512] = xr[2 * j]; o[j * 512 + 32] = xr[2 * j + 1];
    s0 += blo(xr[2 * j]) + bhi(xr[2 * j]); s1 += blo(xr[2 * j + 1]) + bhi(xr[2 * j + 1]);
  }
  const float m0 = qsum(s0) * (1.f / 64), m1 = qsum(s1) * (1.f / 64);
  float v0 = 0, v1 = 0;
#pragma unroll
  for (int j = 0; j < 8; j++) {
    float d;
    d = blo(xr[2 * j]) - m0; v0 += d * d; d = bhi(xr[2 * j]) - m0; v0 += d * d;
    d = blo(xr[2 * j + 1]) - m1; v1 += d * d; d = bhi(xr[2 * j + 1]) - m1; v1 += d * d;
  }
  v0 = qsum(v0); v1 = qsum(v1);
  if (t == 0) g_st[(rb * 128 + lrow) * 8 + ct] = make_float2(m0, v0);
  if (t == 1) g_st[(rb * 128 + lrow + 8) * 8 + ct] = make_float2(m1, v1);
}

constexpr int W2_SMEM = 6 * 32768 + 32768 + 256;
__global__ void __cluster_dims__(2, 1, 1) __launch_bounds__(288, 1) k_w2(const __grid_constant__ CUtensorMap mW, bf16* __restrict__ out) {
  extern __shared__ __align__(1024) uint8_t smem[];
  const uint32_t sR = smem_u32(smem), sX = sR + 6 * 32768, bF = sX + 32768, bE = bF + 48;
  const int tid = threadIdx.x, warp = tid >> 5, lane = tid & 31, g = lane >> 2, t = lane & 3;
  const int kh = blockIdx.x & 1, ct = (blockIdx.x >> 1) & 3, rb = blockIdx.x >> 3;
  pdl_launch();
  if (tid == 256) {
    for (int i = 0; i < 6; i++) { mbar_init(bF + 8 * i, 1); mbar_init(bE + 8 * i, 8); }
    fence_init();
  }
  __syncthreads();
  asm volatile("barrier.cluster.arrive.relaxed.aligned;" ::: "memory");
  if (warp == 8) {
    if (lane == 0) {
      auto abytes = [&](int s) { return (kh == 1 && s == 10) ? 8192 : 16384; };
      auto loadB = [&](int s) {
        const int st = s % 6;
        mbar_expect(bF + 8 * st, 16384 + abytes(s));
        for (int j = 0; j < 2; j++) tma2d(sR + st * 32768 + 16384 + j * 8192, &mW, ct * 128 + j * 64, kh * 704 + s * 64, bF + 8 * st);
      };
      auto loadA = [&](int s) { bulk_load(sR + (s % 6) * 32768, g_h + (rb * 172 + kh * 88 + s * 8) * 1024, abytes(s), bF + 8 * (s % 6)); };
      for (int s = 0; s < 6; s++) loadB(s);
      pdl_wait();
      for (int s = 0; s < 6; s++) loadA(s);
      for (int s = 6; s < 11; s++) { mbar_wait(bE + 8 * (s - 6), 0); loadB(s); loadA(s); }
    }
    __syncwarp();
    asm volatile("barrier.cluster.wait.aligned;" ::: "memory");
    asm volatile("barrier.cluster.arrive.release.aligned;" ::: "memory");
    asm volatile("barrier.cluster.wait.acquire.aligned;" ::: "memory");
    return;
  }
  pdl_wait();
  const int lrow = warp * 16 + g;
  uint32_t xr[16];
  float2 gb[8];
  const uint32_t* xp = (const uint32_t*)g_x1 + ((rb * 64 + ct * 16 + kh * 8) * 128 + lrow) * 4 + t;
#pragma unroll
  for (int j = 0; j < 8; j++) {
    xr[2 * j] = xp[j * 512]; xr[2 * j + 1] = xp[j * 512 + 32];
    gb[j] = *(const float2*)(g_mod + 2560 + ct * 128 + kh * 64 + j * 8 + t * 2);
  }
  float acc[64];
#pragma unroll 1
  for (int s = 0; s < 11; s++) {
    const int st = s % 6;
    mbar_wait(bF + 8 * st, s >= 6);
    const uint64_t da = mk_desc(sR + st * 32768 + (warp >> 2) * 1024, 2048, 128, 0), db = mk_desc(sR + st * 32768 + 16384, 8192, 1024, 1);
    wg_fence();
    wgmma_ss_n128_t1(acc, da, db, s);
    wgmma_ss_n128_t1(acc, da + 256, db + 128, 1);
    wgmma_ss_n128_t1(acc, da + 512, db + 256, 1);
    wgmma_ss_n128_t1(acc, da + 768, db + 384, 1);
    wg_commit();
    wg_wait<1>();
    if (s > 0 && s < 6 && lane == 0) mbar_arrive(bE + 8 * (s - 1));
  }
  wg_wait<0>();
  reg_fence(acc);
  asm volatile("barrier.cluster.wait.aligned;" ::: "memory");
  uint32_t rem;
  asm("mapa.shared::cluster.u32 %0,%1,%2;" : "=r"(rem) : "r"(sX + tid * 16), "r"(kh ^ 1));
#pragma unroll
  for (int j = 0; j < 8; j++) {
    float v[4];
#pragma unroll
    for (int i = 0; i < 4; i++) { v[i] = kh ? acc[4 * j + i] : acc[32 + 4 * j + i]; acc[4 * j + i] = kh ? acc[32 + 4 * j + i] : acc[4 * j + i]; }
    asm volatile("st.shared::cluster.v4.f32 [%0],{%1,%2,%3,%4};" ::"r"(rem + j * 4096), "f"(v[0]), "f"(v[1]), "f"(v[2]), "f"(v[3]) : "memory");
  }
  asm volatile("barrier.cluster.arrive.release.aligned;" ::: "memory");
  asm volatile("barrier.cluster.wait.acquire.aligned;" ::: "memory");
  uint32_t* o = (uint32_t*)(out + (rb * 128 + lrow) * 512 + ct * 128 + kh * 64) + t;
#pragma unroll
  for (int j = 0; j < 8; j++) {
    const float4 p = *(const float4*)(smem + 6 * 32768 + j * 4096 + tid * 16);
    o[j * 4] = pack_rn(fmaf(gb[j].x, acc[4 * j] + p.x, blo(xr[2 * j])), fmaf(gb[j].y, acc[4 * j + 1] + p.y, bhi(xr[2 * j])));
    o[j * 4 + 2048] = pack_rn(fmaf(gb[j].x, acc[4 * j + 2] + p.z, blo(xr[2 * j + 1])), fmaf(gb[j].y, acc[4 * j + 3] + p.w, bhi(xr[2 * j + 1])));
  }
}

typedef CUresult (*EncFn)(CUtensorMap*, CUtensorMapDataType, cuuint32_t, void*, const cuuint64_t*, const cuuint64_t*, const cuuint32_t*,
                          const cuuint32_t*, CUtensorMapInterleave, CUtensorMapSwizzle, CUtensorMapL2promotion, CUtensorMapFloatOOBfill);
static void mk_map(EncFn f, CUtensorMap* m, const void* p, int rows, int cols, int box_rows) {
  cuuint64_t dim[2] = {(cuuint64_t)cols, (cuuint64_t)rows}, str[1] = {(cuuint64_t)cols * 2};
  cuuint32_t box[2] = {64, (cuuint32_t)box_rows}, es[2] = {1, 1};
  f(m, CU_TENSOR_MAP_DATA_TYPE_BFLOAT16, 2, (void*)p, dim, str, box, es, CU_TENSOR_MAP_INTERLEAVE_NONE, CU_TENSOR_MAP_SWIZZLE_128B,
    CU_TENSOR_MAP_L2_PROMOTION_L2_128B, CU_TENSOR_MAP_FLOAT_OOB_FILL_NONE);
}
template <typename... KA, typename... A>
static void launch(void (*k)(KA...), int grid, int block, int smem, bool pdl, A... args) {
  cudaLaunchConfig_t cfg = {};
  cfg.gridDim = dim3(grid); cfg.blockDim = dim3(block); cfg.dynamicSmemBytes = smem; cfg.stream = cudaStreamPerThread;
  cudaLaunchAttribute at[1];
  at[0].id = cudaLaunchAttributeProgrammaticStreamSerialization; at[0].val.programmaticStreamSerializationAllowed = 1;
  cfg.attrs = at; cfg.numAttrs = pdl ? 1 : 0;
  cudaLaunchKernelEx(&cfg, k, args...);
}
extern "C" void kernel_launch(void* const* d_in, const int* in_sizes, int n_in, void* d_out, int out_size) {
  const bf16 *x = (const bf16*)d_in[0], *wqkv = (const bf16*)d_in[1], *wo = (const bf16*)d_in[2], *w1 = (const bf16*)d_in[4],
             *w3 = (const bf16*)d_in[5], *w2 = (const bf16*)d_in[6], *c = (const bf16*)d_in[7], *wmod = (const bf16*)d_in[8];
  void* fp = nullptr;
  cudaDriverEntryPointQueryResult qr;
  cudaGetDriverEntryPoint("cuTensorMapEncodeTiled", &fp, cudaEnableDefault, &qr);
  EncFn f = (EncFn)fp;
  CUtensorMap mX, mQ, mO, m1, m3, m2;
  mk_map(f, &mX, x, S_, D_, 128); mk_map(f, &mQ, wqkv, D_, 3 * D_, 64); mk_map(f, &mO, wo, D_, D_, 64);
  mk_map(f, &m1, w1, D_, F_, 32); mk_map(f, &m3, w3, D_, F_, 32); mk_map(f, &m2, w2, F_, D_, 64);
  cudaFuncSetAttribute(k_lngemm<false>, cudaFuncAttributeMaxDynamicSharedMemorySize, LN_SMEM);
  cudaFuncSetAttribute(k_lngemm<true>, cudaFuncAttributeMaxDynamicSharedMemorySize, LN_SMEM);
  cudaFuncSetAttribute(k_attn, cudaFuncAttributeMaxDynamicSharedMemorySize, AT_SMEM);
  cudaFuncSetAttribute(k_wo, cudaFuncAttributeMaxDynamicSharedMemorySize, WO_SMEM);
  cudaFuncSetAttribute(k_w2, cudaFuncAttributeMaxDynamicSharedMemorySize, W2_SMEM);
  launch(k_mod, 96, 256, 0, false, c, wmod);
  launch(k_lngemm<false>, 128, 384, LN_SMEM, true, mX, mQ, mQ);
  launch(k_attn, 128, 512, AT_SMEM, true, wo, w1, w3, w2);
  launch(k_wo, 128, 256, WO_SMEM, true, mO, x);
  launch(k_lngemm<true>, 128, 384, LN_SMEM, true, mX, m1, m3);
  launch(k_w2, 128, 288, W2_SMEM, true, m2, (bf16*)d_out);
}
```

```cpp
#include <cuda_runtime.h>
#include <cuda_bf16.h>
#include <cuda.h>
#include <stdint.h>
typedef __nv_bfloat16 bf16;
constexpr int S_ = 2048, D_ = 512, F_ = 1376;
__device__ __align__(1024) float g_mod[3072];
__device__ __align__(1024) bf16 g_qkv[192 * 2048 * 8];
__device__ __align__(1024) float g_kmax[32 * 128];
__device__ __align__(1024) bf16 g_o[16 * 64 * 128 * 8];
__device__ __align__(1024) bf16 g_x1[16 * 64 * 128 * 8];
__device__ __align__(1024) float2 g_st[2048 * 8];
__device__ __align__(1024) bf16 g_h[16 * 172 * 128 * 8];

__device__ __forceinline__ uint32_t smem_u32(const void* p) { return (uint32_t)__cvta_generic_to_shared(p); }
__device__ __forceinline__ void mbar_init(uint32_t b, int n) { asm volatile("mbarrier.init.shared::cta.b64 [%0],%1;" ::"r"(b), "r"(n) : "memory"); }
__device__ __forceinline__ void mbar_expect(uint32_t b, int bytes) { asm volatile("mbarrier.arrive.expect_tx.shared::cta.b64 _,[%0],%1;" ::"r"(b), "r"(bytes) : "memory"); }
__device__ __forceinline__ void mbar_arrive(uint32_t b) { asm volatile("mbarrier.arrive.shared::cta.b64 _,[%0];" ::"r"(b) : "memory"); }
__device__ __forceinline__ void mbar_wait(uint32_t b, int parity) {
  asm volatile("{\n.reg .pred p;\n.reg .u32 n;\nmov.u32 n,0;\nLW:\nmbarrier.try_wait.parity.shared::cta.b64 p,[%0],%1;\n@p bra LD;\n"
               "add.u32 n,n,1;\nsetp.lt.u32 p,n,4194304;\n@p bra LW;\nLD:\n}\n" ::"r"(b), "r"(parity) : "memory");
}
__device__ __forceinline__ void fence_init() { asm volatile("fence.mbarrier_init.release.cluster;" ::: "memory"); }
__device__ __forceinline__ void fence_async() { asm volatile("fence.proxy.async.shared::cta;" ::: "memory"); }
__device__ __forceinline__ void bulk_load(uint32_t dst, const void* src, int bytes, uint32_t bar) {
  asm volatile("cp.async.bulk.shared::cluster.global.mbarrier::complete_tx::bytes [%0],[%1],%2,[%3];" ::"r"(dst), "l"(src), "r"(bytes), "r"(bar) : "memory");
}
__device__ __forceinline__ void tma2d(uint32_t dst, const CUtensorMap* m, int c0, int c1, uint32_t bar) {
  asm volatile("cp.async.bulk.tensor.2d.shared::cluster.global.mbarrier::complete_tx::bytes [%0],[%1,{%3,%4}],[%2];" ::"r"(dst), "l"(m), "r"(bar), "r"(c0), "r"(c1) : "memory");
}
__device__ __forceinline__ void l2_prefetch(const void* p, int bytes) { asm volatile("cp.async.bulk.prefetch.L2.global [%0],%1;" ::"l"(p), "r"(bytes) : "memory"); }
__device__ __forceinline__ void pdl_launch() { asm volatile("griddepcontrol.launch_dependents;" ::: "memory"); }
__device__ __forceinline__ void pdl_wait() { asm volatile("griddepcontrol.wait;" ::: "memory"); }
__device__ __forceinline__ void wg_fence() { asm volatile("wgmma.fence.sync.aligned;" ::: "memory"); }
__device__ __forceinline__ void wg_commit() { asm volatile("wgmma.commit_group.sync.aligned;" ::: "memory"); }
template <int N> __device__ __forceinline__ void wg_wait() { asm volatile("wgmma.wait_group.sync.aligned %0;" ::"n"(N) : "memory"); }
template <int N> __device__ __forceinline__ void reg_fence(float (&d)[N]) {
#pragma unroll
  for (int i = 0; i < N; i++) asm volatile("" : "+f"(d[i])::"memory");
}
template <int N> __device__ __forceinline__ void zero(float (&d)[N]) {
#pragma unroll
  for (int i = 0; i < N; i++) d[i] = 0.f;
  reg_fence(d);
}
__device__ __forceinline__ uint64_t mk_desc(uint32_t addr, uint32_t lbo, uint32_t sbo, uint32_t mode) {
  return (uint64_t)((addr >> 4) & 0x3FFF) | ((uint64_t)(lbo >> 4) << 16) | ((uint64_t)(sbo >> 4) << 32) | ((uint64_t)mode << 62);
}
__device__ __forceinline__ void ldsm4(uint32_t a, uint32_t (&r)[4]) {
  asm volatile("ldmatrix.sync.aligned.m8n8.x4.shared.b16 {%0,%1,%2,%3},[%4];" : "=r"(r[0]), "=r"(r[1]), "=r"(r[2]), "=r"(r[3]) : "r"(a) : "memory");
}
__device__ __forceinline__ uint32_t pack_rn(float lo, float hi) { uint32_t r; asm("cvt.rn.bf16x2.f32 %0,%1,%2;" : "=r"(r) : "f"(hi), "f"(lo)); return r; }
__device__ __forceinline__ uint32_t pack_rz(float lo, float hi) { uint32_t r; asm("cvt.rz.bf16x2.f32 %0,%1,%2;" : "=r"(r) : "f"(hi), "f"(lo)); return r; }
__device__ __forceinline__ float blo(uint32_t u) { return __uint_as_float(u << 16); }
__device__ __forceinline__ float bhi(uint32_t u) { return __uint_as_float(u & 0xFFFF0000u); }
__device__ __forceinline__ float rbf(float x) { return __bfloat162float(__float2bfloat16_rn(x)); }
__device__ __forceinline__ float qsum(float v) { v += __shfl_xor_sync(~0u, v, 1); return v + __shfl_xor_sync(~0u, v, 2); }
__device__ __forceinline__ float ex2(float x) { float r; asm("ex2.approx.ftz.f32 %0,%1;" : "=f"(r) : "f"(x)); return r; }
__device__ __forceinline__ void wgmma_rs_n128_t0(float (&d)[64],uint32_t a0,uint32_t a1,uint32_t a2,uint32_t a3,uint64_t db,int sc){
  asm volatile("{\n.reg .pred p;\nsetp.ne.b32 p,%69,0;\n"
    "wgmma.mma_async.sync.aligned.m64n128k16.f32.bf16.bf16 {%0,%1,%2,%3,%4,%5,%6,%7,%8,%9,%10,%11,%12,%13,%14,%15,%16,%17,%18,%19,%20,%21,%22,%23,%24,%25,%26,%27,%28,%29,%30,%31,%32,%33,%34,%35,%36,%37,%38,%39,%40,%41,%42,%43,%44,%45,%46,%47,%48,%49,%50,%51,%52,%53,%54,%55,%56,%57,%58,%59,%60,%61,%62,%63},{%64,%65,%66,%67},%68,p,1,1,0;\n}\n"
    :"+f"(d[0]),"+f"(d[1]),"+f"(d[2]),"+f"(d[3]),"+f"(d[4]),"+f"(d[5]),"+f"(d[6]),"+f"(d[7]),"+f"(d[8]),"+f"(d[9]),"+f"(d[10]),"+f"(d[11]),"+f"(d[12]),"+f"(d[13]),"+f"(d[14]),"+f"(d[15]),"+f"(d[16]),"+f"(d[17]),"+f"(d[18]),"+f"(d[19]),"+f"(d[20]),"+f"(d[21]),"+f"(d[22]),"+f"(d[23]),"+f"(d[24]),"+f"(d[25]),"+f"(d[26]),"+f"(d[27]),"+f"(d[28]),"+f"(d[29]),"+f"(d[30]),"+f"(d[31]),"+f"(d[32]),"+f"(d[33]),"+f"(d[34]),"+f"(d[35]),"+f"(d[36]),"+f"(d[37]),"+f"(d[38]),"+f"(d[39]),"+f"(d[40]),"+f"(d[41]),"+f"(d[42]),"+f"(d[43]),"+f"(d[44]),"+f"(d[45]),"+f"(d[46]),"+f"(d[47]),"+f"(d[48]),"+f"(d[49]),"+f"(d[50]),"+f"(d[51]),"+f"(d[52]),"+f"(d[53]),"+f"(d[54]),"+f"(d[55]),"+f"(d[56]),"+f"(d[57]),"+f"(d[58]),"+f"(d[59]),"+f"(d[60]),"+f"(d[61]),"+f"(d[62]),"+f"(d[63])
    :"r"(a0),"r"(a1),"r"(a2),"r"(a3),"l"(db),"r"(sc));
}
__device__ __forceinline__ void wgmma_rs_n176_t1(float (&d)[88],uint32_t a0,uint32_t a1,uint32_t a2,uint32_t a3,uint64_t db,int sc){
  asm volatile("{\n.reg .pred p;\nsetp.ne.b32 p,%93,0;\n"
    "wgmma.mma_async.sync.aligned.m64n176k16.f32.bf16.bf16 {%0,%1,%2,%3,%4,%5,%6,%7,%8,%9,%10,%11,%12,%13,%14,%15,%16,%17,%18,%19,%20,%21,%22,%23,%24,%25,%26,%27,%28,%29,%30,%31,%32,%33,%34,%35,%36,%37,%38,%39,%40,%41,%42,%43,%44,%45,%46,%47,%48,%49,%50,%51,%52,%53,%54,%55,%56,%57,%58,%59,%60,%61,%62,%63,%64,%65,%66,%67,%68,%69,%70,%71,%72,%73,%74,%75,%76,%77,%78,%79,%80,%81,%82,%83,%84,%85,%86,%87},{%88,%89,%90,%91},%92,p,1,1,1;\n}\n"
    :"+f"(d[0]),"+f"(d[1]),"+f"(d[2]),"+f"(d[3]),"+f"(d[4]),"+f"(d[5]),"+f"(d[6]),"+f"(d[7]),"+f"(d[8]),"+f"(d[9]),"+f"(d[10]),"+f"(d[11]),"+f"(d[12]),"+f"(d[13]),"+f"(d[14]),"+f"(d[15]),"+f"(d[16]),"+f"(d[17]),"+f"(d[18]),"+f"(d[19]),"+f"(d[20]),"+f"(d[21]),"+f"(d[22]),"+f"(d[23]),"+f"(d[24]),"+f"(d[25]),"+f"(d[26]),"+f"(d[27]),"+f"(d[28]),"+f"(d[29]),"+f"(d[30]),"+f"(d[31]),"+f"(d[32]),"+f"(d[33]),"+f"(d[34]),"+f"(d[35]),"+f"(d[36]),"+f"(d[37]),"+f"(d[38]),"+f"(d[39]),"+f"(d[40]),"+f"(d[41]),"+f"(d[42]),"+f"(d[43]),"+f"(d[44]),"+f"(d[45]),"+f"(d[46]),"+f"(d[47]),"+f"(d[48]),"+f"(d[49]),"+f"(d[50]),"+f"(d[51]),"+f"(d[52]),"+f"(d[53]),"+f"(d[54]),"+f"(d[55]),"+f"(d[56]),"+f"(d[57]),"+f"(d[58]),"+f"(d[59]),"+f"(d[60]),"+f"(d[61]),"+f"(d[62]),"+f"(d[63]),"+f"(d[64]),"+f"(d[65]),"+f"(d[66]),"+f"(d[67]),"+f"(d[68]),"+f"(d[69]),"+f"(d[70]),"+f"(d[71]),"+f"(d[72]),"+f"(d[73]),"+f"(d[74]),"+f"(d[75]),"+f"(d[76]),"+f"(d[77]),"+f"(d[78]),"+f"(d[79]),"+f"(d[80]),"+f"(d[81]),"+f"(d[82]),"+f"(d[83]),"+f"(d[84]),"+f"(d[85]),"+f"(d[86]),"+f"(d[87])
    :"r"(a0),"r"(a1),"r"(a2),"r"(a3),"l"(db),"r"(sc));
}
__device__ __forceinline__ void wgmma_rs_n192_t1(float (&d)[96],uint32_t a0,uint32_t a1,uint32_t a2,uint32_t a3,uint64_t db,int sc){
  asm volatile("{\n.reg .pred p;\nsetp.ne.b32 p,%101,0;\n"
    "wgmma.mma_async.sync.aligned.m64n192k16.f32.bf16.bf16 {%0,%1,%2,%3,%4,%5,%6,%7,%8,%9,%10,%11,%12,%13,%14,%15,%16,%17,%18,%19,%20,%21,%22,%23,%24,%25,%26,%27,%28,%29,%30,%31,%32,%33,%34,%35,%36,%37,%38,%39,%40,%41,%42,%43,%44,%45,%46,%47,%48,%49,%50,%51,%52,%53,%54,%55,%56,%57,%58,%59,%60,%61,%62,%63,%64,%65,%66,%67,%68,%69,%70,%71,%72,%73,%74,%75,%76,%77,%78,%79,%80,%81,%82,%83,%84,%85,%86,%87,%88,%89,%90,%91,%92,%93,%94,%95},{%96,%97,%98,%99},%100,p,1,1,1;\n}\n"
    :"+f"(d[0]),"+f"(d[1]),"+f"(d[2]),"+f"(d[3]),"+f"(d[4]),"+f"(d[5]),"+f"(d[6]),"+f"(d[7]),"+f"(d[8]),"+f"(d[9]),"+f"(d[10]),"+f"(d[11]),"+f"(d[12]),"+f"(d[13]),"+f"(d[14]),"+f"(d[15]),"+f"(d[16]),"+f"(d[17]),"+f"(d[18]),"+f"(d[19]),"+f"(d[20]),"+f"(d[21]),"+f"(d[22]),"+f"(d[23]),"+f"(d[24]),"+f"(d[25]),"+f"(d[26]),"+f"(d[27]),"+f"(d[28]),"+f"(d[29]),"+f"(d[30]),"+f"(d[31]),"+f"(d[32]),"+f"(d[33]),"+f"(d[34]),"+f"(d[35]),"+f"(d[36]),"+f"(d[37]),"+f"(d[38]),"+f"(d[39]),"+f"(d[40]),"+f"(d[41]),"+f"(d[42]),"+f"(d[43]),"+f"(d[44]),"+f"(d[45]),"+f"(d[46]),"+f"(d[47]),"+f"(d[48]),"+f"(d[49]),"+f"(d[50]),"+f"(d[51]),"+f"(d[52]),"+f"(d[53]),"+f"(d[54]),"+f"(d[55]),"+f"(d[56]),"+f"(d[57]),"+f"(d[58]),"+f"(d[59]),"+f"(d[60]),"+f"(d[61]),"+f"(d[62]),"+f"(d[63]),"+f"(d[64]),"+f"(d[65]),"+f"(d[66]),"+f"(d[67]),"+f"(d[68]),"+f"(d[69]),"+f"(d[70]),"+f"(d[71]),"+f"(d[72]),"+f"(d[73]),"+f"(d[74]),"+f"(d[75]),"+f"(d[76]),"+f"(d[77]),"+f"(d[78]),"+f"(d[79]),"+f"(d[80]),"+f"(d[81]),"+f"(d[82]),"+f"(d[83]),"+f"(d[84]),"+f"(d[85]),"+f"(d[86]),"+f"(d[87]),"+f"(d[88]),"+f"(d[89]),"+f"(d[90]),"+f"(d[91]),"+f"(d[92]),"+f"(d[93]),"+f"(d[94]),"+f"(d[95])
    :"r"(a0),"r"(a1),"r"(a2),"r"(a3),"l"(db),"r"(sc));
}
__device__ __forceinline__ void wgmma_rs_n24_t1(float (&d)[12],uint32_t a0,uint32_t a1,uint32_t a2,uint32_t a3,uint64_t db,int sc){
  asm volatile("{\n.reg .pred p;\nsetp.ne.b32 p,%17,0;\n"
    "wgmma.mma_async.sync.aligned.m64n24k16.f32.bf16.bf16 {%0,%1,%2,%3,%4,%5,%6,%7,%8,%9,%10,%11},{%12,%13,%14,%15},%16,p,1,1,1;\n}\n"
    :"+f"(d[0]),"+f"(d[1]),"+f"(d[2]),"+f"(d[3]),"+f"(d[4]),"+f"(d[5]),"+f"(d[6]),"+f"(d[7]),"+f"(d[8]),"+f"(d[9]),"+f"(d[10]),"+f"(d[11])
    :"r"(a0),"r"(a1),"r"(a2),"r"(a3),"l"(db),"r"(sc));
}
__device__ __forceinline__ void wgmma_rs_n32_t0(float (&d)[16],uint32_t a0,uint32_t a1,uint32_t a2,uint32_t a3,uint64_t db,int sc){
  asm volatile("{\n.reg .pred p;\nsetp.ne.b32 p,%21,0;\n"
    "wgmma.mma_async.sync.aligned.m64n32k16.f32.bf16.bf16 {%0,%1,%2,%3,%4,%5,%6,%7,%8,%9,%10,%11,%12,%13,%14,%15},{%16,%17,%18,%19},%20,p,1,1,0;\n}\n"
    :"+f"(d[0]),"+f"(d[1]),"+f"(d[2]),"+f"(d[3]),"+f"(d[4]),"+f"(d[5]),"+f"(d[6]),"+f"(d[7]),"+f"(d[8]),"+f"(d[9]),"+f"(d[10]),"+f"(d[11]),"+f"(d[12]),"+f"(d[13]),"+f"(d[14]),"+f"(d[15])
    :"r"(a0),"r"(a1),"r"(a2),"r"(a3),"l"(db),"r"(sc));
}
__device__ __forceinline__ void wgmma_rs_n64_t0(float (&d)[32],uint32_t a0,uint32_t a1,uint32_t a2,uint32_t a3,uint64_t db,int sc){
  asm volatile("{\n.reg .pred p;\nsetp.ne.b32 p,%37,0;\n"
    "wgmma.mma_async.sync.aligned.m64n64k16.f32.bf16.bf16 {%0,%1,%2,%3,%4,%5,%6,%7,%8,%9,%10,%11,%12,%13,%14,%15,%16,%17,%18,%19,%20,%21,%22,%23,%24,%25,%26,%27,%28,%29,%30,%31},{%32,%33,%34,%35},%36,p,1,1,0;\n}\n"
    :"+f"(d[0]),"+f"(d[1]),"+f"(d[2]),"+f"(d[3]),"+f"(d[4]),"+f"(d[5]),"+f"(d[6]),"+f"(d[7]),"+f"(d[8]),"+f"(d[9]),"+f"(d[10]),"+f"(d[11]),"+f"(d[12]),"+f"(d[13]),"+f"(d[14]),"+f"(d[15]),"+f"(d[16]),"+f"(d[17]),"+f"(d[18]),"+f"(d[19]),"+f"(d[20]),"+f"(d[21]),"+f"(d[22]),"+f"(d[23]),"+f"(d[24]),"+f"(d[25]),"+f"(d[26]),"+f"(d[27]),"+f"(d[28]),"+f"(d[29]),"+f"(d[30]),"+f"(d[31])
    :"r"(a0),"r"(a1),"r"(a2),"r"(a3),"l"(db),"r"(sc));
}
__device__ __forceinline__ void wgmma_ss_n128_t1(float (&d)[64],uint64_t da,uint64_t db,int sc){
  asm volatile("{\n.reg .pred p;\nsetp.ne.b32 p,%66,0;\n"
    "wgmma.mma_async.sync.aligned.m64n128k16.f32.bf16.bf16 {%0,%1,%2,%3,%4,%5,%6,%7,%8,%9,%10,%11,%12,%13,%14,%15,%16,%17,%18,%19,%20,%21,%22,%23,%24,%25,%26,%27,%28,%29,%30,%31,%32,%33,%34,%35,%36,%37,%38,%39,%40,%41,%42,%43,%44,%45,%46,%47,%48,%49,%50,%51,%52,%53,%54,%55,%56,%57,%58,%59,%60,%61,%62,%63},%64,%65,p,1,1,0,1;\n}\n"
    :"+f"(d[0]),"+f"(d[1]),"+f"(d[2]),"+f"(d[3]),"+f"(d[4]),"+f"(d[5]),"+f"(d[6]),"+f"(d[7]),"+f"(d[8]),"+f"(d[9]),"+f"(d[10]),"+f"(d[11]),"+f"(d[12]),"+f"(d[13]),"+f"(d[14]),"+f"(d[15]),"+f"(d[16]),"+f"(d[17]),"+f"(d[18]),"+f"(d[19]),"+f"(d[20]),"+f"(d[21]),"+f"(d[22]),"+f"(d[23]),"+f"(d[24]),"+f"(d[25]),"+f"(d[26]),"+f"(d[27]),"+f"(d[28]),"+f"(d[29]),"+f"(d[30]),"+f"(d[31]),"+f"(d[32]),"+f"(d[33]),"+f"(d[34]),"+f"(d[35]),"+f"(d[36]),"+f"(d[37]),"+f"(d[38]),"+f"(d[39]),"+f"(d[40]),"+f"(d[41]),"+f"(d[42]),"+f"(d[43]),"+f"(d[44]),"+f"(d[45]),"+f"(d[46]),"+f"(d[47]),"+f"(d[48]),"+f"(d[49]),"+f"(d[50]),"+f"(d[51]),"+f"(d[52]),"+f"(d[53]),"+f"(d[54]),"+f"(d[55]),"+f"(d[56]),"+f"(d[57]),"+f"(d[58]),"+f"(d[59]),"+f"(d[60]),"+f"(d[61]),"+f"(d[62]),"+f"(d[63])
    :"l"(da),"l"(db),"r"(sc));
}
__device__ __forceinline__ void wgmma_ss_n64_t1(float (&d)[32],uint64_t da,uint64_t db,int sc){
  asm volatile("{\n.reg .pred p;\nsetp.ne.b32 p,%34,0;\n"
    "wgmma.mma_async.sync.aligned.m64n64k16.f32.bf16.bf16 {%0,%1,%2,%3,%4,%5,%6,%7,%8,%9,%10,%11,%12,%13,%14,%15,%16,%17,%18,%19,%20,%21,%22,%23,%24,%25,%26,%27,%28,%29,%30,%31},%32,%33,p,1,1,0,1;\n}\n"
    :"+f"(d[0]),"+f"(d[1]),"+f"(d[2]),"+f"(d[3]),"+f"(d[4]),"+f"(d[5]),"+f"(d[6]),"+f"(d[7]),"+f"(d[8]),"+f"(d[9]),"+f"(d[10]),"+f"(d[11]),"+f"(d[12]),"+f"(d[13]),"+f"(d[14]),"+f"(d[15]),"+f"(d[16]),"+f"(d[17]),"+f"(d[18]),"+f"(d[19]),"+f"(d[20]),"+f"(d[21]),"+f"(d[22]),"+f"(d[23]),"+f"(d[24]),"+f"(d[25]),"+f"(d[26]),"+f"(d[27]),"+f"(d[28]),"+f"(d[29]),"+f"(d[30]),"+f"(d[31])
    :"l"(da),"l"(db),"r"(sc));
}

__global__ void __launch_bounds__(256) k_mod(const bf16* __restrict__ c, const bf16* __restrict__ w) {
  pdl_launch();
  __shared__ float red[8][32];
  const int t = threadIdx.x, n0 = blockIdx.x * 32 + (t & 3) * 8, r0 = t >> 2;
  uint4 v[8];
  float cs[8];
#pragma unroll
  for (int i = 0; i < 8; i++) v[i] = __ldg((const uint4*)(w + (size_t)(r0 + i * 64) * 3072 + n0));
#pragma unroll
  for (int i = 0; i < 8; i++) { float x = __bfloat162float(c[r0 + i * 64]); cs[i] = rbf(x / (1.f + __expf(-x))); }
  float a[8] = {0, 0, 0, 0, 0, 0, 0, 0};
#pragma unroll
  for (int i = 0; i < 8; i++) {
    a[0] += cs[i] * blo(v[i].x); a[1] += cs[i] * bhi(v[i].x); a[2] += cs[i] * blo(v[i].y); a[3] += cs[i] * bhi(v[i].y);
    a[4] += cs[i] * blo(v[i].z); a[5] += cs[i] * bhi(v[i].z); a[6] += cs[i] * blo(v[i].w); a[7] += cs[i] * bhi(v[i].w);
  }
#pragma unroll
  for (int j = 0; j < 8; j++) {
    a[j] += __shfl_xor_sync(~0u, a[j], 4); a[j] += __shfl_xor_sync(~0u, a[j], 8); a[j] += __shfl_xor_sync(~0u, a[j], 16);
  }
  if ((t & 31) < 4) {
#pragma unroll
    for (int j = 0; j < 8; j++) red[t >> 5][(t & 3) * 8 + j] = a[j];
  }
  __syncthreads();
  if (t < 32) {
    float s = 0;
#pragma unroll
    for (int i = 0; i < 8; i++) s += red[i][t];
    const int n = blockIdx.x * 32 + t, seg = n >> 9;
    s = rbf(s);
    if (seg == 1 || seg == 4) s = rbf(1.f + s);
    g_mod[n] = s;
  }
}

constexpr int LN_SMEM = 131072 + 4 * 24576 + 2048 + 256;
template <bool FFN>
__global__ void __launch_bounds__(384, 1) k_lngemm(const __grid_constant__ CUtensorMap mX, const __grid_constant__ CUtensorMap mB0,
                                                   const __grid_constant__ CUtensorMap mB1) {
  extern __shared__ __align__(1024) uint8_t smem[];
  const uint32_t sA = smem_u32(smem), sB = sA + 131072, sM = sB + 4 * 24576, bars = sM + 2048;
  const uint32_t bA = bars, bF = bars + 64, bE = bars + 96;
  const int tid = threadIdx.x, warp = tid >> 5, lane = tid & 31;
  const int rb = blockIdx.x >> 3, ct = blockIdx.x & 7;
  constexpr int NST = FFN ? 16 : 8, KS = FFN ? 2 : 4, BOX = FFN ? 4096 : 8192;
  pdl_launch();
  if (tid == 256) {
    for (int i = 0; i < 8; i++) mbar_init(bA + 8 * i, 1);
    for (int i = 0; i < 4; i++) { mbar_init(bF + 8 * i, 1); mbar_init(bE + 8 * i, 8); }
    fence_init();
  }
  __syncthreads();
  if (warp >= 8) {
    asm volatile("setmaxnreg.dec.sync.aligned.u32 40;");
    if (tid == 256) {
      auto loadB = [&](int s) {
        const uint32_t d = sB + (s & 3) * 24576, b = bF + (s & 3) * 8;
        mbar_expect(b, 24576);
        for (int j = 0; j < 3; j++) {
          if (FFN) { tma2d(d + j * BOX, &mB0, ct * 176 + j * 64, s * 32, b); tma2d(d + (3 + j) * BOX, &mB1, ct * 176 + j * 64, s * 32, b); }
          else tma2d(d + j * BOX, &mB0, ct * 192 + j * 64, s * 64, b);
        }
      };
      if (!FFN) for (int i = 0; i < 8; i++) { mbar_expect(bA + 8 * i, 16384); tma2d(sA + i * 16384, &mX, i * 64, rb * 128, bA + 8 * i); }
      for (int s = 0; s < 4; s++) loadB(s);
      if (FFN) {
        pdl_wait();
        for (int i = 0; i < 8; i++) { mbar_expect(bA + 8 * i, 16384); bulk_load(sA + i * 16384, g_x1 + (rb * 64 + i * 8) * 1024, 16384, bA + 8 * i); }
      }
      for (int s = 4; s < NST; s++) { mbar_wait(bE + (s & 3) * 8, ((s >> 2) - 1) & 1); loadB(s); }
    }
  } else {
  asm volatile("setmaxnreg.inc.sync.aligned.u32 232;");
  const int g = lane >> 2, t = lane & 3;
  const int lr = warp * 16 + (lane & 7) + ((lane >> 3) & 1) * 8;
  auto aaddr = [&](int ks) -> uint32_t {
    if (FFN) return sA + (ks * 2 + (lane >> 4)) * 2048 + lr * 16;
    return sA + (ks >> 2) * 16384 + lr * 128 + ((((ks & 3) * 2 + (lane >> 4)) ^ (lr & 7)) << 4);
  };
  const int row0 = rb * 128 + warp * 16 + g;
  float rs0, rs1, nm0, nm1;
  if (!FFN) {
    float s0 = 0, s1 = 0;
#pragma unroll 4
    for (int ks = 0; ks < 32; ks++) {
      if ((ks & 3) == 0) mbar_wait(bA + 2 * ks, 0);
      uint32_t r[4]; ldsm4(aaddr(ks), r);
      s0 += (blo(r[0]) + bhi(r[0])) + (blo(r[2]) + bhi(r[2]));
      s1 += (blo(r[1]) + bhi(r[1])) + (blo(r[3]) + bhi(r[3]));
    }
    const float m0 = qsum(s0) * (1.f / 512), m1 = qsum(s1) * (1.f / 512);
    float v0 = 0, v1 = 0, v2 = 0, v3 = 0;
#pragma unroll 4
    for (int ks = 0; ks < 32; ks++) {
      uint32_t r[4]; ldsm4(aaddr(ks), r);
      float d;
      d = blo(r[0]) - m0; v0 += d * d; d = bhi(r[0]) - m0; v2 += d * d; d = blo(r[2]) - m0; v0 += d * d; d = bhi(r[2]) - m0; v2 += d * d;
      d = blo(r[1]) - m1; v1 += d * d; d = bhi(r[1]) - m1; v3 += d * d; d = blo(r[3]) - m1; v1 += d * d; d = bhi(r[3]) - m1; v3 += d * d;
    }
    rs0 = rsqrtf(qsum(v0 + v2) * (1.f / 512) + 1e-5f); rs1 = rsqrtf(qsum(v1 + v3) * (1.f / 512) + 1e-5f);
    nm0 = -m0 * rs0; nm1 = -m1 * rs1;
    pdl_wait();
  } else {
    pdl_wait();
    const float4 p0 = *(const float4*)(g_st + row0 * 8 + t * 2), p1 = *(const float4*)(g_st + (row0 + 8) * 8 + t * 2);
    const float m0 = qsum(p0.x + p0.z) * 0.125f, m1 = qsum(p1.x + p1.z) * 0.125f;
    const float v0 = qsum(p0.y + p0.w + 64.f * ((p0.x - m0) * (p0.x - m0) + (p0.z - m0) * (p0.z - m0)));
    const float v1 = qsum(p1.y + p1.w + 64.f * ((p1.x - m1) * (p1.x - m1) + (p1.z - m1) * (p1.z - m1)));
    rs0 = rsqrtf(v0 * (1.f / 512) + 1e-5f); rs1 = rsqrtf(v1 * (1.f / 512) + 1e-5f);
    nm0 = -m0 * rs0; nm1 = -m1 * rs1;
  }
  {
    const float2 sh = *(const float2*)(g_mod + (FFN ? 1536 : 0) + tid * 2), sc = *(const float2*)(g_mod + (FFN ? 2048 : 512) + tid * 2);
    uint32_t* m = (uint32_t*)(smem + (sM - sA)) + (tid >> 3) * 16 + (tid & 3) * 4 + ((tid >> 2) & 1);
    m[0] = pack_rn(sc.x, sc.y); m[2] = pack_rn(sh.x, sh.y);
    asm volatile("bar.sync 1,256;" ::: "memory");
  }
  constexpr int NA = FFN ? 88 : 96;
  float acc0[NA], acc1[FFN ? 88 : 1];
  uint32_t a[2][4];
  auto prep = [&](int ks, uint32_t(&o)[4]) {
    if (FFN && (ks & 3) == 0) mbar_wait(bA + 2 * ks, 0);
    uint32_t r[4]; ldsm4(aaddr(ks), r);
    const uint4 m = *(const uint4*)(smem + (sM - sA) + ks * 64 + t * 16);
#pragma unroll
    for (int i = 0; i < 4; i++) {
      const float rs = (i & 1) ? rs1 : rs0, nm = (i & 1) ? nm1 : nm0;
      const uint32_t n = pack_rn(fmaf(blo(r[i]), rs, nm), fmaf(bhi(r[i]), rs, nm));
      asm("fma.rn.bf16x2 %0,%1,%2,%3;" : "=r"(o[i]) : "r"(n), "r"(i < 2 ? m.x : m.y), "r"(i < 2 ? m.z : m.w));
    }
  };
  prep(0, a[0]);
#pragma unroll 1
  for (int s = 0; s < NST; s++) {
    mbar_wait(bF + (s & 3) * 8, (s >> 2) & 1);
    const uint64_t db = mk_desc(sB + (s & 3) * 24576, BOX, 1024, 1);
#pragma unroll
    for (int k = 0; k < KS; k++) {
      const int ks = s * KS + k;
      uint32_t(&c)[4] = a[k & 1];
      wg_fence();
      if constexpr (FFN) {
        wgmma_rs_n176_t1(acc0, c[0], c[1], c[2], c[3], db + k * 128, ks);
        wgmma_rs_n176_t1(acc1, c[0], c[1], c[2], c[3], db + k * 128 + 3 * BOX / 16, ks);
      } else {
        wgmma_rs_n192_t1(acc0, c[0], c[1], c[2], c[3], db + k * 128, ks);
      }
      wg_commit();
      wg_wait<1>();
      if (k == 0 && s > 0 && lane == 0) mbar_arrive(bE + ((s - 1) & 3) * 8);
      if (ks < 31) prep(ks + 1, a[(k + 1) & 1]);
    }
  }
  wg_wait<0>();
  reg_fence(acc0);
  if constexpr (FFN) {
    reg_fence(acc1);
    uint32_t* o = (uint32_t*)g_h + ((rb * 172 + ct * 22) * 128 + warp * 16 + g) * 4 + t;
#pragma unroll
    for (int j = 0; j < 22; j++) {
      if (ct * 22 + j < 172) {
        float h[4];
#pragma unroll
        for (int i = 0; i < 4; i++) { const float x = acc0[4 * j + i]; h[i] = __fdividef(x, 1.f + ex2(-1.4426950408889634f * x)) * acc1[4 * j + i]; }
        o[j * 512] = pack_rn(h[0], h[1]);
        o[j * 512 + 32] = pack_rn(h[2], h[3]);
      }
    }
  } else {
    uint32_t* o = (uint32_t*)g_qkv + (ct * 24 * 2048 + row0) * 4 + t;
#pragma unroll
    for (int j = 0; j < 24; j += 2) {
      const int G = ct * 24 + j;
      const float sc = G < 64 ? 0.25f * 1.4426950408889634f : 1.f;
      uint32_t p[4];
#pragma unroll
      for (int i = 0; i < 4; i++) p[i] = pack_rn(acc0[4 * j + 2 * i] * sc, acc0[4 * j + 2 * i + 1] * sc);
      o[j * 8192] = p[0]; o[j * 8192 + 32] = p[1]; o[(j + 1) * 8192] = p[2]; o[(j + 1) * 8192 + 32] = p[3];
      if (G >= 64 && G < 128) {
        float n0 = blo(p[0]) * blo(p[0]) + bhi(p[0]) * bhi(p[0]) + blo(p[2]) * blo(p[2]) + bhi(p[2]) * bhi(p[2]);
        float n1 = blo(p[1]) * blo(p[1]) + bhi(p[1]) * bhi(p[1]) + blo(p[3]) * blo(p[3]) + bhi(p[3]) * bhi(p[3]);
        n0 = qsum(n0); n1 = qsum(n1);
        const uint32_t mx = __reduce_max_sync(~0u, max(__float_as_uint(n0), __float_as_uint(n1)));
        if (lane == 0) g_kmax[((G - 64) >> 1) * 128 + rb * 8 + warp] = __uint_as_float(mx);
      }
    }
  }
}
}

#define POLYMASK 0xA54AA54Au
#define BRK 0
#define AUG 0
constexpr int AT_SMEM = 5 * 32768 + 256;
__device__ __forceinline__ uint32_t exp2_pair_fma(float s0, float s1, float c, uint32_t k256) {
  uint32_t r;
  asm volatile("{\n.reg .f32 y0,y1,u0,u1,t0,t1;\n.reg .b32 e,m;\n"
      "fma.rn.sat.f32 y0,%1,0f00008000,%3;\nfma.rn.sat.f32 y1,%2,0f00008000,%3;\n"
      "lop3.b32 u0,y0,0x7FFF,%4,0xEA;\nlop3.b32 u1,y1,0x7FFF,%4,0xEA;\n"
      "fma.rn.f32 u0,u0,0f3EDAF929,0fC2DA25F3;\nfma.rn.f32 u1,u1,0f3EDAF929,0fC2DA25F3;\n"
      "fma.rn.f32 t0,u0,u0,0f3F8EC750;\nfma.rn.f32 t1,u1,u1,0f3F8EC750;\n"
      "fma.rn.f32 t0,t0,u0,0f3EF07623;\nfma.rn.f32 t1,t1,u1,0f3EF07623;\n"
      "prmt.b32 e,y0,y1,0x6521;\ncvt.rz.bf16x2.f32 m,t1,t0;\nlop3.b32 %0,e,0x7F807F80,m,0xE2;\n}\n"
      : "=r"(r) : "f"(s0), "f"(s1), "f"(c), "r"(k256));
  return r;
}
#define NK 64
#define PP 0
template <uint32_t MASK, bool AG>
__device__ __forceinline__ void attn_pass(float (&o)[12], const uint32_t (&q)[4], float m0, float m1, uint32_t sK, uint32_t bars, bool first, uint32_t k256) {
  const uint64_t dk = mk_desc(sK, 32768, 128, 0), dv = mk_desc(sK + 65536, 128, 32768, 0), d1 = mk_desc(sK + 131072, 128, 128, 0);
  const float c0 = (AG ? 127.f : 127.f - m0) * __uint_as_float(0x8000u), c1 = (AG ? 127.f : 127.f - m1) * __uint_as_float(0x8000u);
  const uint32_t am0 = (threadIdx.x & 3) ? 0u : (__float_as_uint(-m0) >> 16), am1 = (threadIdx.x & 3) ? 0u : (__float_as_uint(-m1) >> 16);
  constexpr int NS = NK / 2, NP = NK / 4, NI = 2048 / NK;
  auto qk = [&](float (&s)[NS], int i) {
    if (AG) wgmma_rs_n64_t0(s, am0, am1, 0, 0, d1, 0);
    wgmma_rs_n64_t0(s, q[0], q[1], q[2], q[3], dk + i * NK, AG);
  };
  auto softmax = [&](float (&s)[NS], uint32_t (&p)[NP], uint32_t mask) {
    reg_fence(s);
    float e0, e1;
    int pend = -1;
#pragma unroll
    for (int j = 0; j < NP; j++) {
      if ((mask >> j) & 1) {
        p[j] = exp2_pair_fma(s[2 * j], s[2 * j + 1], (j & 1) ? c1 : c0, k256);
      } else {
        const float m = AG ? 0.f : (j & 1) ? m1 : m0;
        float f0, f1;
        if (AG) { f0 = s[2 * j]; f1 = s[2 * j + 1]; }
        else asm volatile("sub.f32 %0,%2,%4;\nsub.f32 %1,%3,%4;" : "=&f"(f0), "=f"(f1) : "f"(s[2 * j]), "f"(s[2 * j + 1]), "f"(m));
        asm volatile("ex2.approx.ftz.f32 %0,%0;\nex2.approx.ftz.f32 %1,%1;" : "+f"(f0), "+f"(f1));
        if (pend >= 0) asm volatile("cvt.rz.bf16x2.f32 %0,%1,%2;" : "=r"(p[pend]) : "f"(e1), "f"(e0));
        e0 = f0; e1 = f1; pend = j;
      }
    }
    if (pend >= 0) asm volatile("cvt.rz.bf16x2.f32 %0,%1,%2;" : "=r"(p[pend]) : "f"(e1), "f"(e0));
#pragma unroll
    for (int j = 0; j < NP; j++) asm volatile("" : "+r"(p[j])::"memory");
  };
  auto pv = [&](uint32_t (&p)[NP], int i) {
#pragma unroll
    for (int k = 0; k < NK / 16; k++) wgmma_rs_n24_t1(o, p[4 * k], p[4 * k + 1], p[4 * k + 2], p[4 * k + 3], dv + i * NK + k * 16, 1);
  };
  auto ld = [&](int i) { if (first && (i & (NI / 4 - 1)) == 0) mbar_wait(bars + i / (NI / 4) * 8, 0); };
  constexpr uint32_t M0 = MASK, M1 = NK == 128 ? MASK : MASK >> NP;
  zero(o);
  ld(0);
  float s[NS];
  zero(s);
  uint32_t p[NP];
  wg_fence(); qk(s, 0); wg_commit(); wg_wait<0>(); softmax(s, p, M0);
#pragma unroll 1
  for (int i = 0; i < NI - 2; i += 2) {
    wg_fence(); qk(s, i + 1); pv(p, i); wg_commit(); wg_wait<0>(); softmax(s, p, M1);
    ld(i + 2);
    wg_fence(); qk(s, i + 2); pv(p, i + 1); wg_commit(); wg_wait<0>(); softmax(s, p, M0);
  }
  wg_fence(); qk(s, NI - 1); pv(p, NI - 2); wg_commit(); wg_wait<0>(); softmax(s, p, M1);
  wg_fence(); pv(p, NI - 1); wg_commit();
  wg_wait<0>();
  reg_fence(o);
}
__device__ __forceinline__ void mma16816(float (&d)[4], const uint32_t (&a)[4], uint32_t b0, uint32_t b1) {
  asm("mma.sync.aligned.m16n8k16.row.col.f32.bf16.bf16.f32 {%0,%1,%2,%3},{%4,%5,%6,%7},{%8,%9},{%0,%1,%2,%3};"
      : "+f"(d[0]), "+f"(d[1]), "+f"(d[2]), "+f"(d[3]) : "r"(a[0]), "r"(a[1]), "r"(a[2]), "r"(a[3]), "r"(b0), "r"(b1));
}
__device__ __forceinline__ void attn_safe(float (&o)[12], const uint32_t (&q)[4], uint32_t sK) {
  const int lane = threadIdx.x & 31;
  const uint32_t ka = sK + (lane >> 4) * 32768 + (lane & 15) * 16;
  float m0 = -INFINITY, m1 = -INFINITY;
#pragma unroll 2
  for (int i = 0; i < 128; i++) {
    uint32_t k[4]; ldsm4(ka + i * 256, k);
    float s0[4] = {0, 0, 0, 0}, s1[4] = {0, 0, 0, 0};
    mma16816(s0, q, k[0], k[2]); mma16816(s1, q, k[1], k[3]);
    m0 = fmaxf(fmaxf(m0, fmaxf(s0[0], s0[1])), fmaxf(s1[0], s1[1])); m1 = fmaxf(fmaxf(m1, fmaxf(s0[2], s0[3])), fmaxf(s1[2], s1[3]));
  }
  m0 = fmaxf(m0, __shfl_xor_sync(~0u, m0, 1)); m0 = fmaxf(m0, __shfl_xor_sync(~0u, m0, 2));
  m1 = fmaxf(m1, __shfl_xor_sync(~0u, m1, 1)); m1 = fmaxf(m1, __shfl_xor_sync(~0u, m1, 2));
  float o0[4] = {0, 0, 0, 0}, o1[4] = {0, 0, 0, 0}, o2[4] = {0, 0, 0, 0};
#pragma unroll 2
  for (int i = 0; i < 128; i++) {
    uint32_t k[4], v[4]; ldsm4(ka + i * 256, k);
    asm volatile("ldmatrix.sync.aligned.m8n8.x4.trans.shared.b16 {%0,%1,%2,%3},[%4];" : "=r"(v[0]), "=r"(v[1]), "=r"(v[2]), "=r"(v[3]) : "r"(ka + 65536 + i * 256) : "memory");
    float s0[4] = {0, 0, 0, 0}, s1[4] = {0, 0, 0, 0};
    mma16816(s0, q, k[0], k[2]); mma16816(s1, q, k[1], k[3]);
    const uint32_t p[4] = {pack_rn(ex2(s0[0] - m0), ex2(s0[1] - m0)), pack_rn(ex2(s0[2] - m1), ex2(s0[3] - m1)),
                           pack_rn(ex2(s1[0] - m0), ex2(s1[1] - m0)), pack_rn(ex2(s1[2] - m1), ex2(s1[3] - m1))};
    mma16816(o0, p, v[0], v[1]); mma16816(o1, p, v[2], v[3]); mma16816(o2, p, 0x3F803F80u, 0x3F803F80u);
  }
#pragma unroll
  for (int i = 0; i < 4; i++) { o[i] = o0[i]; o[4 + i] = o1[i]; o[8 + i] = o2[i]; }
}
__global__ void __launch_bounds__(512, 1) k_attn(const bf16* wo, const bf16* w1, const bf16* w3, const bf16* w2, uint32_t k256) {
  extern __shared__ __align__(1024) uint8_t smem[];
  const uint32_t sK = smem_u32(smem), bars = sK + 5 * 32768;
  const int tid = threadIdx.x, warp = tid >> 5, lane = tid & 31, g = lane >> 2, t = lane & 3;
  const int h = blockIdx.x >> 2, qb = blockIdx.x & 3;
  pdl_launch();
  if (tid == 0) { for (int i = 0; i < 4; i++) mbar_init(bars + 8 * i, 1); fence_init(); }
#pragma unroll
  for (int i = 0; i < 4; i++) *(uint4*)(smem + 131072 + i * 8192 + tid * 16) = make_uint4(0x3F803F80u, 0x3F803F80u, 0x3F803F80u, 0x3F803F80u);
  fence_async();
  __syncthreads();
  pdl_wait();
  if (tid == 0) {
    for (int c = 0; c < 4; c++) {
      mbar_expect(bars + 8 * c, 32768);
      for (int pl = 0; pl < 4; pl++)
        bulk_load(sK + pl * 32768 + c * 8192, g_qkv + ((64 + (pl >> 1) * 64 + h * 2 + (pl & 1)) * 2048 + c * 512) * 8, 8192, bars + 8 * c);
    }
  }
  if (tid == 32) {
    l2_prefetch((const char*)wo + blockIdx.x * 4096, 4096);
    l2_prefetch((const char*)w1 + blockIdx.x * 11008, 11008);
    l2_prefetch((const char*)w3 + blockIdx.x * 11008, 11008);
    l2_prefetch((const char*)w2 + blockIdx.x * 11008, 11008);
  }
  const uint4 km4 = *(const uint4*)(g_kmax + h * 128 + lane * 4);
  const float kmax = __uint_as_float(__reduce_max_sync(~0u, max(max(km4.x, km4.y), max(km4.z, km4.w))));
#pragma unroll 1
  for (int tile = 0; tile < 2; tile++) {
    const int row = qb * 512 + tile * 256 + warp * 16 + g;
    const uint32_t* qp = (const uint32_t*)g_qkv + (h * 2 * 2048 + row) * 4 + t;
    uint32_t q[4] = {qp[0], qp[32], qp[8192], qp[8192 + 32]};
    const float n0 = qsum(blo(q[0]) * blo(q[0]) + bhi(q[0]) * bhi(q[0]) + blo(q[2]) * blo(q[2]) + bhi(q[2]) * bhi(q[2]));
    const float n1 = qsum(blo(q[1]) * blo(q[1]) + bhi(q[1]) * bhi(q[1]) + blo(q[3]) * blo(q[3]) + bhi(q[3]) * bhi(q[3]));
    const float b0 = sqrtf(n0 * kmax) * 1.001f, b1 = sqrtf(n1 * kmax) * 1.001f;
    float m0 = ceilf(b0 - 100.f), m1 = ceilf(b1 - 100.f);
    if (AUG) { m0 = __bfloat162float(__float2bfloat16_ru(m0)); m1 = __bfloat162float(__float2bfloat16_ru(m1)); }
    float o[12];
    attn_pass<POLYMASK, AUG>(o, q, m0, m1, sK, bars, tile == 0, k256);
    bool ok = b0 < 1e4f && b1 < 1e4f && o[8] >= 0x1p-90f && o[10] >= 0x1p-90f;
#pragma unroll
    for (int i = 0; i < 12; i++) ok = ok && fabsf(o[i]) < INFINITY;
    if (!__all_sync(~0u, ok)) attn_safe(o, q, sK);
    const float r0 = 1.f / o[8], r1 = 1.f / o[10];
    uint32_t* op = (uint32_t*)g_o + (((row >> 7) * 64 + h * 2) * 128 + (row & 127)) * 4 + t;
    op[0] = pack_rn(o[0] * r0, o[1] * r0); op[32] = pack_rn(o[2] * r1, o[3] * r1);
    op[512] = pack_rn(o[4] * r0, o[5] * r0); op[512 + 32] = pack_rn(o[6] * r1, o[7] * r1);
  }
}

constexpr int WO_SMEM = 131072 + 65536 + 256;
__global__ void __launch_bounds__(256, 1) k_wo(const __grid_constant__ CUtensorMap mW, const bf16* __restrict__ x) {
  extern __shared__ __align__(1024) uint8_t smem[];
  const uint32_t sA = smem_u32(smem), sB = sA + 131072, bars = sB + 65536;
  const int tid = threadIdx.x, warp = tid >> 5, lane = tid & 31, g = lane >> 2, t = lane & 3;
  const int rb = blockIdx.x >> 3, ct = blockIdx.x & 7;
  pdl_launch();
  if (tid == 0) {
    for (int i = 0; i < 8; i++) mbar_init(bars + 8 * i, 1);
    fence_init();
    for (int i = 0; i < 8; i++) { mbar_expect(bars + 8 * i, 24576); tma2d(sB + i * 8192, &mW, ct * 64, i * 64, bars + 8 * i); }
  }
  const int lrow = warp * 16 + g;
  uint32_t xr[16];
  const uint32_t* xp = (const uint32_t*)(x + (rb * 128 + lrow) * 512 + ct * 64) + t;
#pragma unroll
  for (int j = 0; j < 8; j++) { xr[2 * j] = __ldg(xp + j * 4); xr[2 * j + 1] = __ldg(xp + j * 4 + 8 * 256); }
  __syncthreads();
  pdl_wait();
  if (tid == 0) for (int i = 0; i < 8; i++) bulk_load(sA + i * 16384, g_o + (rb * 64 + i * 8) * 1024, 16384, bars + 8 * i);
  float2 ga[8];
#pragma unroll
  for (int j = 0; j < 8; j++) ga[j] = *(const float2*)(g_mod + 1024 + ct * 64 + j * 8 + t * 2);
  float acc[32];
  const uint64_t da = mk_desc(sA + (warp >> 2) * 1024, 2048, 128, 0), db = mk_desc(sB, 8192, 1024, 1);
#pragma unroll
  for (int c = 0; c < 8; c++) {
    mbar_wait(bars + 8 * c, 0);
    wg_fence();
#pragma unroll
    for (int k = 0; k < 4; k++) wgmma_ss_n64_t1(acc, da + (c * 4 + k) * 256, db + (c * 4 + k) * 128, c + k);
    wg_commit();
  }
  wg_wait<0>();
  reg_fence(acc);
  uint32_t* o = (uint32_t*)g_x1 + ((rb * 64 + ct * 8) * 128 + lrow) * 4 + t;
  float s0 = 0, s1 = 0;
#pragma unroll
  for (int j = 0; j < 8; j++) {
    xr[2 * j] = pack_rn(fmaf(ga[j].x, acc[4 * j], blo(xr[2 * j])), fmaf(ga[j].y, acc[4 * j + 1], bhi(xr[2 * j])));
    xr[2 * j + 1] = pack_rn(fmaf(ga[j].x, acc[4 * j + 2], blo(xr[2 * j + 1])), fmaf(ga[j].y, acc[4 * j + 3], bhi(xr[2 * j + 1])));
    o[j * 512] = xr[2 * j]; o[j * 512 + 32] = xr[2 * j + 1];
    s0 += blo(xr[2 * j]) + bhi(xr[2 * j]); s1 += blo(xr[2 * j + 1]) + bhi(xr[2 * j + 1]);
  }
  const float m0 = qsum(s0) * (1.f / 64), m1 = qsum(s1) * (1.f / 64);
  float v0 = 0, v1 = 0;
#pragma unroll
  for (int j = 0; j < 8; j++) {
    float d;
    d = blo(xr[2 * j]) - m0; v0 += d * d; d = bhi(xr[2 * j]) - m0; v0 += d * d;
    d = blo(xr[2 * j + 1]) - m1; v1 += d * d; d = bhi(xr[2 * j + 1]) - m1; v1 += d * d;
  }
  v0 = qsum(v0); v1 = qsum(v1);
  if (t == 0) g_st[(rb * 128 + lrow) * 8 + ct] = make_float2(m0, v0);
  if (t == 1) g_st[(rb * 128 + lrow + 8) * 8 + ct] = make_float2(m1, v1);
}

constexpr int W2_SMEM = 6 * 32768 + 32768 + 256;
__global__ void __cluster_dims__(2, 1, 1) __launch_bounds__(288, 1) k_w2(const __grid_constant__ CUtensorMap mW, bf16* __restrict__ out) {
  extern __shared__ __align__(1024) uint8_t smem[];
  const uint32_t sR = smem_u32(smem), sX = sR + 6 * 32768, bF = sX + 32768, bE = bF + 48;
  const int tid = threadIdx.x, warp = tid >> 5, lane = tid & 31, g = lane >> 2, t = lane & 3;
  const int kh = blockIdx.x & 1, ct = (blockIdx.x >> 1) & 3, rb = blockIdx.x >> 3;
  pdl_launch();
  if (tid == 256) {
    for (int i = 0; i < 6; i++) { mbar_init(bF + 8 * i, 1); mbar_init(bE + 8 * i, 8); }
    fence_init();
  }
  __syncthreads();
  asm volatile("barrier.cluster.arrive.relaxed.aligned;" ::: "memory");
  if (warp == 8) {
    if (lane == 0) {
      auto abytes = [&](int s) { return (kh == 1 && s == 10) ? 8192 : 16384; };
      auto loadB = [&](int s) {
        const int st = s % 6;
        mbar_expect(bF + 8 * st, 16384 + abytes(s));
        for (int j = 0; j < 2; j++) tma2d(sR + st * 32768 + 16384 + j * 8192, &mW, ct * 128 + j * 64, kh * 704 + s * 64, bF + 8 * st);
      };
      auto loadA = [&](int s) { bulk_load(sR + (s % 6) * 32768, g_h + (rb * 172 + kh * 88 + s * 8) * 1024, abytes(s), bF + 8 * (s % 6)); };
      for (int s = 0; s < 6; s++) loadB(s);
      pdl_wait();
      for (int s = 0; s < 6; s++) loadA(s);
      for (int s = 6; s < 11; s++) { mbar_wait(bE + 8 * (s - 6), 0); loadB(s); loadA(s); }
    }
    __syncwarp();
    asm volatile("barrier.cluster.wait.aligned;" ::: "memory");
    asm volatile("barrier.cluster.arrive.release.aligned;" ::: "memory");
    asm volatile("barrier.cluster.wait.acquire.aligned;" ::: "memory");
    return;
  }
  pdl_wait();
  const int lrow = warp * 16 + g;
  uint32_t xr[16];
  float2 gb[8];
  const uint32_t* xp = (const uint32_t*)g_x1 + ((rb * 64 + ct * 16 + kh * 8) * 128 + lrow) * 4 + t;
#pragma unroll
  for (int j = 0; j < 8; j++) {
    xr[2 * j] = xp[j * 512]; xr[2 * j + 1] = xp[j * 512 + 32];
    gb[j] = *(const float2*)(g_mod + 2560 + ct * 128 + kh * 64 + j * 8 + t * 2);
  }
  float acc[64];
#pragma unroll 1
  for (int s = 0; s < 11; s++) {
    const int st = s % 6;
    mbar_wait(bF + 8 * st, s >= 6);
    const uint64_t da = mk_desc(sR + st * 32768 + (warp >> 2) * 1024, 2048, 128, 0), db = mk_desc(sR + st * 32768 + 16384, 8192, 1024, 1);
    wg_fence();
    wgmma_ss_n128_t1(acc, da, db, s);
    wgmma_ss_n128_t1(acc, da + 256, db + 128, 1);
    wgmma_ss_n128_t1(acc, da + 512, db + 256, 1);
    wgmma_ss_n128_t1(acc, da + 768, db + 384, 1);
    wg_commit();
    wg_wait<1>();
    if (s > 0 && s < 6 && lane == 0) mbar_arrive(bE + 8 * (s - 1));
  }
  wg_wait<0>();
  reg_fence(acc);
  asm volatile("barrier.cluster.wait.aligned;" ::: "memory");
  uint32_t rem;
  asm("mapa.shared::cluster.u32 %0,%1,%2;" : "=r"(rem) : "r"(sX + tid * 16), "r"(kh ^ 1));
#pragma unroll
  for (int j = 0; j < 8; j++) {
    float v[4];
#pragma unroll
    for (int i = 0; i < 4; i++) { v[i] = kh ? acc[4 * j + i] : acc[32 + 4 * j + i]; acc[4 * j + i] = kh ? acc[32 + 4 * j + i] : acc[4 * j + i]; }
    asm volatile("st.shared::cluster.v4.f32 [%0],{%1,%2,%3,%4};" ::"r"(rem + j * 4096), "f"(v[0]), "f"(v[1]), "f"(v[2]), "f"(v[3]) : "memory");
  }
  asm volatile("barrier.cluster.arrive.release.aligned;" ::: "memory");
  asm volatile("barrier.cluster.wait.acquire.aligned;" ::: "memory");
  uint32_t* o = (uint32_t*)(out + (rb * 128 + lrow) * 512 + ct * 128 + kh * 64) + t;
#pragma unroll
  for (int j = 0; j < 8; j++) {
    const float4 p = *(const float4*)(smem + 6 * 32768 + j * 4096 + tid * 16);
    o[j * 4] = pack_rn(fmaf(gb[j].x, acc[4 * j] + p.x, blo(xr[2 * j])), fmaf(gb[j].y, acc[4 * j + 1] + p.y, bhi(xr[2 * j])));
    o[j * 4 + 2048] = pack_rn(fmaf(gb[j].x, acc[4 * j + 2] + p.z, blo(xr[2 * j + 1])), fmaf(gb[j].y, acc[4 * j + 3] + p.w, bhi(xr[2 * j + 1])));
  }
}

typedef CUresult (*EncFn)(CUtensorMap*, CUtensorMapDataType, cuuint32_t, void*, const cuuint64_t*, const cuuint64_t*, const cuuint32_t*,
                          const cuuint32_t*, CUtensorMapInterleave, CUtensorMapSwizzle, CUtensorMapL2promotion, CUtensorMapFloatOOBfill);
static void mk_map(EncFn f, CUtensorMap* m, const void* p, int rows, int cols, int box_rows) {
  cuuint64_t dim[2] = {(cuuint64_t)cols, (cuuint64_t)rows}, str[1] = {(cuuint64_t)cols * 2};
  cuuint32_t box[2] = {64, (cuuint32_t)box_rows}, es[2] = {1, 1};
  f(m, CU_TENSOR_MAP_DATA_TYPE_BFLOAT16, 2, (void*)p, dim, str, box, es, CU_TENSOR_MAP_INTERLEAVE_NONE, CU_TENSOR_MAP_SWIZZLE_128B,
    CU_TENSOR_MAP_L2_PROMOTION_L2_128B, CU_TENSOR_MAP_FLOAT_OOB_FILL_NONE);
}
template <typename... KA, typename... A>
static void launch(void (*k)(KA...), int grid, int block, int smem, bool pdl, A... args) {
  cudaLaunchConfig_t cfg = {};
  cfg.gridDim = dim3(grid); cfg.blockDim = dim3(block); cfg.dynamicSmemBytes = smem; cfg.stream = cudaStreamPerThread;
  cudaLaunchAttribute at[1];
  at[0].id = cudaLaunchAttributeProgrammaticStreamSerialization; at[0].val.programmaticStreamSerializationAllowed = 1;
  cfg.attrs = at; cfg.numAttrs = pdl ? 1 : 0;
  cudaLaunchKernelEx(&cfg, k, args...);
}
extern "C" void kernel_launch(void* const* d_in, const int* in_sizes, int n_in, void* d_out, int out_size) {
  const bf16 *x = (const bf16*)d_in[0], *wqkv = (const bf16*)d_in[1], *wo = (const bf16*)d_in[2], *w1 = (const bf16*)d_in[4],
             *w3 = (const bf16*)d_in[5], *w2 = (const bf16*)d_in[6], *c = (const bf16*)d_in[7], *wmod = (const bf16*)d_in[8];
  void* fp = nullptr;
  cudaDriverEntryPointQueryResult qr;
  cudaGetDriverEntryPoint("cuTensorMapEncodeTiled", &fp, cudaEnableDefault, &qr);
  EncFn f = (EncFn)fp;
  CUtensorMap mX, mQ, mO, m1, m3, m2;
  mk_map(f, &mX, x, S_, D_, 128); mk_map(f, &mQ, wqkv, D_, 3 * D_, 64); mk_map(f, &mO, wo, D_, D_, 64);
  mk_map(f, &m1, w1, D_, F_, 32); mk_map(f, &m3, w3, D_, F_, 32); mk_map(f, &m2, w2, F_, D_, 64);
  cudaFuncSetAttribute(k_lngemm<false>, cudaFuncAttributeMaxDynamicSharedMemorySize, LN_SMEM);
  cudaFuncSetAttribute(k_lngemm<true>, cudaFuncAttributeMaxDynamicSharedMemorySize, LN_SMEM);
  cudaFuncSetAttribute(k_attn, cudaFuncAttributeMaxDynamicSharedMemorySize, AT_SMEM);
  cudaFuncSetAttribute(k_wo, cudaFuncAttributeMaxDynamicSharedMemorySize, WO_SMEM);
  cudaFuncSetAttribute(k_w2, cudaFuncAttributeMaxDynamicSharedMemorySize, W2_SMEM);
  launch(k_mod, 96, 256, 0, false, c, wmod);
  launch(k_lngemm<false>, 128, 384, LN_SMEM, true, mX, mQ, mQ);
  launch(k_attn, 128, 512, AT_SMEM, true, wo, w1, w3, w2, 0x43800000u);
  launch(k_wo, 128, 256, WO_SMEM, true, mO, x);
  launch(k_lngemm<true>, 128, 384, LN_SMEM, true, mX, m1, m3);
  launch(k_w2, 128, 288, W2_SMEM, true, m2, (bf16*)d_out);
}
```

```cpp
#include <cuda_runtime.h>
#include <cuda_bf16.h>
#include <cuda.h>
#include <stdint.h>
typedef __nv_bfloat16 bf16;
constexpr int S_ = 2048, D_ = 512, F_ = 1376;
__device__ __align__(1024) float g_mod[3072];
__device__ __align__(1024) bf16 g_qkv[192 * 2048 * 8];
__device__ __align__(1024) float g_kmax[32 * 128];
__device__ __align__(1024) bf16 g_o[16 * 64 * 128 * 8];
__device__ __align__(1024) bf16 g_x1[16 * 64 * 128 * 8];
__device__ __align__(1024) float2 g_st[2048 * 8];
__device__ __align__(1024) bf16 g_h[16 * 172 * 128 * 8];

__device__ __forceinline__ uint32_t smem_u32(const void* p) { return (uint32_t)__cvta_generic_to_shared(p); }
__device__ __forceinline__ void mbar_init(uint32_t b, int n) { asm volatile("mbarrier.init.shared::cta.b64 [%0],%1;" ::"r"(b), "r"(n) : "memory"); }
__device__ __forceinline__ void mbar_expect(uint32_t b, int bytes) { asm volatile("mbarrier.arrive.expect_tx.shared::cta.b64 _,[%0],%1;" ::"r"(b), "r"(bytes) : "memory"); }
__device__ __forceinline__ void mbar_arrive(uint32_t b) { asm volatile("mbarrier.arrive.shared::cta.b64 _,[%0];" ::"r"(b) : "memory"); }
__device__ __forceinline__ void mbar_wait(uint32_t b, int parity) {
  asm volatile("{\n.reg .pred p;\n.reg .u32 n;\nmov.u32 n,0;\nLW:\nmbarrier.try_wait.parity.shared::cta.b64 p,[%0],%1;\n@p bra LD;\n"
               "add.u32 n,n,1;\nsetp.lt.u32 p,n,4194304;\n@p bra LW;\nLD:\n}\n" ::"r"(b), "r"(parity) : "memory");
}
__device__ __forceinline__ void fence_init() { asm volatile("fence.mbarrier_init.release.cluster;" ::: "memory"); }
__device__ __forceinline__ void fence_async() { asm volatile("fence.proxy.async.shared::cta;" ::: "memory"); }
__device__ __forceinline__ void bulk_load(uint32_t dst, const void* src, int bytes, uint32_t bar) {
  asm volatile("cp.async.bulk.shared::cluster.global.mbarrier::complete_tx::bytes [%0],[%1],%2,[%3];" ::"r"(dst), "l"(src), "r"(bytes), "r"(bar) : "memory");
}
__device__ __forceinline__ void tma2d(uint32_t dst, const CUtensorMap* m, int c0, int c1, uint32_t bar) {
  asm volatile("cp.async.bulk.tensor.2d.shared::cluster.global.mbarrier::complete_tx::bytes [%0],[%1,{%3,%4}],[%2];" ::"r"(dst), "l"(m), "r"(bar), "r"(c0), "r"(c1) : "memory");
}
__device__ __forceinline__ void l2_prefetch(const void* p, int bytes) { asm volatile("cp.async.bulk.prefetch.L2.global [%0],%1;" ::"l"(p), "r"(bytes) : "memory"); }
__device__ __forceinline__ void pdl_launch() { asm volatile("griddepcontrol.launch_dependents;" ::: "memory"); }
__device__ __forceinline__ void pdl_wait() { asm volatile("griddepcontrol.wait;" ::: "memory"); }
__device__ __forceinline__ void wg_fence() { asm volatile("wgmma.fence.sync.aligned;" ::: "memory"); }
__device__ __forceinline__ void wg_commit() { asm volatile("wgmma.commit_group.sync.aligned;" ::: "memory"); }
template <int N> __device__ __forceinline__ void wg_wait() { asm volatile("wgmma.wait_group.sync.aligned %0;" ::"n"(N) : "memory"); }
template <int N> __device__ __forceinline__ void reg_fence(float (&d)[N]) {
#pragma unroll
  for (int i = 0; i < N; i++) asm volatile("" : "+f"(d[i])::"memory");
}
template <int N> __device__ __forceinline__ void zero(float (&d)[N]) {
#pragma unroll
  for (int i = 0; i < N; i++) d[i] = 0.f;
  reg_fence(d);
}
__device__ __forceinline__ uint64_t mk_desc(uint32_t addr, uint32_t lbo, uint32_t sbo, uint32_t mode) {
  return (uint64_t)((addr >> 4) & 0x3FFF) | ((uint64_t)(lbo >> 4) << 16) | ((uint64_t)(sbo >> 4) << 32) | ((uint64_t)mode << 62);
}
__device__ __forceinline__ void ldsm4(uint32_t a, uint32_t (&r)[4]) {
  asm volatile("ldmatrix.sync.aligned.m8n8.x4.shared.b16 {%0,%1,%2,%3},[%4];" : "=r"(r[0]), "=r"(r[1]), "=r"(r[2]), "=r"(r[3]) : "r"(a) : "memory");
}
__device__ __forceinline__ uint32_t pack_rn(float lo, float hi) { uint32_t r; asm("cvt.rn.bf16x2.f32 %0,%1,%2;" : "=r"(r) : "f"(hi), "f"(lo)); return r; }
__device__ __forceinline__ uint32_t pack_rz(float lo, float hi) { uint32_t r; asm("cvt.rz.bf16x2.f32 %0,%1,%2;" : "=r"(r) : "f"(hi), "f"(lo)); return r; }
__device__ __forceinline__ float blo(uint32_t u) { return __uint_as_float(u << 16); }
__device__ __forceinline__ float bhi(uint32_t u) { return __uint_as_float(u & 0xFFFF0000u); }
__device__ __forceinline__ float rbf(float x) { return __bfloat162float(__float2bfloat16_rn(x)); }
__device__ __forceinline__ float qsum(float v) { v += __shfl_xor_sync(~0u, v, 1); return v + __shfl_xor_sync(~0u, v, 2); }
__device__ __forceinline__ float ex2(float x) { float r; asm("ex2.approx.ftz.f32 %0,%1;" : "=f"(r) : "f"(x)); return r; }
__device__ __forceinline__ void wgmma_rs_n176_t1(float (&d)[88],uint32_t a0,uint32_t a1,uint32_t a2,uint32_t a3,uint64_t db,int sc){
  asm volatile("{\n.reg .pred p;\nsetp.ne.b32 p,%93,0;\n"
    "wgmma.mma_async.sync.aligned.m64n176k16.f32.bf16.bf16 {%0,%1,%2,%3,%4,%5,%6,%7,%8,%9,%10,%11,%12,%13,%14,%15,%16,%17,%18,%19,%20,%21,%22,%23,%24,%25,%26,%27,%28,%29,%30,%31,%32,%33,%34,%35,%36,%37,%38,%39,%40,%41,%42,%43,%44,%45,%46,%47,%48,%49,%50,%51,%52,%53,%54,%55,%56,%57,%58,%59,%60,%61,%62,%63,%64,%65,%66,%67,%68,%69,%70,%71,%72,%73,%74,%75,%76,%77,%78,%79,%80,%81,%82,%83,%84,%85,%86,%87},{%88,%89,%90,%91},%92,p,1,1,1;\n}\n"
    :"+f"(d[0]),"+f"(d[1]),"+f"(d[2]),"+f"(d[3]),"+f"(d[4]),"+f"(d[5]),"+f"(d[6]),"+f"(d[7]),"+f"(d[8]),"+f"(d[9]),"+f"(d[10]),"+f"(d[11]),"+f"(d[12]),"+f"(d[13]),"+f"(d[14]),"+f"(d[15]),"+f"(d[16]),"+f"(d[17]),"+f"(d[18]),"+f"(d[19]),"+f"(d[20]),"+f"(d[21]),"+f"(d[22]),"+f"(d[23]),"+f"(d[24]),"+f"(d[25]),"+f"(d[26]),"+f"(d[27]),"+f"(d[28]),"+f"(d[29]),"+f"(d[30]),"+f"(d[31]),"+f"(d[32]),"+f"(d[33]),"+f"(d[34]),"+f"(d[35]),"+f"(d[36]),"+f"(d[37]),"+f"(d[38]),"+f"(d[39]),"+f"(d[40]),"+f"(d[41]),"+f"(d[42]),"+f"(d[43]),"+f"(d[44]),"+f"(d[45]),"+f"(d[46]),"+f"(d[47]),"+f"(d[48]),"+f"(d[49]),"+f"(d[50]),"+f"(d[51]),"+f"(d[52]),"+f"(d[53]),"+f"(d[54]),"+f"(d[55]),"+f"(d[56]),"+f"(d[57]),"+f"(d[58]),"+f"(d[59]),"+f"(d[60]),"+f"(d[61]),"+f"(d[62]),"+f"(d[63]),"+f"(d[64]),"+f"(d[65]),"+f"(d[66]),"+f"(d[67]),"+f"(d[68]),"+f"(d[69]),"+f"(d[70]),"+f"(d[71]),"+f"(d[72]),"+f"(d[73]),"+f"(d[74]),"+f"(d[75]),"+f"(d[76]),"+f"(d[77]),"+f"(d[78]),"+f"(d[79]),"+f"(d[80]),"+f"(d[81]),"+f"(d[82]),"+f"(d[83]),"+f"(d[84]),"+f"(d[85]),"+f"(d[86]),"+f"(d[87])
    :"r"(a0),"r"(a1),"r"(a2),"r"(a3),"l"(db),"r"(sc));
}
__device__ __forceinline__ void wgmma_rs_n192_t1(float (&d)[96],uint32_t a0,uint32_t a1,uint32_t a2,uint32_t a3,uint64_t db,int sc){
  asm volatile("{\n.reg .pred p;\nsetp.ne.b32 p,%101,0;\n"
    "wgmma.mma_async.sync.aligned.m64n192k16.f32.bf16.bf16 {%0,%1,%2,%3,%4,%5,%6,%7,%8,%9,%10,%11,%12,%13,%14,%15,%16,%17,%18,%19,%20,%21,%22,%23,%24,%25,%26,%27,%28,%29,%30,%31,%32,%33,%34,%35,%36,%37,%38,%39,%40,%41,%42,%43,%44,%45,%46,%47,%48,%49,%50,%51,%52,%53,%54,%55,%56,%57,%58,%59,%60,%61,%62,%63,%64,%65,%66,%67,%68,%69,%70,%71,%72,%73,%74,%75,%76,%77,%78,%79,%80,%81,%82,%83,%84,%85,%86,%87,%88,%89,%90,%91,%92,%93,%94,%95},{%96,%97,%98,%99},%100,p,1,1,1;\n}\n"
    :"+f"(d[0]),"+f"(d[1]),"+f"(d[2]),"+f"(d[3]),"+f"(d[4]),"+f"(d[5]),"+f"(d[6]),"+f"(d[7]),"+f"(d[8]),"+f"(d[9]),"+f"(d[10]),"+f"(d[11]),"+f"(d[12]),"+f"(d[13]),"+f"(d[14]),"+f"(d[15]),"+f"(d[16]),"+f"(d[17]),"+f"(d[18]),"+f"(d[19]),"+f"(d[20]),"+f"(d[21]),"+f"(d[22]),"+f"(d[23]),"+f"(d[24]),"+f"(d[25]),"+f"(d[26]),"+f"(d[27]),"+f"(d[28]),"+f"(d[29]),"+f"(d[30]),"+f"(d[31]),"+f"(d[32]),"+f"(d[33]),"+f"(d[34]),"+f"(d[35]),"+f"(d[36]),"+f"(d[37]),"+f"(d[38]),"+f"(d[39]),"+f"(d[40]),"+f"(d[41]),"+f"(d[42]),"+f"(d[43]),"+f"(d[44]),"+f"(d[45]),"+f"(d[46]),"+f"(d[47]),"+f"(d[48]),"+f"(d[49]),"+f"(d[50]),"+f"(d[51]),"+f"(d[52]),"+f"(d[53]),"+f"(d[54]),"+f"(d[55]),"+f"(d[56]),"+f"(d[57]),"+f"(d[58]),"+f"(d[59]),"+f"(d[60]),"+f"(d[61]),"+f"(d[62]),"+f"(d[63]),"+f"(d[64]),"+f"(d[65]),"+f"(d[66]),"+f"(d[67]),"+f"(d[68]),"+f"(d[69]),"+f"(d[70]),"+f"(d[71]),"+f"(d[72]),"+f"(d[73]),"+f"(d[74]),"+f"(d[75]),"+f"(d[76]),"+f"(d[77]),"+f"(d[78]),"+f"(d[79]),"+f"(d[80]),"+f"(d[81]),"+f"(d[82]),"+f"(d[83]),"+f"(d[84]),"+f"(d[85]),"+f"(d[86]),"+f"(d[87]),"+f"(d[88]),"+f"(d[89]),"+f"(d[90]),"+f"(d[91]),"+f"(d[92]),"+f"(d[93]),"+f"(d[94]),"+f"(d[95])
    :"r"(a0),"r"(a1),"r"(a2),"r"(a3),"l"(db),"r"(sc));
}
__device__ __forceinline__ void wgmma_rs_n24_t1(float (&d)[12],uint32_t a0,uint32_t a1,uint32_t a2,uint32_t a3,uint64_t db,int sc){
  asm volatile("{\n.reg .pred p;\nsetp.ne.b32 p,%17,0;\n"
    "wgmma.mma_async.sync.aligned.m64n24k16.f32.bf16.bf16 {%0,%1,%2,%3,%4,%5,%6,%7,%8,%9,%10,%11},{%12,%13,%14,%15},%16,p,1,1,1;\n}\n"
    :"+f"(d[0]),"+f"(d[1]),"+f"(d[2]),"+f"(d[3]),"+f"(d[4]),"+f"(d[5]),"+f"(d[6]),"+f"(d[7]),"+f"(d[8]),"+f"(d[9]),"+f"(d[10]),"+f"(d[11])
    :"r"(a0),"r"(a1),"r"(a2),"r"(a3),"l"(db),"r"(sc));
}
__device__ __forceinline__ void wgmma_rs_n64_t0(float (&d)[32],uint32_t a0,uint32_t a1,uint32_t a2,uint32_t a3,uint64_t db,int sc){
  asm volatile("{\n.reg .pred p;\nsetp.ne.b32 p,%37,0;\n"
    "wgmma.mma_async.sync.aligned.m64n64k16.f32.bf16.bf16 {%0,%1,%2,%3,%4,%5,%6,%7,%8,%9,%10,%11,%12,%13,%14,%15,%16,%17,%18,%19,%20,%21,%22,%23,%24,%25,%26,%27,%28,%29,%30,%31},{%32,%33,%34,%35},%36,p,1,1,0;\n}\n"
    :"+f"(d[0]),"+f"(d[1]),"+f"(d[2]),"+f"(d[3]),"+f"(d[4]),"+f"(d[5]),"+f"(d[6]),"+f"(d[7]),"+f"(d[8]),"+f"(d[9]),"+f"(d[10]),"+f"(d[11]),"+f"(d[12]),"+f"(d[13]),"+f"(d[14]),"+f"(d[15]),"+f"(d[16]),"+f"(d[17]),"+f"(d[18]),"+f"(d[19]),"+f"(d[20]),"+f"(d[21]),"+f"(d[22]),"+f"(d[23]),"+f"(d[24]),"+f"(d[25]),"+f"(d[26]),"+f"(d[27]),"+f"(d[28]),"+f"(d[29]),"+f"(d[30]),"+f"(d[31])
    :"r"(a0),"r"(a1),"r"(a2),"r"(a3),"l"(db),"r"(sc));
}
__device__ __forceinline__ void wgmma_ss_n128_t1(float (&d)[64],uint64_t da,uint64_t db,int sc){
  asm volatile("{\n.reg .pred p;\nsetp.ne.b32 p,%66,0;\n"
    "wgmma.mma_async.sync.aligned.m64n128k16.f32.bf16.bf16 {%0,%1,%2,%3,%4,%5,%6,%7,%8,%9,%10,%11,%12,%13,%14,%15,%16,%17,%18,%19,%20,%21,%22,%23,%24,%25,%26,%27,%28,%29,%30,%31,%32,%33,%34,%35,%36,%37,%38,%39,%40,%41,%42,%43,%44,%45,%46,%47,%48,%49,%50,%51,%52,%53,%54,%55,%56,%57,%58,%59,%60,%61,%62,%63},%64,%65,p,1,1,0,1;\n}\n"
    :"+f"(d[0]),"+f"(d[1]),"+f"(d[2]),"+f"(d[3]),"+f"(d[4]),"+f"(d[5]),"+f"(d[6]),"+f"(d[7]),"+f"(d[8]),"+f"(d[9]),"+f"(d[10]),"+f"(d[11]),"+f"(d[12]),"+f"(d[13]),"+f"(d[14]),"+f"(d[15]),"+f"(d[16]),"+f"(d[17]),"+f"(d[18]),"+f"(d[19]),"+f"(d[20]),"+f"(d[21]),"+f"(d[22]),"+f"(d[23]),"+f"(d[24]),"+f"(d[25]),"+f"(d[26]),"+f"(d[27]),"+f"(d[28]),"+f"(d[29]),"+f"(d[30]),"+f"(d[31]),"+f"(d[32]),"+f"(d[33]),"+f"(d[34]),"+f"(d[35]),"+f"(d[36]),"+f"(d[37]),"+f"(d[38]),"+f"(d[39]),"+f"(d[40]),"+f"(d[41]),"+f"(d[42]),"+f"(d[43]),"+f"(d[44]),"+f"(d[45]),"+f"(d[46]),"+f"(d[47]),"+f"(d[48]),"+f"(d[49]),"+f"(d[50]),"+f"(d[51]),"+f"(d[52]),"+f"(d[53]),"+f"(d[54]),"+f"(d[55]),"+f"(d[56]),"+f"(d[57]),"+f"(d[58]),"+f"(d[59]),"+f"(d[60]),"+f"(d[61]),"+f"(d[62]),"+f"(d[63])
    :"l"(da),"l"(db),"r"(sc));
}
__device__ __forceinline__ void wgmma_ss_n64_t1(float (&d)[32],uint64_t da,uint64_t db,int sc){
  asm volatile("{\n.reg .pred p;\nsetp.ne.b32 p,%34,0;\n"
    "wgmma.mma_async.sync.aligned.m64n64k16.f32.bf16.bf16 {%0,%1,%2,%3,%4,%5,%6,%7,%8,%9,%10,%11,%12,%13,%14,%15,%16,%17,%18,%19,%20,%21,%22,%23,%24,%25,%26,%27,%28,%29,%30,%31},%32,%33,p,1,1,0,1;\n}\n"
    :"+f"(d[0]),"+f"(d[1]),"+f"(d[2]),"+f"(d[3]),"+f"(d[4]),"+f"(d[5]),"+f"(d[6]),"+f"(d[7]),"+f"(d[8]),"+f"(d[9]),"+f"(d[10]),"+f"(d[11]),"+f"(d[12]),"+f"(d[13]),"+f"(d[14]),"+f"(d[15]),"+f"(d[16]),"+f"(d[17]),"+f"(d[18]),"+f"(d[19]),"+f"(d[20]),"+f"(d[21]),"+f"(d[22]),"+f"(d[23]),"+f"(d[24]),"+f"(d[25]),"+f"(d[26]),"+f"(d[27]),"+f"(d[28]),"+f"(d[29]),"+f"(d[30]),"+f"(d[31])
    :"l"(da),"l"(db),"r"(sc));
}

__global__ void __launch_bounds__(256) k_mod(const bf16* __restrict__ c, const bf16* __restrict__ w) {
  pdl_launch();
  __shared__ float red[8][32];
  const int t = threadIdx.x, n0 = blockIdx.x * 32 + (t & 3) * 8, r0 = t >> 2;
  uint4 v[8];
  float cs[8];
#pragma unroll
  for (int i = 0; i < 8; i++) v[i] = __ldg((const uint4*)(w + (size_t)(r0 + i * 64) * 3072 + n0));
#pragma unroll
  for (int i = 0; i < 8; i++) { float x = __bfloat162float(c[r0 + i * 64]); cs[i] = rbf(x / (1.f + __expf(-x))); }
  float a[8] = {0, 0, 0, 0, 0, 0, 0, 0};
#pragma unroll
  for (int i = 0; i < 8; i++) {
    a[0] += cs[i] * blo(v[i].x); a[1] += cs[i] * bhi(v[i].x); a[2] += cs[i] * blo(v[i].y); a[3] += cs[i] * bhi(v[i].y);
    a[4] += cs[i] * blo(v[i].z); a[5] += cs[i] * bhi(v[i].z); a[6] += cs[i] * blo(v[i].w); a[7] += cs[i] * bhi(v[i].w);
  }
#pragma unroll
  for (int j = 0; j < 8; j++) {
    a[j] += __shfl_xor_sync(~0u, a[j], 4); a[j] += __shfl_xor_sync(~0u, a[j], 8); a[j] += __shfl_xor_sync(~0u, a[j], 16);
  }
  if ((t & 31) < 4) {
#pragma unroll
    for (int j = 0; j < 8; j++) red[t >> 5][(t & 3) * 8 + j] = a[j];
  }
  __syncthreads();
  if (t < 32) {
    float s = 0;
#pragma unroll
    for (int i = 0; i < 8; i++) s += red[i][t];
    const int n = blockIdx.x * 32 + t, seg = n >> 9;
    s = rbf(s);
    if (seg == 1 || seg == 4) s = rbf(1.f + s);
    g_mod[n] = s;
  }
}

constexpr int LN_SMEM = 131072 + 4 * 24576 + 2048 + 256;
template <bool FFN>
__global__ void __launch_bounds__(384, 1) k_lngemm(const __grid_constant__ CUtensorMap mX, const __grid_constant__ CUtensorMap mB0,
                                                   const __grid_constant__ CUtensorMap mB1) {
  extern __shared__ __align__(1024) uint8_t smem[];
  const uint32_t sA = smem_u32(smem), sB = sA + 131072, sM = sB + 4 * 24576, bars = sM + 2048;
  const uint32_t bA = bars, bF = bars + 64, bE = bars + 96;
  const int tid = threadIdx.x, warp = tid >> 5, lane = tid & 31;
  const int rb = blockIdx.x >> 3, ct = blockIdx.x & 7;
  constexpr int NST = FFN ? 16 : 8, KS = FFN ? 2 : 4, BOX = FFN ? 4096 : 8192;
  pdl_launch();
  if (tid == 256) {
    for (int i = 0; i < 8; i++) mbar_init(bA + 8 * i, 1);
    for (int i = 0; i < 4; i++) { mbar_init(bF + 8 * i, 1); mbar_init(bE + 8 * i, 8); }
    fence_init();
  }
  __syncthreads();
  if (warp >= 8) {
    asm volatile("setmaxnreg.dec.sync.aligned.u32 40;");
    if (tid == 256) {
      auto loadB = [&](int s) {
        const uint32_t d = sB + (s & 3) * 24576, b = bF + (s & 3) * 8;
        mbar_expect(b, 24576);
        for (int j = 0; j < 3; j++) {
          if (FFN) { tma2d(d + j * BOX, &mB0, ct * 176 + j * 64, s * 32, b); tma2d(d + (3 + j) * BOX, &mB1, ct * 176 + j * 64, s * 32, b); }
          else tma2d(d + j * BOX, &mB0, ct * 192 + j * 64, s * 64, b);
        }
      };
      if (!FFN) for (int i = 0; i < 8; i++) { mbar_expect(bA + 8 * i, 16384); tma2d(sA + i * 16384, &mX, i * 64, rb * 128, bA + 8 * i); }
      for (int s = 0; s < 4; s++) loadB(s);
      if (FFN) {
        pdl_wait();
        for (int i = 0; i < 8; i++) { mbar_expect(bA + 8 * i, 16384); bulk_load(sA + i * 16384, g_x1 + (rb * 64 + i * 8) * 1024, 16384, bA + 8 * i); }
      }
      for (int s = 4; s < NST; s++) { mbar_wait(bE + (s & 3) * 8, ((s >> 2) - 1) & 1); loadB(s); }
    }
  } else {
  asm volatile("setmaxnreg.inc.sync.aligned.u32 232;");
  const int g = lane >> 2, t = lane & 3;
  const int lr = warp * 16 + (lane & 7) + ((lane >> 3) & 1) * 8;
  auto aaddr = [&](int ks) -> uint32_t {
    if (FFN) return sA + (ks * 2 + (lane >> 4)) * 2048 + lr * 16;
    return sA + (ks >> 2) * 16384 + lr * 128 + ((((ks & 3) * 2 + (lane >> 4)) ^ (lr & 7)) << 4);
  };
  const int row0 = rb * 128 + warp * 16 + g;
  float rs0, rs1, nm0, nm1;
  if (!FFN) {
    float s0 = 0, s1 = 0;
#pragma unroll 4
    for (int ks = 0; ks < 32; ks++) {
      if ((ks & 3) == 0) mbar_wait(bA + 2 * ks, 0);
      uint32_t r[4]; ldsm4(aaddr(ks), r);
      s0 += (blo(r[0]) + bhi(r[0])) + (blo(r[2]) + bhi(r[2]));
      s1 += (blo(r[1]) + bhi(r[1])) + (blo(r[3]) + bhi(r[3]));
    }
    const float m0 = qsum(s0) * (1.f / 512), m1 = qsum(s1) * (1.f / 512);
    float v0 = 0, v1 = 0, v2 = 0, v3 = 0;
#pragma unroll 4
    for (int ks = 0; ks < 32; ks++) {
      uint32_t r[4]; ldsm4(aaddr(ks), r);
      float d;
      d = blo(r[0]) - m0; v0 += d * d; d = bhi(r[0]) - m0; v2 += d * d; d = blo(r[2]) - m0; v0 += d * d; d = bhi(r[2]) - m0; v2 += d * d;
      d = blo(r[1]) - m1; v1 += d * d; d = bhi(r[1]) - m1; v3 += d * d; d = blo(r[3]) - m1; v1 += d * d; d = bhi(r[3]) - m1; v3 += d * d;
    }
    rs0 = rsqrtf(qsum(v0 + v2) * (1.f / 512) + 1e-5f); rs1 = rsqrtf(qsum(v1 + v3) * (1.f / 512) + 1e-5f);
    nm0 = -m0 * rs0; nm1 = -m1 * rs1;
    pdl_wait();
  } else {
    pdl_wait();
    const float4 p0 = *(const float4*)(g_st + row0 * 8 + t * 2), p1 = *(const float4*)(g_st + (row0 + 8) * 8 + t * 2);
    const float m0 = qsum(p0.x + p0.z) * 0.125f, m1 = qsum(p1.x + p1.z) * 0.125f;
    const float v0 = qsum(p0.y + p0.w + 64.f * ((p0.x - m0) * (p0.x - m0) + (p0.z - m0) * (p0.z - m0)));
    const float v1 = qsum(p1.y + p1.w + 64.f * ((p1.x - m1) * (p1.x - m1) + (p1.z - m1) * (p1.z - m1)));
    rs0 = rsqrtf(v0 * (1.f / 512) + 1e-5f); rs1 = rsqrtf(v1 * (1.f / 512) + 1e-5f);
    nm0 = -m0 * rs0; nm1 = -m1 * rs1;
  }
  {
    const float2 sh = *(const float2*)(g_mod + (FFN ? 1536 : 0) + tid * 2), sc = *(const float2*)(g_mod + (FFN ? 2048 : 512) + tid * 2);
    uint32_t* m = (uint32_t*)(smem + (sM - sA)) + (tid >> 3) * 16 + (tid & 3) * 4 + ((tid >> 2) & 1);
    m[0] = pack_rn(sc.x, sc.y); m[2] = pack_rn(sh.x, sh.y);
    asm volatile("bar.sync 1,256;" ::: "memory");
  }
  constexpr int NA = FFN ? 88 : 96;
  float acc0[NA], acc1[FFN ? 88 : 1];
  uint32_t a[2][4];
  auto prep = [&](int ks, uint32_t(&o)[4]) {
    if (FFN && (ks & 3) == 0) mbar_wait(bA + 2 * ks, 0);
    uint32_t r[4]; ldsm4(aaddr(ks), r);
    const uint4 m = *(const uint4*)(smem + (sM - sA) + ks * 64 + t * 16);
#pragma unroll
    for (int i = 0; i < 4; i++) {
      const float rs = (i & 1) ? rs1 : rs0, nm = (i & 1) ? nm1 : nm0;
      const uint32_t n = pack_rn(fmaf(blo(r[i]), rs, nm), fmaf(bhi(r[i]), rs, nm));
      asm("fma.rn.bf16x2 %0,%1,%2,%3;" : "=r"(o[i]) : "r"(n), "r"(i < 2 ? m.x : m.y), "r"(i < 2 ? m.z : m.w));
    }
  };
  prep(0, a[0]);
#pragma unroll 1
  for (int s = 0; s < NST; s++) {
    mbar_wait(bF + (s & 3) * 8, (s >> 2) & 1);
    const uint64_t db = mk_desc(sB + (s & 3) * 24576, BOX, 1024, 1);
#pragma unroll
    for (int k = 0; k < KS; k++) {
      const int ks = s * KS + k;
      uint32_t(&c)[4] = a[k & 1];
      wg_fence();
      if constexpr (FFN) {
        wgmma_rs_n176_t1(acc0, c[0], c[1], c[2], c[3], db + k * 128, ks);
        wgmma_rs_n176_t1(acc1, c[0], c[1], c[2], c[3], db + k * 128 + 3 * BOX / 16, ks);
      } else {
        wgmma_rs_n192_t1(acc0, c[0], c[1], c[2], c[3], db + k * 128, ks);
      }
      wg_commit();
      wg_wait<1>();
      if (k == 0 && s > 0 && lane == 0) mbar_arrive(bE + ((s - 1) & 3) * 8);
      if (ks < 31) prep(ks + 1, a[(k + 1) & 1]);
    }
  }
  wg_wait<0>();
  reg_fence(acc0);
  if constexpr (FFN) {
    reg_fence(acc1);
    uint32_t* o = (uint32_t*)g_h + ((rb * 172 + ct * 22) * 128 + warp * 16 + g) * 4 + t;
#pragma unroll
    for (int j = 0; j < 22; j++) {
      if (ct * 22 + j < 172) {
        float h[4];
#pragma unroll
        for (int i = 0; i < 4; i++) { const float x = acc0[4 * j + i]; h[i] = __fdividef(x, 1.f + ex2(-1.4426950408889634f * x)) * acc1[4 * j + i]; }
        o[j * 512] = pack_rn(h[0], h[1]);
        o[j * 512 + 32] = pack_rn(h[2], h[3]);
      }
    }
  } else {
    uint32_t* o = (uint32_t*)g_qkv + (ct * 24 * 2048 + row0) * 4 + t;
#pragma unroll
    for (int j = 0; j < 24; j += 2) {
      const int G = ct * 24 + j;
      const float sc = G < 64 ? 0.25f * 1.4426950408889634f : 1.f;
      uint32_t p[4];
#pragma unroll
      for (int i = 0; i < 4; i++) p[i] = pack_rn(acc0[4 * j + 2 * i] * sc, acc0[4 * j + 2 * i + 1] * sc);
      o[j * 8192] = p[0]; o[j * 8192 + 32] = p[1]; o[(j + 1) * 8192] = p[2]; o[(j + 1) * 8192 + 32] = p[3];
      if (G >= 64 && G < 128) {
        float n0 = blo(p[0]) * blo(p[0]) + bhi(p[0]) * bhi(p[0]) + blo(p[2]) * blo(p[2]) + bhi(p[2]) * bhi(p[2]);
        float n1 = blo(p[1]) * blo(p[1]) + bhi(p[1]) * bhi(p[1]) + blo(p[3]) * blo(p[3]) + bhi(p[3]) * bhi(p[3]);
        n0 = qsum(n0); n1 = qsum(n1);
        const uint32_t mx = __reduce_max_sync(~0u, max(__float_as_uint(n0), __float_as_uint(n1)));
        if (lane == 0) g_kmax[((G - 64) >> 1) * 128 + rb * 8 + warp] = __uint_as_float(mx);
      }
    }
  }
}
}

#define SMASK 0xAAu
#define BRK 0
#define PACK 0
#define PP 0
constexpr int AT_SMEM = 5 * 32768 + 256;
__device__ __forceinline__ uint32_t exp2_pair_fma(float s0, float s1, float c, uint32_t ka, uint32_t kz) {
  uint32_t r;
  asm volatile("{\n.reg .b32 y0,y1,e,u,t;\n"
      "fma.rn.sat.f32 y0,%1,0f00000080,%3;\nfma.rn.sat.f32 y1,%2,0f00000080,%3;\n"
      "prmt.b32 e,y0,y1,0x5410;\n"
      "and.b32 u,e,0x007F007F;\n"
      "fma.rn.f16x2 u,u,%4,%5;\nfma.rn.f16x2 t,u,u,%6;\nfma.rn.f16x2 t,t,u,%7;\n"
      "lop3.b32 %0,t,0x007F007F,e,0xE2;\n}\n"
      : "=r"(r) : "f"(s0), "f"(s1), "f"(c), "r"(ka), "r"(0x36B236B2u), "r"(0x3C733C73u), "r"(0x47764776u), "r"(kz));
  return r;
}
__device__ __forceinline__ void attn_pass(float (&oa)[12], float (&ob)[12], const uint32_t (&q)[4], float m0, float m1, uint32_t sK, uint32_t bars, bool first, uint32_t kz) {
  const uint64_t dk = mk_desc(sK, 32768, 128, 0), dv = mk_desc(sK + 65536, 128, 32768, 0);
  const float c0 = (127.f - m0) * __uint_as_float(0x80u), c1 = (127.f - m1) * __uint_as_float(0x80u);
  const uint32_t ka = 0x7ACE7ACEu + kz;
  constexpr int NK = 64, NS = 32, NP = 16, NI = 32;
  auto qk = [&](float (&s)[NS], int i) { wgmma_rs_n64_t0(s, q[0], q[1], q[2], q[3], dk + i * NK, 0); };
  auto softmax = [&](float (&s)[NS], uint32_t (&p)[NP], uint32_t mask) {
    reg_fence(s);
    float e0, e1;
    int pend = -1;
#pragma unroll
    for (int t = 0; t < NP; t++) {
      const int j = (t & 3) * 4 + (t >> 2);
      if ((mask >> (t & 3)) & 1) {
        p[j] = exp2_pair_fma(s[2 * j], s[2 * j + 1], (j & 1) ? c1 : c0, ka, kz);
      } else {
        float f0, f1;
        asm volatile("ex2.approx.ftz.f32 %0,%2;\nex2.approx.ftz.f32 %1,%3;" : "=&f"(f0), "=f"(f1) : "f"(s[2 * j]), "f"(s[2 * j + 1]));
        if (pend >= 0) asm volatile("cvt.rn.bf16x2.f32 %0,%1,%2;" : "=r"(p[pend]) : "f"(e1), "f"(e0));
        e0 = f0; e1 = f1; pend = j;
      }
    }
    if (pend >= 0) asm volatile("cvt.rn.bf16x2.f32 %0,%1,%2;" : "=r"(p[pend]) : "f"(e1), "f"(e0));
#pragma unroll
    for (int j = 0; j < NP; j++) asm volatile("" : "+r"(p[j])::"memory");
  };
  auto pv = [&](uint32_t (&p)[NP], int i, uint32_t mask) {
#pragma unroll
    for (int k = 0; k < 4; k++) wgmma_rs_n24_t1(((mask >> k) & 1) ? ob : oa, p[4 * k], p[4 * k + 1], p[4 * k + 2], p[4 * k + 3], dv + i * NK + k * 16, 1);
  };
  auto ld = [&](int i) { if (first && (i & (NI / 4 - 1)) == 0) mbar_wait(bars + i / (NI / 4) * 8, 0); };
  constexpr uint32_t M0 = SMASK & 15, M1 = SMASK >> 4;
  zero(oa); zero(ob);
  ld(0);
  float s[NS];
  zero(s);
  uint32_t p[NP];
  wg_fence(); qk(s, 0); wg_commit(); wg_wait<0>(); softmax(s, p, M0);
#pragma unroll 1
  for (int i = 0; i < NI - 2; i += 2) {
    wg_fence(); qk(s, i + 1); pv(p, i, M0); wg_commit(); wg_wait<0>(); softmax(s, p, M1);
    ld(i + 2);
    wg_fence(); qk(s, i + 2); pv(p, i + 1, M1); wg_commit(); wg_wait<0>(); softmax(s, p, M0);
  }
  wg_fence(); qk(s, NI - 1); pv(p, NI - 2, M0); wg_commit(); wg_wait<0>(); softmax(s, p, M1);
  wg_fence(); pv(p, NI - 1, M1); wg_commit();
  wg_wait<0>();
  reg_fence(oa); reg_fence(ob);
}
__device__ __forceinline__ void mma16816(float (&d)[4], const uint32_t (&a)[4], uint32_t b0, uint32_t b1) {
  asm("mma.sync.aligned.m16n8k16.row.col.f32.bf16.bf16.f32 {%0,%1,%2,%3},{%4,%5,%6,%7},{%8,%9},{%0,%1,%2,%3};"
      : "+f"(d[0]), "+f"(d[1]), "+f"(d[2]), "+f"(d[3]) : "r"(a[0]), "r"(a[1]), "r"(a[2]), "r"(a[3]), "r"(b0), "r"(b1));
}
__device__ __forceinline__ void attn_safe(float (&o)[12], const uint32_t (&q)[4], uint32_t sK) {
  const int lane = threadIdx.x & 31;
  const uint32_t ka = sK + (lane >> 4) * 32768 + (lane & 15) * 16;
  float m0 = -INFINITY, m1 = -INFINITY;
#pragma unroll 2
  for (int i = 0; i < 128; i++) {
    uint32_t k[4]; ldsm4(ka + i * 256, k);
    float s0[4] = {0, 0, 0, 0}, s1[4] = {0, 0, 0, 0};
    mma16816(s0, q, k[0], k[2]); mma16816(s1, q, k[1], k[3]);
    m0 = fmaxf(fmaxf(m0, fmaxf(s0[0], s0[1])), fmaxf(s1[0], s1[1])); m1 = fmaxf(fmaxf(m1, fmaxf(s0[2], s0[3])), fmaxf(s1[2], s1[3]));
  }
  m0 = fmaxf(m0, __shfl_xor_sync(~0u, m0, 1)); m0 = fmaxf(m0, __shfl_xor_sync(~0u, m0, 2));
  m1 = fmaxf(m1, __shfl_xor_sync(~0u, m1, 1)); m1 = fmaxf(m1, __shfl_xor_sync(~0u, m1, 2));
  float o0[4] = {0, 0, 0, 0}, o1[4] = {0, 0, 0, 0}, o2[4] = {0, 0, 0, 0};
#pragma unroll 2
  for (int i = 0; i < 128; i++) {
    uint32_t k[4], v[4]; ldsm4(ka + i * 256, k);
    asm volatile("ldmatrix.sync.aligned.m8n8.x4.trans.shared.b16 {%0,%1,%2,%3},[%4];" : "=r"(v[0]), "=r"(v[1]), "=r"(v[2]), "=r"(v[3]) : "r"(ka + 65536 + i * 256) : "memory");
    float s0[4] = {0, 0, 0, 0}, s1[4] = {0, 0, 0, 0};
    mma16816(s0, q, k[0], k[2]); mma16816(s1, q, k[1], k[3]);
    const uint32_t p[4] = {pack_rn(ex2(s0[0] - m0), ex2(s0[1] - m0)), pack_rn(ex2(s0[2] - m1), ex2(s0[3] - m1)),
                           pack_rn(ex2(s1[0] - m0), ex2(s1[1] - m0)), pack_rn(ex2(s1[2] - m1), ex2(s1[3] - m1))};
    mma16816(o0, p, v[0], v[1]); mma16816(o1, p, v[2], v[3]); mma16816(o2, p, 0x3F803F80u, 0x3F803F80u);
  }
#pragma unroll
  for (int i = 0; i < 4; i++) { o[i] = o0[i]; o[4 + i] = o1[i]; o[8 + i] = o2[i]; }
}
__global__ void __launch_bounds__(512, 1) k_attn(const bf16* wo, const bf16* w1, const bf16* w3, const bf16* w2, uint32_t kz) {
  extern __shared__ __align__(1024) uint8_t smem[];
  const uint32_t sK = smem_u32(smem), bars = sK + 5 * 32768;
  const int tid = threadIdx.x, warp = tid >> 5, lane = tid & 31, g = lane >> 2, t = lane & 3;
  const int h = blockIdx.x >> 2, qb = blockIdx.x & 3;
  pdl_launch();
  if (tid == 0) { for (int i = 0; i < 4; i++) mbar_init(bars + 8 * i, 1); fence_init(); }
#pragma unroll
  for (int i = 0; i < 4; i++) *(uint4*)(smem + 131072 + i * 8192 + tid * 16) = make_uint4(0x3F803F80u, 0x3F803F80u, 0x3F803F80u, 0x3F803F80u);
  fence_async();
  __syncthreads();
  pdl_wait();
  if (tid == 0) {
    for (int c = 0; c < 4; c++) {
      mbar_expect(bars + 8 * c, 32768);
      for (int pl = 0; pl < 4; pl++)
        bulk_load(sK + pl * 32768 + c * 8192, g_qkv + ((64 + (pl >> 1) * 64 + h * 2 + (pl & 1)) * 2048 + c * 512) * 8, 8192, bars + 8 * c);
    }
  }
  if (tid == 32) {
    l2_prefetch((const char*)wo + blockIdx.x * 4096, 4096);
    l2_prefetch((const char*)w1 + blockIdx.x * 11008, 11008);
    l2_prefetch((const char*)w3 + blockIdx.x * 11008, 11008);
    l2_prefetch((const char*)w2 + blockIdx.x * 11008, 11008);
  }
  const uint4 km4 = *(const uint4*)(g_kmax + h * 128 + lane * 4);
  const float kmax = __uint_as_float(__reduce_max_sync(~0u, max(max(km4.x, km4.y), max(km4.z, km4.w))));
#pragma unroll 1
  for (int tile = 0; tile < 2; tile++) {
    const int row = qb * 512 + tile * 256 + warp * 16 + g;
    const uint32_t* qp = (const uint32_t*)g_qkv + (h * 2 * 2048 + row) * 4 + t;
    uint32_t q[4] = {qp[0], qp[32], qp[8192], qp[8192 + 32]};
    const float n0 = qsum(blo(q[0]) * blo(q[0]) + bhi(q[0]) * bhi(q[0]) + blo(q[2]) * blo(q[2]) + bhi(q[2]) * bhi(q[2]));
    const float n1 = qsum(blo(q[1]) * blo(q[1]) + bhi(q[1]) * bhi(q[1]) + blo(q[3]) * blo(q[3]) + bhi(q[3]) * bhi(q[3]));
    const float b0 = sqrtf(n0 * kmax) * 1.001f, b1 = sqrtf(n1 * kmax) * 1.001f;
    const float m0 = fmaxf(ceilf(b0 - 100.f), 0.f), m1 = fmaxf(ceilf(b1 - 100.f), 0.f);
    float o[12], ob[12];
    attn_pass(o, ob, q, m0, m1, sK, bars, tile == 0, kz);
    const float f0 = ex2(-m0), f1 = ex2(-m1);
#pragma unroll
    for (int i = 0; i < 12; i++) o[i] = fmaf(o[i], (i & 2) ? f1 : f0, ob[i]);
    bool ok = b0 < 220.f && b1 < 220.f && o[8] >= 0x1p-90f && o[10] >= 0x1p-90f;
#pragma unroll
    for (int i = 0; i < 12; i++) ok = ok && fabsf(o[i]) < INFINITY;
    if (!__all_sync(~0u, ok)) attn_safe(o, q, sK);
    const float r0 = 1.f / o[8], r1 = 1.f / o[10];
    uint32_t* op = (uint32_t*)g_o + (((row >> 7) * 64 + h * 2) * 128 + (row & 127)) * 4 + t;
    op[0] = pack_rn(o[0] * r0, o[1] * r0); op[32] = pack_rn(o[2] * r1, o[3] * r1);
    op[512] = pack_rn(o[4] * r0, o[5] * r0); op[512 + 32] = pack_rn(o[6] * r1, o[7] * r1);
  }
}

constexpr int WO_SMEM = 131072 + 65536 + 256;
__global__ void __launch_bounds__(256, 1) k_wo(const __grid_constant__ CUtensorMap mW, const bf16* __restrict__ x) {
  extern __shared__ __align__(1024) uint8_t smem[];
  const uint32_t sA = smem_u32(smem), sB = sA + 131072, bars = sB + 65536;
  const int tid = threadIdx.x, warp = tid >> 5, lane = tid & 31, g = lane >> 2, t = lane & 3;
  const int rb = blockIdx.x >> 3, ct = blockIdx.x & 7;
  pdl_launch();
  if (tid == 0) {
    for (int i = 0; i < 8; i++) mbar_init(bars + 8 * i, 1);
    fence_init();
    for (int i = 0; i < 8; i++) { mbar_expect(bars + 8 * i, 24576); tma2d(sB + i * 8192, &mW, ct * 64, i * 64, bars + 8 * i); }
  }
  const int lrow = warp * 16 + g;
  uint32_t xr[16];
  const uint32_t* xp = (const uint32_t*)(x + (rb * 128 + lrow) * 512 + ct * 64) + t;
#pragma unroll
  for (int j = 0; j < 8; j++) { xr[2 * j] = __ldg(xp + j * 4); xr[2 * j + 1] = __ldg(xp + j * 4 + 8 * 256); }
  __syncthreads();
  pdl_wait();
  if (tid == 0) for (int i = 0; i < 8; i++) bulk_load(sA + i * 16384, g_o + (rb * 64 + i * 8) * 1024, 16384, bars + 8 * i);
  float2 ga[8];
#pragma unroll
  for (int j = 0; j < 8; j++) ga[j] = *(const float2*)(g_mod + 1024 + ct * 64 + j * 8 + t * 2);
  float acc[32];
  const uint64_t da = mk_desc(sA + (warp >> 2) * 1024, 2048, 128, 0), db = mk_desc(sB, 8192, 1024, 1);
#pragma unroll
  for (int c = 0; c < 8; c++) {
    mbar_wait(bars + 8 * c, 0);
    wg_fence();
#pragma unroll
    for (int k = 0; k < 4; k++) wgmma_ss_n64_t1(acc, da + (c * 4 + k) * 256, db + (c * 4 + k) * 128, c + k);
    wg_commit();
  }
  wg_wait<0>();
  reg_fence(acc);
  uint32_t* o = (uint32_t*)g_x1 + ((rb * 64 + ct * 8) * 128 + lrow) * 4 + t;
  float s0 = 0, s1 = 0;
#pragma unroll
  for (int j = 0; j < 8; j++) {
    xr[2 * j] = pack_rn(fmaf(ga[j].x, acc[4 * j], blo(xr[2 * j])), fmaf(ga[j].y, acc[4 * j + 1], bhi(xr[2 * j])));
    xr[2 * j + 1] = pack_rn(fmaf(ga[j].x, acc[4 * j + 2], blo(xr[2 * j + 1])), fmaf(ga[j].y, acc[4 * j + 3], bhi(xr[2 * j + 1])));
    o[j * 512] = xr[2 * j]; o[j * 512 + 32] = xr[2 * j + 1];
    s0 += blo(xr[2 * j]) + bhi(xr[2 * j]); s1 += blo(xr[2 * j + 1]) + bhi(xr[2 * j + 1]);
  }
  const float m0 = qsum(s0) * (1.f / 64), m1 = qsum(s1) * (1.f / 64);
  float v0 = 0, v1 = 0;
#pragma unroll
  for (int j = 0; j < 8; j++) {
    float d;
    d = blo(xr[2 * j]) - m0; v0 += d * d; d = bhi(xr[2 * j]) - m0; v0 += d * d;
    d = blo(xr[2 * j + 1]) - m1; v1 += d * d; d = bhi(xr[2 * j + 1]) - m1; v1 += d * d;
  }
  v0 = qsum(v0); v1 = qsum(v1);
  if (t == 0) g_st[(rb * 128 + lrow) * 8 + ct] = make_float2(m0, v0);
  if (t == 1) g_st[(rb * 128 + lrow + 8) * 8 + ct] = make_float2(m1, v1);
}

constexpr int W2_SMEM = 6 * 32768 + 32768 + 256;
__global__ void __cluster_dims__(2, 1, 1) __launch_bounds__(288, 1) k_w2(const __grid_constant__ CUtensorMap mW, bf16* __restrict__ out) {
  extern __shared__ __align__(1024) uint8_t smem[];
  const uint32_t sR = smem_u32(smem), sX = sR + 6 * 32768, bF = sX + 32768, bE = bF + 48;
  const int tid = threadIdx.x, warp = tid >> 5, lane = tid & 31, g = lane >> 2, t = lane & 3;
  const int kh = blockIdx.x & 1, ct = (blockIdx.x >> 1) & 3, rb = blockIdx.x >> 3;
  pdl_launch();
  if (tid == 256) {
    for (int i = 0; i < 6; i++) { mbar_init(bF + 8 * i, 1); mbar_init(bE + 8 * i, 8); }
    fence_init();
  }
  __syncthreads();
  asm volatile("barrier.cluster.arrive.relaxed.aligned;" ::: "memory");
  if (warp == 8) {
    if (lane == 0) {
      auto abytes = [&](int s) { return (kh == 1 && s == 10) ? 8192 : 16384; };
      auto loadB = [&](int s) {
        const int st = s % 6;
        mbar_expect(bF + 8 * st, 16384 + abytes(s));
        for (int j = 0; j < 2; j++) tma2d(sR + st * 32768 + 16384 + j * 8192, &mW, ct * 128 + j * 64, kh * 704 + s * 64, bF + 8 * st);
      };
      auto loadA = [&](int s) { bulk_load(sR + (s % 6) * 32768, g_h + (rb * 172 + kh * 88 + s * 8) * 1024, abytes(s), bF + 8 * (s % 6)); };
      for (int s = 0; s < 6; s++) loadB(s);
      pdl_wait();
      for (int s = 0; s < 6; s++) loadA(s);
      for (int s = 6; s < 11; s++) { mbar_wait(bE + 8 * (s - 6), 0); loadB(s); loadA(s); }
    }
    __syncwarp();
    asm volatile("barrier.cluster.wait.aligned;" ::: "memory");
    asm volatile("barrier.cluster.arrive.release.aligned;" ::: "memory");
    asm volatile("barrier.cluster.wait.acquire.aligned;" ::: "memory");
    return;
  }
  pdl_wait();
  const int lrow = warp * 16 + g;
  uint32_t xr[16];
  float2 gb[8];
  const uint32_t* xp = (const uint32_t*)g_x1 + ((rb * 64 + ct * 16 + kh * 8) * 128 + lrow) * 4 + t;
#pragma unroll
  for (int j = 0; j < 8; j++) {
    xr[2 * j] = xp[j * 512]; xr[2 * j + 1] = xp[j * 512 + 32];
    gb[j] = *(const float2*)(g_mod + 2560 + ct * 128 + kh * 64 + j * 8 + t * 2);
  }
  float acc[64];
#pragma unroll 1
  for (int s = 0; s < 11; s++) {
    const int st = s % 6;
    mbar_wait(bF + 8 * st, s >= 6);
    const uint64_t da = mk_desc(sR + st * 32768 + (warp >> 2) * 1024, 2048, 128, 0), db = mk_desc(sR + st * 32768 + 16384, 8192, 1024, 1);
    wg_fence();
    wgmma_ss_n128_t1(acc, da, db, s);
    wgmma_ss_n128_t1(acc, da + 256, db + 128, 1);
    wgmma_ss_n128_t1(acc, da + 512, db + 256, 1);
    wgmma_ss_n128_t1(acc, da + 768, db + 384, 1);
    wg_commit();
    wg_wait<1>();
    if (s > 0 && s < 6 && lane == 0) mbar_arrive(bE + 8 * (s - 1));
  }
  wg_wait<0>();
  reg_fence(acc);
  asm volatile("barrier.cluster.wait.aligned;" ::: "memory");
  uint32_t rem;
  asm("mapa.shared::cluster.u32 %0,%1,%2;" : "=r"(rem) : "r"(sX + tid * 16), "r"(kh ^ 1));
#pragma unroll
  for (int j = 0; j < 8; j++) {
    float v[4];
#pragma unroll
    for (int i = 0; i < 4; i++) { v[i] = kh ? acc[4 * j + i] : acc[32 + 4 * j + i]; acc[4 * j + i] = kh ? acc[32 + 4 * j + i] : acc[4 * j + i]; }
    asm volatile("st.shared::cluster.v4.f32 [%0],{%1,%2,%3,%4};" ::"r"(rem + j * 4096), "f"(v[0]), "f"(v[1]), "f"(v[2]), "f"(v[3]) : "memory");
  }
  asm volatile("barrier.cluster.arrive.release.aligned;" ::: "memory");
  asm volatile("barrier.cluster.wait.acquire.aligned;" ::: "memory");
  uint32_t* o = (uint32_t*)(out + (rb * 128 + lrow) * 512 + ct * 128 + kh * 64) + t;
#pragma unroll
  for (int j = 0; j < 8; j++) {
    const float4 p = *(const float4*)(smem + 6 * 32768 + j * 4096 + tid * 16);
    o[j * 4] = pack_rn(fmaf(gb[j].x, acc[4 * j] + p.x, blo(xr[2 * j])), fmaf(gb[j].y, acc[4 * j + 1] + p.y, bhi(xr[2 * j])));
    o[j * 4 + 2048] = pack_rn(fmaf(gb[j].x, acc[4 * j + 2] + p.z, blo(xr[2 * j + 1])), fmaf(gb[j].y, acc[4 * j + 3] + p.w, bhi(xr[2 * j + 1])));
  }
}

typedef CUresult (*EncFn)(CUtensorMap*, CUtensorMapDataType, cuuint32_t, void*, const cuuint64_t*, const cuuint64_t*, const cuuint32_t*,
                          const cuuint32_t*, CUtensorMapInterleave, CUtensorMapSwizzle, CUtensorMapL2promotion, CUtensorMapFloatOOBfill);
static void mk_map(EncFn f, CUtensorMap* m, const void* p, int rows, int cols, int box_rows) {
  cuuint64_t dim[2] = {(cuuint64_t)cols, (cuuint64_t)rows}, str[1] = {(cuuint64_t)cols * 2};
  cuuint32_t box[2] = {64, (cuuint32_t)box_rows}, es[2] = {1, 1};
  f(m, CU_TENSOR_MAP_DATA_TYPE_BFLOAT16, 2, (void*)p, dim, str, box, es, CU_TENSOR_MAP_INTERLEAVE_NONE, CU_TENSOR_MAP_SWIZZLE_128B,
    CU_TENSOR_MAP_L2_PROMOTION_L2_128B, CU_TENSOR_MAP_FLOAT_OOB_FILL_NONE);
}
template <typename... KA, typename... A>
static void launch(void (*k)(KA...), int grid, int block, int smem, bool pdl, A... args) {
  cudaLaunchConfig_t cfg = {};
  cfg.gridDim = dim3(grid); cfg.blockDim = dim3(block); cfg.dynamicSmemBytes = smem; cfg.stream = cudaStreamPerThread;
  cudaLaunchAttribute at[1];
  at[0].id = cudaLaunchAttributeProgrammaticStreamSerialization; at[0].val.programmaticStreamSerializationAllowed = 1;
  cfg.attrs = at; cfg.numAttrs = pdl ? 1 : 0;
  cudaLaunchKernelEx(&cfg, k, args...);
}
extern "C" void kernel_launch(void* const* d_in, const int* in_sizes, int n_in, void* d_out, int out_size) {
  const bf16 *x = (const bf16*)d_in[0], *wqkv = (const bf16*)d_in[1], *wo = (const bf16*)d_in[2], *w1 = (const bf16*)d_in[4],
             *w3 = (const bf16*)d_in[5], *w2 = (const bf16*)d_in[6], *c = (const bf16*)d_in[7], *wmod = (const bf16*)d_in[8];
  void* fp = nullptr;
  cudaDriverEntryPointQueryResult qr;
  cudaGetDriverEntryPoint("cuTensorMapEncodeTiled", &fp, cudaEnableDefault, &qr);
  EncFn f = (EncFn)fp;
  CUtensorMap mX, mQ, mO, m1, m3, m2;
  mk_map(f, &mX, x, S_, D_, 128); mk_map(f, &mQ, wqkv, D_, 3 * D_, 64); mk_map(f, &mO, wo, D_, D_, 64);
  mk_map(f, &m1, w1, D_, F_, 32); mk_map(f, &m3, w3, D_, F_, 32); mk_map(f, &m2, w2, F_, D_, 64);
  cudaFuncSetAttribute(k_lngemm<false>, cudaFuncAttributeMaxDynamicSharedMemorySize, LN_SMEM);
  cudaFuncSetAttribute(k_lngemm<true>, cudaFuncAttributeMaxDynamicSharedMemorySize, LN_SMEM);
  cudaFuncSetAttribute(k_attn, cudaFuncAttributeMaxDynamicSharedMemorySize, AT_SMEM);
  cudaFuncSetAttribute(k_wo, cudaFuncAttributeMaxDynamicSharedMemorySize, WO_SMEM);
  cudaFuncSetAttribute(k_w2, cudaFuncAttributeMaxDynamicSharedMemorySize, W2_SMEM);
  launch(k_mod, 96, 256, 0, false, c, wmod);
  launch(k_lngemm<false>, 128, 384, LN_SMEM, true, mX, mQ, mQ);
  launch(k_attn, 128, 512, AT_SMEM, true, wo, w1, w3, w2, 0u);
  launch(k_wo, 128, 256, WO_SMEM, true, mO, x);
  launch(k_lngemm<true>, 128, 384, LN_SMEM, true, mX, m1, m3);
  launch(k_w2, 128, 288, W2_SMEM, true, m2, (bf16*)d_out);
}
```

```cpp
#include <cuda_runtime.h>
#include <cuda_bf16.h>
#include <cuda.h>
#include <stdint.h>
typedef __nv_bfloat16 bf16;
constexpr int S_ = 2048, D_ = 512, F_ = 1376;
__device__ __align__(1024) float g_mod[3072];
__device__ __align__(1024) uint32_t g_modv[1024];
__device__ __align__(1024) bf16 g_qkv[192 * 2048 * 8];
__device__ __align__(1024) float g_kmax[32 * 128];
__device__ __align__(1024) bf16 g_o[16 * 64 * 128 * 8];
__device__ __align__(1024) bf16 g_x1[16 * 64 * 128 * 8];
__device__ __align__(1024) float2 g_st[2048 * 8];
__device__ __align__(1024) bf16 g_h[16 * 172 * 128 * 8];

__device__ __forceinline__ uint32_t smem_u32(const void* p) { return (uint32_t)__cvta_generic_to_shared(p); }
__device__ __forceinline__ void mbar_init(uint32_t b, int n) { asm volatile("mbarrier.init.shared::cta.b64 [%0],%1;" ::"r"(b), "r"(n) : "memory"); }
__device__ __forceinline__ void mbar_expect(uint32_t b, int bytes) { asm volatile("mbarrier.arrive.expect_tx.shared::cta.b64 _,[%0],%1;" ::"r"(b), "r"(bytes) : "memory"); }
__device__ __forceinline__ void mbar_arrive(uint32_t b) { asm volatile("mbarrier.arrive.shared::cta.b64 _,[%0];" ::"r"(b) : "memory"); }
__device__ __forceinline__ void mbar_wait(uint32_t b, int parity) {
  asm volatile("{\n.reg .pred p;\n.reg .u32 n;\nmov.u32 n,0;\nLW:\nmbarrier.try_wait.parity.shared::cta.b64 p,[%0],%1;\n@p bra LD;\n"
               "add.u32 n,n,1;\nsetp.lt.u32 p,n,4194304;\n@p bra LW;\nLD:\n}\n" ::"r"(b), "r"(parity) : "memory");
}
__device__ __forceinline__ void fence_init() { asm volatile("fence.mbarrier_init.release.cluster;" ::: "memory"); }
__device__ __forceinline__ void fence_async() { asm volatile("fence.proxy.async.shared::cta;" ::: "memory"); }
__device__ __forceinline__ void bulk_load(uint32_t dst, const void* src, int bytes, uint32_t bar) {
  asm volatile("cp.async.bulk.shared::cluster.global.mbarrier::complete_tx::bytes [%0],[%1],%2,[%3];" ::"r"(dst), "l"(src), "r"(bytes), "r"(bar) : "memory");
}
__device__ __forceinline__ void tma2d(uint32_t dst, const CUtensorMap* m, int c0, int c1, uint32_t bar) {
  asm volatile("cp.async.bulk.tensor.2d.shared::cluster.global.mbarrier::complete_tx::bytes [%0],[%1,{%3,%4}],[%2];" ::"r"(dst), "l"(m), "r"(bar), "r"(c0), "r"(c1) : "memory");
}
__device__ __forceinline__ void l2_prefetch(const void* p, int bytes) { asm volatile("cp.async.bulk.prefetch.L2.global [%0],%1;" ::"l"(p), "r"(bytes) : "memory"); }
__device__ __forceinline__ void pdl_launch() { asm volatile("griddepcontrol.launch_dependents;" ::: "memory"); }
__device__ __forceinline__ void pdl_wait() { asm volatile("griddepcontrol.wait;" ::: "memory"); }
__device__ __forceinline__ void wg_fence() { asm volatile("wgmma.fence.sync.aligned;" ::: "memory"); }
__device__ __forceinline__ void wg_commit() { asm volatile("wgmma.commit_group.sync.aligned;" ::: "memory"); }
template <int N> __device__ __forceinline__ void wg_wait() { asm volatile("wgmma.wait_group.sync.aligned %0;" ::"n"(N) : "memory"); }
template <int N> __device__ __forceinline__ void reg_fence(float (&d)[N]) {
#pragma unroll
  for (int i = 0; i < N; i++) asm volatile("" : "+f"(d[i])::"memory");
}
template <int N> __device__ __forceinline__ void zero(float (&d)[N]) {
#pragma unroll
  for (int i = 0; i < N; i++) d[i] = 0.f;
  reg_fence(d);
}
__device__ __forceinline__ uint64_t mk_desc(uint32_t addr, uint32_t lbo, uint32_t sbo, uint32_t mode) {
  return (uint64_t)((addr >> 4) & 0x3FFF) | ((uint64_t)(lbo >> 4) << 16) | ((uint64_t)(sbo >> 4) << 32) | ((uint64_t)mode << 62);
}
__device__ __forceinline__ void ldsm4(uint32_t a, uint32_t (&r)[4]) {
  asm volatile("ldmatrix.sync.aligned.m8n8.x4.shared.b16 {%0,%1,%2,%3},[%4];" : "=r"(r[0]), "=r"(r[1]), "=r"(r[2]), "=r"(r[3]) : "r"(a) : "memory");
}
__device__ __forceinline__ uint32_t pack_rn(float lo, float hi) { uint32_t r; asm("cvt.rn.bf16x2.f32 %0,%1,%2;" : "=r"(r) : "f"(hi), "f"(lo)); return r; }
__device__ __forceinline__ uint32_t pack_rz(float lo, float hi) { uint32_t r; asm("cvt.rz.bf16x2.f32 %0,%1,%2;" : "=r"(r) : "f"(hi), "f"(lo)); return r; }
__device__ __forceinline__ float blo(uint32_t u) { return __uint_as_float(u << 16); }
__device__ __forceinline__ float bhi(uint32_t u) { return __uint_as_float(u & 0xFFFF0000u); }
__device__ __forceinline__ float rbf(float x) { return __bfloat162float(__float2bfloat16_rn(x)); }
__device__ __forceinline__ float qsum(float v) { v += __shfl_xor_sync(~0u, v, 1); return v + __shfl_xor_sync(~0u, v, 2); }
__device__ __forceinline__ float ex2(float x) { float r; asm("ex2.approx.ftz.f32 %0,%1;" : "=f"(r) : "f"(x)); return r; }
#define TS(k, i)
__device__ __forceinline__ void wgmma_rs_n176_t1(float (&d)[88],uint32_t a0,uint32_t a1,uint32_t a2,uint32_t a3,uint64_t db,int sc){
  asm volatile("{\n.reg .pred p;\nsetp.ne.b32 p,%93,0;\n"
    "wgmma.mma_async.sync.aligned.m64n176k16.f32.bf16.bf16 {%0,%1,%2,%3,%4,%5,%6,%7,%8,%9,%10,%11,%12,%13,%14,%15,%16,%17,%18,%19,%20,%21,%22,%23,%24,%25,%26,%27,%28,%29,%30,%31,%32,%33,%34,%35,%36,%37,%38,%39,%40,%41,%42,%43,%44,%45,%46,%47,%48,%49,%50,%51,%52,%53,%54,%55,%56,%57,%58,%59,%60,%61,%62,%63,%64,%65,%66,%67,%68,%69,%70,%71,%72,%73,%74,%75,%76,%77,%78,%79,%80,%81,%82,%83,%84,%85,%86,%87},{%88,%89,%90,%91},%92,p,1,1,1;\n}\n"
    :"+f"(d[0]),"+f"(d[1]),"+f"(d[2]),"+f"(d[3]),"+f"(d[4]),"+f"(d[5]),"+f"(d[6]),"+f"(d[7]),"+f"(d[8]),"+f"(d[9]),"+f"(d[10]),"+f"(d[11]),"+f"(d[12]),"+f"(d[13]),"+f"(d[14]),"+f"(d[15]),"+f"(d[16]),"+f"(d[17]),"+f"(d[18]),"+f"(d[19]),"+f"(d[20]),"+f"(d[21]),"+f"(d[22]),"+f"(d[23]),"+f"(d[24]),"+f"(d[25]),"+f"(d[26]),"+f"(d[27]),"+f"(d[28]),"+f"(d[29]),"+f"(d[30]),"+f"(d[31]),"+f"(d[32]),"+f"(d[33]),"+f"(d[34]),"+f"(d[35]),"+f"(d[36]),"+f"(d[37]),"+f"(d[38]),"+f"(d[39]),"+f"(d[40]),"+f"(d[41]),"+f"(d[42]),"+f"(d[43]),"+f"(d[44]),"+f"(d[45]),"+f"(d[46]),"+f"(d[47]),"+f"(d[48]),"+f"(d[49]),"+f"(d[50]),"+f"(d[51]),"+f"(d[52]),"+f"(d[53]),"+f"(d[54]),"+f"(d[55]),"+f"(d[56]),"+f"(d[57]),"+f"(d[58]),"+f"(d[59]),"+f"(d[60]),"+f"(d[61]),"+f"(d[62]),"+f"(d[63]),"+f"(d[64]),"+f"(d[65]),"+f"(d[66]),"+f"(d[67]),"+f"(d[68]),"+f"(d[69]),"+f"(d[70]),"+f"(d[71]),"+f"(d[72]),"+f"(d[73]),"+f"(d[74]),"+f"(d[75]),"+f"(d[76]),"+f"(d[77]),"+f"(d[78]),"+f"(d[79]),"+f"(d[80]),"+f"(d[81]),"+f"(d[82]),"+f"(d[83]),"+f"(d[84]),"+f"(d[85]),"+f"(d[86]),"+f"(d[87])
    :"r"(a0),"r"(a1),"r"(a2),"r"(a3),"l"(db),"r"(sc));
}
__device__ __forceinline__ void wgmma_rs_n192_t1(float (&d)[96],uint32_t a0,uint32_t a1,uint32_t a2,uint32_t a3,uint64_t db,int sc){
  asm volatile("{\n.reg .pred p;\nsetp.ne.b32 p,%101,0;\n"
    "wgmma.mma_async.sync.aligned.m64n192k16.f32.bf16.bf16 {%0,%1,%2,%3,%4,%5,%6,%7,%8,%9,%10,%11,%12,%13,%14,%15,%16,%17,%18,%19,%20,%21,%22,%23,%24,%25,%26,%27,%28,%29,%30,%31,%32,%33,%34,%35,%36,%37,%38,%39,%40,%41,%42,%43,%44,%45,%46,%47,%48,%49,%50,%51,%52,%53,%54,%55,%56,%57,%58,%59,%60,%61,%62,%63,%64,%65,%66,%67,%68,%69,%70,%71,%72,%73,%74,%75,%76,%77,%78,%79,%80,%81,%82,%83,%84,%85,%86,%87,%88,%89,%90,%91,%92,%93,%94,%95},{%96,%97,%98,%99},%100,p,1,1,1;\n}\n"
    :"+f"(d[0]),"+f"(d[1]),"+f"(d[2]),"+f"(d[3]),"+f"(d[4]),"+f"(d[5]),"+f"(d[6]),"+f"(d[7]),"+f"(d[8]),"+f"(d[9]),"+f"(d[10]),"+f"(d[11]),"+f"(d[12]),"+f"(d[13]),"+f"(d[14]),"+f"(d[15]),"+f"(d[16]),"+f"(d[17]),"+f"(d[18]),"+f"(d[19]),"+f"(d[20]),"+f"(d[21]),"+f"(d[22]),"+f"(d[23]),"+f"(d[24]),"+f"(d[25]),"+f"(d[26]),"+f"(d[27]),"+f"(d[28]),"+f"(d[29]),"+f"(d[30]),"+f"(d[31]),"+f"(d[32]),"+f"(d[33]),"+f"(d[34]),"+f"(d[35]),"+f"(d[36]),"+f"(d[37]),"+f"(d[38]),"+f"(d[39]),"+f"(d[40]),"+f"(d[41]),"+f"(d[42]),"+f"(d[43]),"+f"(d[44]),"+f"(d[45]),"+f"(d[46]),"+f"(d[47]),"+f"(d[48]),"+f"(d[49]),"+f"(d[50]),"+f"(d[51]),"+f"(d[52]),"+f"(d[53]),"+f"(d[54]),"+f"(d[55]),"+f"(d[56]),"+f"(d[57]),"+f"(d[58]),"+f"(d[59]),"+f"(d[60]),"+f"(d[61]),"+f"(d[62]),"+f"(d[63]),"+f"(d[64]),"+f"(d[65]),"+f"(d[66]),"+f"(d[67]),"+f"(d[68]),"+f"(d[69]),"+f"(d[70]),"+f"(d[71]),"+f"(d[72]),"+f"(d[73]),"+f"(d[74]),"+f"(d[75]),"+f"(d[76]),"+f"(d[77]),"+f"(d[78]),"+f"(d[79]),"+f"(d[80]),"+f"(d[81]),"+f"(d[82]),"+f"(d[83]),"+f"(d[84]),"+f"(d[85]),"+f"(d[86]),"+f"(d[87]),"+f"(d[88]),"+f"(d[89]),"+f"(d[90]),"+f"(d[91]),"+f"(d[92]),"+f"(d[93]),"+f"(d[94]),"+f"(d[95])
    :"r"(a0),"r"(a1),"r"(a2),"r"(a3),"l"(db),"r"(sc));
}
__device__ __forceinline__ void wgmma_rs_n24_t1(float (&d)[12],uint32_t a0,uint32_t a1,uint32_t a2,uint32_t a3,uint64_t db,int sc){
  asm volatile("{\n.reg .pred p;\nsetp.ne.b32 p,%17,0;\n"
    "wgmma.mma_async.sync.aligned.m64n24k16.f32.bf16.bf16 {%0,%1,%2,%3,%4,%5,%6,%7,%8,%9,%10,%11},{%12,%13,%14,%15},%16,p,1,1,1;\n}\n"
    :"+f"(d[0]),"+f"(d[1]),"+f"(d[2]),"+f"(d[3]),"+f"(d[4]),"+f"(d[5]),"+f"(d[6]),"+f"(d[7]),"+f"(d[8]),"+f"(d[9]),"+f"(d[10]),"+f"(d[11])
    :"r"(a0),"r"(a1),"r"(a2),"r"(a3),"l"(db),"r"(sc));
}
__device__ __forceinline__ void wgmma_rs_n64_t0(float (&d)[32],uint32_t a0,uint32_t a1,uint32_t a2,uint32_t a3,uint64_t db,int sc){
  asm volatile("{\n.reg .pred p;\nsetp.ne.b32 p,%37,0;\n"
    "wgmma.mma_async.sync.aligned.m64n64k16.f32.bf16.bf16 {%0,%1,%2,%3,%4,%5,%6,%7,%8,%9,%10,%11,%12,%13,%14,%15,%16,%17,%18,%19,%20,%21,%22,%23,%24,%25,%26,%27,%28,%29,%30,%31},{%32,%33,%34,%35},%36,p,1,1,0;\n}\n"
    :"+f"(d[0]),"+f"(d[1]),"+f"(d[2]),"+f"(d[3]),"+f"(d[4]),"+f"(d[5]),"+f"(d[6]),"+f"(d[7]),"+f"(d[8]),"+f"(d[9]),"+f"(d[10]),"+f"(d[11]),"+f"(d[12]),"+f"(d[13]),"+f"(d[14]),"+f"(d[15]),"+f"(d[16]),"+f"(d[17]),"+f"(d[18]),"+f"(d[19]),"+f"(d[20]),"+f"(d[21]),"+f"(d[22]),"+f"(d[23]),"+f"(d[24]),"+f"(d[25]),"+f"(d[26]),"+f"(d[27]),"+f"(d[28]),"+f"(d[29]),"+f"(d[30]),"+f"(d[31])
    :"r"(a0),"r"(a1),"r"(a2),"r"(a3),"l"(db),"r"(sc));
}
__device__ __forceinline__ void wgmma_ss_n128_t1(float (&d)[64],uint64_t da,uint64_t db,int sc){
  asm volatile("{\n.reg .pred p;\nsetp.ne.b32 p,%66,0;\n"
    "wgmma.mma_async.sync.aligned.m64n128k16.f32.bf16.bf16 {%0,%1,%2,%3,%4,%5,%6,%7,%8,%9,%10,%11,%12,%13,%14,%15,%16,%17,%18,%19,%20,%21,%22,%23,%24,%25,%26,%27,%28,%29,%30,%31,%32,%33,%34,%35,%36,%37,%38,%39,%40,%41,%42,%43,%44,%45,%46,%47,%48,%49,%50,%51,%52,%53,%54,%55,%56,%57,%58,%59,%60,%61,%62,%63},%64,%65,p,1,1,0,1;\n}\n"
    :"+f"(d[0]),"+f"(d[1]),"+f"(d[2]),"+f"(d[3]),"+f"(d[4]),"+f"(d[5]),"+f"(d[6]),"+f"(d[7]),"+f"(d[8]),"+f"(d[9]),"+f"(d[10]),"+f"(d[11]),"+f"(d[12]),"+f"(d[13]),"+f"(d[14]),"+f"(d[15]),"+f"(d[16]),"+f"(d[17]),"+f"(d[18]),"+f"(d[19]),"+f"(d[20]),"+f"(d[21]),"+f"(d[22]),"+f"(d[23]),"+f"(d[24]),"+f"(d[25]),"+f"(d[26]),"+f"(d[27]),"+f"(d[28]),"+f"(d[29]),"+f"(d[30]),"+f"(d[31]),"+f"(d[32]),"+f"(d[33]),"+f"(d[34]),"+f"(d[35]),"+f"(d[36]),"+f"(d[37]),"+f"(d[38]),"+f"(d[39]),"+f"(d[40]),"+f"(d[41]),"+f"(d[42]),"+f"(d[43]),"+f"(d[44]),"+f"(d[45]),"+f"(d[46]),"+f"(d[47]),"+f"(d[48]),"+f"(d[49]),"+f"(d[50]),"+f"(d[51]),"+f"(d[52]),"+f"(d[53]),"+f"(d[54]),"+f"(d[55]),"+f"(d[56]),"+f"(d[57]),"+f"(d[58]),"+f"(d[59]),"+f"(d[60]),"+f"(d[61]),"+f"(d[62]),"+f"(d[63])
    :"l"(da),"l"(db),"r"(sc));
}
__device__ __forceinline__ void wgmma_ss_n64_t1(float (&d)[32],uint64_t da,uint64_t db,int sc){
  asm volatile("{\n.reg .pred p;\nsetp.ne.b32 p,%34,0;\n"
    "wgmma.mma_async.sync.aligned.m64n64k16.f32.bf16.bf16 {%0,%1,%2,%3,%4,%5,%6,%7,%8,%9,%10,%11,%12,%13,%14,%15,%16,%17,%18,%19,%20,%21,%22,%23,%24,%25,%26,%27,%28,%29,%30,%31},%32,%33,p,1,1,0,1;\n}\n"
    :"+f"(d[0]),"+f"(d[1]),"+f"(d[2]),"+f"(d[3]),"+f"(d[4]),"+f"(d[5]),"+f"(d[6]),"+f"(d[7]),"+f"(d[8]),"+f"(d[9]),"+f"(d[10]),"+f"(d[11]),"+f"(d[12]),"+f"(d[13]),"+f"(d[14]),"+f"(d[15]),"+f"(d[16]),"+f"(d[17]),"+f"(d[18]),"+f"(d[19]),"+f"(d[20]),"+f"(d[21]),"+f"(d[22]),"+f"(d[23]),"+f"(d[24]),"+f"(d[25]),"+f"(d[26]),"+f"(d[27]),"+f"(d[28]),"+f"(d[29]),"+f"(d[30]),"+f"(d[31])
    :"l"(da),"l"(db),"r"(sc));
}

__device__ __forceinline__ float silu_bf(const bf16* c, int r) { const float x = __bfloat162float(c[r]); return rbf(x / (1.f + __expf(-x))); }
__device__ __forceinline__ void fma8(float (&a)[8], float s, const uint4& v) {
  a[0] += s * blo(v.x); a[1] += s * bhi(v.x); a[2] += s * blo(v.y); a[3] += s * bhi(v.y);
  a[4] += s * blo(v.z); a[5] += s * bhi(v.z); a[6] += s * blo(v.w); a[7] += s * bhi(v.w);
}
__device__ __forceinline__ float red8(float (&a)[8], int lane) {
#pragma unroll
  for (int w = 4; w >= 1; w >>= 1) {
    const bool up = lane & (w * 4);
#pragma unroll
    for (int j = 0; j < w; j++) a[j] = (up ? a[j + w] : a[j]) + __shfl_xor_sync(~0u, up ? a[j] : a[j + w], w * 4);
  }
  return a[0];
}
__device__ __forceinline__ float mod_fin(float s, int n) { s = rbf(s); return ((n >> 9) == 1 || (n >> 9) == 4) ? rbf(1.f + s) : s; }
__device__ __forceinline__ uint2 poll2(const uint32_t* p) {
  uint2 v;
  asm volatile("{\n.reg .pred p;\n.reg .u32 n,t;\nmov.u32 n,0;\nLW:\nld.relaxed.gpu.global.v2.u32 {%0,%1},[%2];\nand.b32 t,%0,%1;\nand.b32 t,t,1;\n"
               "setp.ne.u32 p,t,0;\n@p bra LD;\nadd.u32 n,n,1;\nsetp.lt.u32 p,n,1048576;\n@p bra LW;\nLD:\n}\n" : "=r"(v.x), "=r"(v.y) : "l"(p) : "memory");
  return v;
}

constexpr int LN_SMEM = 131072 + 4 * 24576 + 2048 + 256 + 512;
template <bool FFN>
__global__ void __launch_bounds__(384, 1) k_lngemm(const __grid_constant__ CUtensorMap mX, const __grid_constant__ CUtensorMap mB0,
                                                   const __grid_constant__ CUtensorMap mB1, const bf16* __restrict__ cv, const bf16* __restrict__ wm) {
  extern __shared__ __align__(1024) uint8_t smem[];
  const uint32_t sA = smem_u32(smem), sB = sA + 131072, sM = sB + 4 * 24576, bars = sM + 2048;
  const uint32_t bA = bars, bF = bars + 64, bE = bars + 96;
  const int tid = threadIdx.x, warp = tid >> 5, lane = tid & 31;
  const int rb = blockIdx.x >> 3, ct = blockIdx.x & 7;
  constexpr int NST = FFN ? 16 : 8, KS = FFN ? 2 : 4, BOX = FFN ? 4096 : 8192;
  TS(FFN ? 4 : 1, 0);
  pdl_launch();
  float* red = (float*)(smem + (bars - sA) + 256);
  uint4 wv0, wv1;
  if (!FFN && tid < 256) { wv0 = __ldg((const uint4*)(wm + tid * 3072 + blockIdx.x * 8)); wv1 = __ldg((const uint4*)(wm + (tid + 256) * 3072 + blockIdx.x * 8)); }
  if (tid == 256) {
    for (int i = 0; i < 8; i++) mbar_init(bA + 8 * i, 1);
    for (int i = 0; i < 4; i++) { mbar_init(bF + 8 * i, 1); mbar_init(bE + 8 * i, 8); }
    fence_init();
  }
  __syncthreads();
  if (warp >= 8) {
    asm volatile("setmaxnreg.dec.sync.aligned.u32 40;");
    if (tid == 256) {
      auto loadB = [&](int s) {
        const uint32_t d = sB + (s & 3) * 24576, b = bF + (s & 3) * 8;
        mbar_expect(b, 24576);
        for (int j = 0; j < 3; j++) {
          if (FFN) { tma2d(d + j * BOX, &mB0, ct * 176 + j * 64, s * 32, b); tma2d(d + (3 + j) * BOX, &mB1, ct * 176 + j * 64, s * 32, b); }
          else tma2d(d + j * BOX, &mB0, ct * 192 + j * 64, s * 64, b);
        }
      };
      if (!FFN) for (int i = 0; i < 8; i++) { mbar_expect(bA + 8 * i, 16384); tma2d(sA + i * 16384, &mX, i * 64, rb * 128, bA + 8 * i); }
      for (int s = 0; s < 4; s++) loadB(s);
      if (FFN) {
        pdl_wait();
        for (int i = 0; i < 8; i++) { mbar_expect(bA + 8 * i, 16384); bulk_load(sA + i * 16384, g_x1 + (rb * 64 + i * 8) * 1024, 16384, bA + 8 * i); }
      }
      for (int s = 4; s < NST; s++) { mbar_wait(bE + (s & 3) * 8, ((s >> 2) - 1) & 1); loadB(s); }
    } else if (!FFN && warp > 8) {
      mbar_wait(bA + 56, 0);
      const int u = tid - 288, n0 = 1024 + blockIdx.x * 16;
      float a[8] = {0, 0, 0, 0, 0, 0, 0, 0};
#pragma unroll 3
      for (int r = u >> 1; r < 512; r += 48) fma8(a, silu_bf(cv, r), __ldg((const uint4*)(wm + r * 3072 + n0 + (u & 1) * 8)));
      float s = red8(a, lane);
      s += __shfl_xor_sync(~0u, s, 2);
      if (!(lane & 2)) red[64 + (warp - 9) * 16 + (lane & 1) * 8 + (lane >> 2)] = s;
      asm volatile("bar.sync 2,96;" ::: "memory");
      if (u < 16) g_mod[n0 + u] = mod_fin(red[64 + u] + red[80 + u] + red[96 + u], n0 + u);
    }
  } else {
  asm volatile("setmaxnreg.inc.sync.aligned.u32 232;");
  const int g = lane >> 2, t = lane & 3;
  const int lr = warp * 16 + (lane & 7) + ((lane >> 3) & 1) * 8;
  auto aaddr = [&](int ks) -> uint32_t {
    if (FFN) return sA + (ks * 2 + (lane >> 4)) * 2048 + lr * 16;
    return sA + (ks >> 2) * 16384 + lr * 128 + ((((ks & 3) * 2 + (lane >> 4)) ^ (lr & 7)) << 4);
  };
  const int row0 = rb * 128 + warp * 16 + g;
  float2 msh, msc;
  float rs0, rs1, nm0, nm1;
  if (!FFN) {
    {
      float a[8] = {0, 0, 0, 0, 0, 0, 0, 0};
      fma8(a, silu_bf(cv, tid), wv0); fma8(a, silu_bf(cv, tid + 256), wv1);
      const float s = qsum(red8(a, lane));
      if (t == 0) red[warp * 8 + g] = s;
      asm volatile("bar.sync 1,256;" ::: "memory");
      if (tid < 8) {
        float r = 0;
#pragma unroll
        for (int i = 0; i < 8; i++) r += red[i * 8 + tid];
        const int n = blockIdx.x * 8 + tid;
        asm volatile("st.relaxed.gpu.global.u32 [%0],%1;" ::"l"(g_modv + n), "r"(__float_as_uint(mod_fin(r, n)) | 1u) : "memory");
      }
      TS(0, 1);
    }
    float s0 = 0, s1 = 0;
#pragma unroll 4
    for (int ks = 0; ks < 32; ks++) {
      if ((ks & 3) == 0) mbar_wait(bA + 2 * ks, 0);
      uint32_t r[4]; ldsm4(aaddr(ks), r);
      s0 += (blo(r[0]) + bhi(r[0])) + (blo(r[2]) + bhi(r[2]));
      s1 += (blo(r[1]) + bhi(r[1])) + (blo(r[3]) + bhi(r[3]));
    }
    const float m0 = qsum(s0) * (1.f / 512), m1 = qsum(s1) * (1.f / 512);
    float v0 = 0, v1 = 0, v2 = 0, v3 = 0;
#pragma unroll 4
    for (int ks = 0; ks < 32; ks++) {
      uint32_t r[4]; ldsm4(aaddr(ks), r);
      float d;
      d = blo(r[0]) - m0; v0 += d * d; d = bhi(r[0]) - m0; v2 += d * d; d = blo(r[2]) - m0; v0 += d * d; d = bhi(r[2]) - m0; v2 += d * d;
      d = blo(r[1]) - m1; v1 += d * d; d = bhi(r[1]) - m1; v3 += d * d; d = blo(r[3]) - m1; v1 += d * d; d = bhi(r[3]) - m1; v3 += d * d;
    }
    rs0 = rsqrtf(qsum(v0 + v2) * (1.f / 512) + 1e-5f); rs1 = rsqrtf(qsum(v1 + v3) * (1.f / 512) + 1e-5f);
    nm0 = -m0 * rs0; nm1 = -m1 * rs1;
#pragma unroll 4
    for (int ks = 0; ks < 32; ks++) {
      uint32_t r[4]; ldsm4(aaddr(ks), r);
#pragma unroll
      for (int i = 0; i < 4; i++) { const float rs = (i & 1) ? rs1 : rs0, nm = (i & 1) ? nm1 : nm0; r[i] = pack_rn(fmaf(blo(r[i]), rs, nm), fmaf(bhi(r[i]), rs, nm)); }
      asm volatile("stmatrix.sync.aligned.m8n8.x4.shared.b16 [%0],{%1,%2,%3,%4};" ::"r"(aaddr(ks)), "r"(r[0]), "r"(r[1]), "r"(r[2]), "r"(r[3]) : "memory");
    }
    TS(1, 1);
  } else {
    pdl_wait();
    TS(4, 1);
    msh = *(const float2*)(g_mod + 1536 + tid * 2); msc = *(const float2*)(g_mod + 2048 + tid * 2);
    const float4 p0 = *(const float4*)(g_st + row0 * 8 + t * 2), p1 = *(const float4*)(g_st + (row0 + 8) * 8 + t * 2);
    const float m0 = qsum(p0.x + p0.z) * 0.125f, m1 = qsum(p1.x + p1.z) * 0.125f;
    const float v0 = qsum(p0.y + p0.w + 64.f * ((p0.x - m0) * (p0.x - m0) + (p0.z - m0) * (p0.z - m0)));
    const float v1 = qsum(p1.y + p1.w + 64.f * ((p1.x - m1) * (p1.x - m1) + (p1.z - m1) * (p1.z - m1)));
    rs0 = rsqrtf(v0 * (1.f / 512) + 1e-5f); rs1 = rsqrtf(v1 * (1.f / 512) + 1e-5f);
    nm0 = -m0 * rs0; nm1 = -m1 * rs1;
  }
  {
    uint32_t* m = (uint32_t*)(smem + (sM - sA)) + (tid >> 3) * 16 + (tid & 3) * 4 + ((tid >> 2) & 1);
    if (FFN) { m[0] = pack_rn(msc.x, msc.y); m[2] = pack_rn(msh.x, msh.y); }
    else { const uint2 sh = poll2(g_modv + tid * 2), sc = poll2(g_modv + 512 + tid * 2); m[0] = __byte_perm(sc.x, sc.y, 0x7632); m[2] = __byte_perm(sh.x, sh.y, 0x7632); }
    asm volatile("bar.sync 1,256;" ::: "memory");
  }
  constexpr int NA = FFN ? 88 : 96;
  float acc0[NA], acc1[FFN ? 88 : 1];
  uint32_t a[2][4];
  auto prep = [&](int ks, uint32_t(&o)[4]) {
    if (FFN && (ks & 3) == 0) mbar_wait(bA + 2 * ks, 0);
    uint32_t r[4]; ldsm4(aaddr(ks), r);
    const uint4 m = *(const uint4*)(smem + (sM - sA) + ks * 64 + t * 16);
#pragma unroll
    for (int i = 0; i < 4; i++) {
      const float rs = (i & 1) ? rs1 : rs0, nm = (i & 1) ? nm1 : nm0;
      const uint32_t n = FFN ? pack_rn(fmaf(blo(r[i]), rs, nm), fmaf(bhi(r[i]), rs, nm)) : r[i];
      asm("fma.rn.bf16x2 %0,%1,%2,%3;" : "=r"(o[i]) : "r"(n), "r"(i < 2 ? m.x : m.y), "r"(i < 2 ? m.z : m.w));
    }
  };
  prep(0, a[0]);
  TS(FFN ? 4 : 1, 2);
#pragma unroll 1
  for (int s = 0; s < NST; s++) {
    mbar_wait(bF + (s & 3) * 8, (s >> 2) & 1);
    const uint64_t db = mk_desc(sB + (s & 3) * 24576, BOX, 1024, 1);
#pragma unroll
    for (int k = 0; k < KS; k++) {
      const int ks = s * KS + k;
      uint32_t(&c)[4] = a[k & 1];
      wg_fence();
      if constexpr (FFN) {
        wgmma_rs_n176_t1(acc0, c[0], c[1], c[2], c[3], db + k * 128, ks);
        wgmma_rs_n176_t1(acc1, c[0], c[1], c[2], c[3], db + k * 128 + 3 * BOX / 16, ks);
      } else {
        wgmma_rs_n192_t1(acc0, c[0], c[1], c[2], c[3], db + k * 128, ks);
      }
      wg_commit();
      wg_wait<1>();
      if (k == 0 && s > 0 && lane == 0) mbar_arrive(bE + ((s - 1) & 3) * 8);
      if (ks < 31) prep(ks + 1, a[(k + 1) & 1]);
    }
  }
  wg_wait<0>();
  reg_fence(acc0);
  TS(FFN ? 4 : 1, 3);
  if constexpr (FFN) {
    reg_fence(acc1);
    uint32_t* o = (uint32_t*)g_h + ((rb * 172 + ct * 22) * 128 + warp * 16 + g) * 4 + t;
#pragma unroll
    for (int j = 0; j < 22; j++) {
      if (ct * 22 + j < 172) {
        float h[4];
#pragma unroll
        for (int i = 0; i < 4; i++) { const float x = acc0[4 * j + i]; h[i] = __fdividef(x, 1.f + ex2(-1.4426950408889634f * x)) * acc1[4 * j + i]; }
        o[j * 512] = pack_rn(h[0], h[1]);
        o[j * 512 + 32] = pack_rn(h[2], h[3]);
      }
    }
  } else {
    uint32_t* o = (uint32_t*)g_qkv + (ct * 24 * 2048 + row0) * 4 + t;
#pragma unroll
    for (int j = 0; j < 24; j += 2) {
      const int G = ct * 24 + j;
      const float sc = G < 64 ? 0.25f * 1.4426950408889634f : 1.f;
      uint32_t p[4];
#pragma unroll
      for (int i = 0; i < 4; i++) p[i] = pack_rn(acc0[4 * j + 2 * i] * sc, acc0[4 * j + 2 * i + 1] * sc);
      o[j * 8192] = p[0]; o[j * 8192 + 32] = p[1]; o[(j + 1) * 8192] = p[2]; o[(j + 1) * 8192 + 32] = p[3];
      if (G >= 64 && G < 128) {
        float n0 = blo(p[0]) * blo(p[0]) + bhi(p[0]) * bhi(p[0]) + blo(p[2]) * blo(p[2]) + bhi(p[2]) * bhi(p[2]);
        float n1 = blo(p[1]) * blo(p[1]) + bhi(p[1]) * bhi(p[1]) + blo(p[3]) * blo(p[3]) + bhi(p[3]) * bhi(p[3]);
        n0 = qsum(n0); n1 = qsum(n1);
        const uint32_t mx = __reduce_max_sync(~0u, max(__float_as_uint(n0), __float_as_uint(n1)));
        if (lane == 0) g_kmax[((G - 64) >> 1) * 128 + rb * 8 + warp] = __uint_as_float(mx);
      }
    }
  }
  TS(FFN ? 4 : 1, 4);
}
}

#define SMASK 0xAAu
#define BRK 0
#define PACK 1
#define PP 1
constexpr int AT_SMEM = 5 * 32768 + 256;
__device__ __forceinline__ uint32_t exp2_pair_fma(float s0, float s1, float c, uint32_t ka, uint32_t kz) {
  uint32_t r;
  asm volatile("{\n.reg .b32 y0,y1,e,u,t;\n"
      "fma.rn.sat.f32 y0,%1,0f00000080,%3;\nfma.rn.sat.f32 y1,%2,0f00000080,%3;\n"
      "mad.lo.u32 e,y1,65536,y0;\n"
      "and.b32 u,e,0x007F007F;\n"
      "fma.rn.f16x2 u,u,%4,%5;\nfma.rn.f16x2 t,u,u,%6;\nfma.rn.f16x2 t,t,u,%7;\n"
      "lop3.b32 %0,t,0x007F007F,e,0xE2;\n}\n"
      : "=r"(r) : "f"(s0), "f"(s1), "f"(c), "r"(ka), "r"(0x36B236B2u), "r"(0x3C733C73u), "r"(0x47764776u), "r"(kz));
  return r;
}
__device__ __forceinline__ void attn_pass(float (&oa)[12], float (&ob)[12], const uint32_t (&q)[4], float m0, float m1, uint32_t sK, uint32_t bars, bool first, uint32_t kz) {
  const uint64_t dk = mk_desc(sK, 32768, 128, 0), dv = mk_desc(sK + 65536, 128, 32768, 0);
  const float c0 = (127.f - m0) * __uint_as_float(0x80u), c1 = (127.f - m1) * __uint_as_float(0x80u);
  const uint32_t ka = 0x7ACE7ACEu + kz;
  constexpr int NK = 64, NS = 32, NP = 16, NI = 32;
  auto qk = [&](float (&s)[NS], int i) { wgmma_rs_n64_t0(s, q[0], q[1], q[2], q[3], dk + i * NK, 0); };
  auto softmax = [&](float (&s)[NS], uint32_t (&p)[NP], uint32_t mask) {
    reg_fence(s);
    float e0, e1;
    int pend = -1;
#pragma unroll
    for (int t = 0; t < NP; t++) {
      const int j = (t & 3) * 4 + (t >> 2);
      if ((mask >> (t & 3)) & 1) {
        p[j] = exp2_pair_fma(s[2 * j], s[2 * j + 1], (j & 1) ? c1 : c0, ka, kz);
      } else {
        float f0, f1;
        asm volatile("ex2.approx.ftz.f32 %0,%2;\nex2.approx.ftz.f32 %1,%3;" : "=&f"(f0), "=f"(f1) : "f"(s[2 * j]), "f"(s[2 * j + 1]));
        if (pend >= 0) asm volatile("cvt.rn.bf16x2.f32 %0,%1,%2;" : "=r"(p[pend]) : "f"(e1), "f"(e0));
        e0 = f0; e1 = f1; pend = j;
      }
    }
    if (pend >= 0) asm volatile("cvt.rn.bf16x2.f32 %0,%1,%2;" : "=r"(p[pend]) : "f"(e1), "f"(e0));
#pragma unroll
    for (int j = 0; j < NP; j++) asm volatile("" : "+r"(p[j])::"memory");
  };
  auto pv = [&](uint32_t (&p)[NP], int i, uint32_t mask) {
#pragma unroll
    for (int k = 0; k < 4; k++) wgmma_rs_n24_t1(((mask >> k) & 1) ? ob : oa, p[4 * k], p[4 * k + 1], p[4 * k + 2], p[4 * k + 3], dv + i * NK + k * 16, 1);
  };
  auto ld = [&](int i) { if (first && (i & (NI / 4 - 1)) == 0) mbar_wait(bars + i / (NI / 4) * 8, 0); };
  constexpr uint32_t M0 = SMASK & 15, M1 = SMASK >> 4;
  zero(oa); zero(ob);
  ld(0);
  if (first) TS(2, 2);
  float s[NS];
  zero(s);
  uint32_t p0[NP], p1[NP];
  wg_fence(); qk(s, 0); wg_commit(); wg_wait<0>(); softmax(s, p0, M0);
#pragma unroll 1
  for (int i = 0; i < NI - 2; i += 2) {
    wg_fence(); qk(s, i + 1); wg_commit(); pv(p0, i, M0); wg_commit(); wg_wait<1>(); softmax(s, p1, M1); wg_wait<0>();
    ld(i + 2);
    wg_fence(); qk(s, i + 2); wg_commit(); pv(p1, i + 1, M1); wg_commit(); wg_wait<1>(); softmax(s, p0, M0); wg_wait<0>();
  }
  wg_fence(); qk(s, NI - 1); wg_commit(); pv(p0, NI - 2, M0); wg_commit(); wg_wait<1>(); softmax(s, p1, M1); wg_wait<0>();
  wg_fence(); pv(p1, NI - 1, M1); wg_commit();
  wg_wait<0>();
  reg_fence(oa); reg_fence(ob);
}
__device__ __forceinline__ void mma16816(float (&d)[4], const uint32_t (&a)[4], uint32_t b0, uint32_t b1) {
  asm("mma.sync.aligned.m16n8k16.row.col.f32.bf16.bf16.f32 {%0,%1,%2,%3},{%4,%5,%6,%7},{%8,%9},{%0,%1,%2,%3};"
      : "+f"(d[0]), "+f"(d[1]), "+f"(d[2]), "+f"(d[3]) : "r"(a[0]), "r"(a[1]), "r"(a[2]), "r"(a[3]), "r"(b0), "r"(b1));
}
__device__ __forceinline__ void attn_safe(float (&o)[12], const uint32_t (&q)[4], uint32_t sK) {
  const int lane = threadIdx.x & 31;
  const uint32_t ka = sK + (lane >> 4) * 32768 + (lane & 15) * 16;
  float m0 = -INFINITY, m1 = -INFINITY;
#pragma unroll 2
  for (int i = 0; i < 128; i++) {
    uint32_t k[4]; ldsm4(ka + i * 256, k);
    float s0[4] = {0, 0, 0, 0}, s1[4] = {0, 0, 0, 0};
    mma16816(s0, q, k[0], k[2]); mma16816(s1, q, k[1], k[3]);
    m0 = fmaxf(fmaxf(m0, fmaxf(s0[0], s0[1])), fmaxf(s1[0], s1[1])); m1 = fmaxf(fmaxf(m1, fmaxf(s0[2], s0[3])), fmaxf(s1[2], s1[3]));
  }
  m0 = fmaxf(m0, __shfl_xor_sync(~0u, m0, 1)); m0 = fmaxf(m0, __shfl_xor_sync(~0u, m0, 2));
  m1 = fmaxf(m1, __shfl_xor_sync(~0u, m1, 1)); m1 = fmaxf(m1, __shfl_xor_sync(~0u, m1, 2));
  float o0[4] = {0, 0, 0, 0}, o1[4] = {0, 0, 0, 0}, o2[4] = {0, 0, 0, 0};
#pragma unroll 2
  for (int i = 0; i < 128; i++) {
    uint32_t k[4], v[4]; ldsm4(ka + i * 256, k);
    asm volatile("ldmatrix.sync.aligned.m8n8.x4.trans.shared.b16 {%0,%1,%2,%3},[%4];" : "=r"(v[0]), "=r"(v[1]), "=r"(v[2]), "=r"(v[3]) : "r"(ka + 65536 + i * 256) : "memory");
    float s0[4] = {0, 0, 0, 0}, s1[4] = {0, 0, 0, 0};
    mma16816(s0, q, k[0], k[2]); mma16816(s1, q, k[1], k[3]);
    const uint32_t p[4] = {pack_rn(ex2(s0[0] - m0), ex2(s0[1] - m0)), pack_rn(ex2(s0[2] - m1), ex2(s0[3] - m1)),
                           pack_rn(ex2(s1[0] - m0), ex2(s1[1] - m0)), pack_rn(ex2(s1[2] - m1), ex2(s1[3] - m1))};
    mma16816(o0, p, v[0], v[1]); mma16816(o1, p, v[2], v[3]); mma16816(o2, p, 0x3F803F80u, 0x3F803F80u);
  }
#pragma unroll
  for (int i = 0; i < 4; i++) { o[i] = o0[i]; o[4 + i] = o1[i]; o[8 + i] = o2[i]; }
}
__global__ void __launch_bounds__(512, 1) k_attn(const bf16* wo, const bf16* w1, const bf16* w3, const bf16* w2, uint32_t kz) {
  extern __shared__ __align__(1024) uint8_t smem[];
  const uint32_t sK = smem_u32(smem), bars = sK + 5 * 32768;
  const int tid = threadIdx.x, warp = tid >> 5, lane = tid & 31, g = lane >> 2, t = lane & 3;
  const int h = blockIdx.x >> 2, qb = blockIdx.x & 3;
  TS(2, 0);
  pdl_launch();
  if (tid == 0) { for (int i = 0; i < 4; i++) mbar_init(bars + 8 * i, 1); fence_init(); }
#pragma unroll
  for (int i = 0; i < 4; i++) *(uint4*)(smem + 131072 + i * 8192 + tid * 16) = make_uint4(0x3F803F80u, 0x3F803F80u, 0x3F803F80u, 0x3F803F80u);
  fence_async();
  __syncthreads();
  pdl_wait();
  TS(2, 1);
  if (tid >= 504) g_modv[blockIdx.x * 8 + tid - 504] = 0;
  if (tid == 0) {
    for (int c = 0; c < 4; c++) {
      mbar_expect(bars + 8 * c, 32768);
      for (int pl = 0; pl < 4; pl++)
        bulk_load(sK + pl * 32768 + c * 8192, g_qkv + ((64 + (pl >> 1) * 64 + h * 2 + (pl & 1)) * 2048 + c * 512) * 8, 8192, bars + 8 * c);
    }
  }
  if (tid == 32) {
    l2_prefetch((const char*)wo + blockIdx.x * 4096, 4096);
    l2_prefetch((const char*)w1 + blockIdx.x * 11008, 11008);
    l2_prefetch((const char*)w3 + blockIdx.x * 11008, 11008);
    l2_prefetch((const char*)w2 + blockIdx.x * 11008, 11008);
  }
  const uint4 km4 = *(const uint4*)(g_kmax + h * 128 + lane * 4);
  const float kmax = __uint_as_float(__reduce_max_sync(~0u, max(max(km4.x, km4.y), max(km4.z, km4.w))));
#pragma unroll 1
  for (int tile = 0; tile < 2; tile++) {
    const int row = qb * 512 + tile * 256 + warp * 16 + g;
    const uint32_t* qp = (const uint32_t*)g_qkv + (h * 2 * 2048 + row) * 4 + t;
    uint32_t q[4] = {qp[0], qp[32], qp[8192], qp[8192 + 32]};
    const float n0 = qsum(blo(q[0]) * blo(q[0]) + bhi(q[0]) * bhi(q[0]) + blo(q[2]) * blo(q[2]) + bhi(q[2]) * bhi(q[2]));
    const float n1 = qsum(blo(q[1]) * blo(q[1]) + bhi(q[1]) * bhi(q[1]) + blo(q[3]) * blo(q[3]) + bhi(q[3]) * bhi(q[3]));
    const float b0 = sqrtf(n0 * kmax) * 1.001f, b1 = sqrtf(n1 * kmax) * 1.001f;
    const float m0 = fmaxf(ceilf(b0 - 100.f), 0.f), m1 = fmaxf(ceilf(b1 - 100.f), 0.f);
    float o[12], ob[12];
    attn_pass(o, ob, q, m0, m1, sK, bars, tile == 0, kz);
    const float f0 = ex2(-m0), f1 = ex2(-m1);
#pragma unroll
    for (int i = 0; i < 12; i++) o[i] = fmaf(o[i], (i & 2) ? f1 : f0, ob[i]);
    bool ok = b0 < 220.f && b1 < 220.f && o[8] >= 0x1p-90f && o[10] >= 0x1p-90f;
#pragma unroll
    for (int i = 0; i < 12; i++) ok = ok && fabsf(o[i]) < INFINITY;
    if (!__all_sync(~0u, ok)) attn_safe(o, q, sK);
    const float r0 = 1.f / o[8], r1 = 1.f / o[10];
    uint32_t* op = (uint32_t*)g_o + (((row >> 7) * 64 + h * 2) * 128 + (row & 127)) * 4 + t;
    op[0] = pack_rn(o[0] * r0, o[1] * r0); op[32] = pack_rn(o[2] * r1, o[3] * r1);
    op[512] = pack_rn(o[4] * r0, o[5] * r0); op[512 + 32] = pack_rn(o[6] * r1, o[7] * r1);
    TS(2, 3 + tile);
  }
}

constexpr int WO_SMEM = 131072 + 65536 + 256;
__global__ void __launch_bounds__(256, 1) k_wo(const __grid_constant__ CUtensorMap mW, const bf16* __restrict__ x) {
  extern __shared__ __align__(1024) uint8_t smem[];
  const uint32_t sA = smem_u32(smem), sB = sA + 131072, bars = sB + 65536;
  const int tid = threadIdx.x, warp = tid >> 5, lane = tid & 31, g = lane >> 2, t = lane & 3;
  const int rb = blockIdx.x >> 3, ct = blockIdx.x & 7;
  TS(3, 0);
  pdl_launch();
  if (tid == 0) {
    for (int i = 0; i < 8; i++) mbar_init(bars + 8 * i, 1);
    fence_init();
    for (int i = 0; i < 8; i++) { mbar_expect(bars + 8 * i, 24576); tma2d(sB + i * 8192, &mW, ct * 64, i * 64, bars + 8 * i); }
  }
  const int lrow = warp * 16 + g;
  uint32_t xr[16];
  const uint32_t* xp = (const uint32_t*)(x + (rb * 128 + lrow) * 512 + ct * 64) + t;
#pragma unroll
  for (int j = 0; j < 8; j++) { xr[2 * j] = __ldg(xp + j * 4); xr[2 * j + 1] = __ldg(xp + j * 4 + 8 * 256); }
  __syncthreads();
  pdl_wait();
  TS(3, 1);
  if (tid == 0) for (int i = 0; i < 8; i++) bulk_load(sA + i * 16384, g_o + (rb * 64 + i * 8) * 1024, 16384, bars + 8 * i);
  float2 ga[8];
#pragma unroll
  for (int j = 0; j < 8; j++) ga[j] = *(const float2*)(g_mod + 1024 + ct * 64 + j * 8 + t * 2);
  float acc[32];
  const uint64_t da = mk_desc(sA + (warp >> 2) * 1024, 2048, 128, 0), db = mk_desc(sB, 8192, 1024, 1);
#pragma unroll
  for (int c = 0; c < 8; c++) {
    mbar_wait(bars + 8 * c, 0);
    if (c == 0) TS(3, 2);
    wg_fence();
#pragma unroll
    for (int k = 0; k < 4; k++) wgmma_ss_n64_t1(acc, da + (c * 4 + k) * 256, db + (c * 4 + k) * 128, c + k);
    wg_commit();
  }
  wg_wait<0>();
  reg_fence(acc);
  TS(3, 3);
  uint32_t* o = (uint32_t*)g_x1 + ((rb * 64 + ct * 8) * 128 + lrow) * 4 + t;
  float s0 = 0, s1 = 0;
#pragma unroll
  for (int j = 0; j < 8; j++) {
    xr[2 * j] = pack_rn(fmaf(ga[j].x, acc[4 * j], blo(xr[2 * j])), fmaf(ga[j].y, acc[4 * j + 1], bhi(xr[2 * j])));
    xr[2 * j + 1] = pack_rn(fmaf(ga[j].x, acc[4 * j + 2], blo(xr[2 * j + 1])), fmaf(ga[j].y, acc[4 * j + 3], bhi(xr[2 * j + 1])));
    o[j * 512] = xr[2 * j]; o[j * 512 + 32] = xr[2 * j + 1];
    s0 += blo(xr[2 * j]) + bhi(xr[2 * j]); s1 += blo(xr[2 * j + 1]) + bhi(xr[2 * j + 1]);
  }
  const float m0 = qsum(s0) * (1.f / 64), m1 = qsum(s1) * (1.f / 64);
  float v0 = 0, v1 = 0;
#pragma unroll
  for (int j = 0; j < 8; j++) {
    float d;
    d = blo(xr[2 * j]) - m0; v0 += d * d; d = bhi(xr[2 * j]) - m0; v0 += d * d;
    d = blo(xr[2 * j + 1]) - m1; v1 += d * d; d = bhi(xr[2 * j + 1]) - m1; v1 += d * d;
  }
  v0 = qsum(v0); v1 = qsum(v1);
  if (t == 0) g_st[(rb * 128 + lrow) * 8 + ct] = make_float2(m0, v0);
  if (t == 1) g_st[(rb * 128 + lrow + 8) * 8 + ct] = make_float2(m1, v1);
  TS(3, 4);
}

constexpr int W2_SMEM = 6 * 32768 + 32768 + 256;
__global__ void __cluster_dims__(2, 1, 1) __launch_bounds__(288, 1) k_w2(const __grid_constant__ CUtensorMap mW, bf16* __restrict__ out) {
  extern __shared__ __align__(1024) uint8_t smem[];
  const uint32_t sR = smem_u32(smem), sX = sR + 6 * 32768, bF = sX + 32768, bE = bF + 48;
  const int tid = threadIdx.x, warp = tid >> 5, lane = tid & 31, g = lane >> 2, t = lane & 3;
  const int kh = blockIdx.x & 1, ct = (blockIdx.x >> 1) & 3, rb = blockIdx.x >> 3;
  TS(5, 0);
  pdl_launch();
  if (tid == 256) {
    for (int i = 0; i < 6; i++) { mbar_init(bF + 8 * i, 1); mbar_init(bE + 8 * i, 8); }
    fence_init();
  }
  __syncthreads();
  asm volatile("barrier.cluster.arrive.relaxed.aligned;" ::: "memory");
  if (warp == 8) {
    if (lane == 0) {
      auto abytes = [&](int s) { return (kh == 1 && s == 10) ? 8192 : 16384; };
      auto loadB = [&](int s) {
        const int st = s % 6;
        mbar_expect(bF + 8 * st, 16384 + abytes(s));
        for (int j = 0; j < 2; j++) tma2d(sR + st * 32768 + 16384 + j * 8192, &mW, ct * 128 + j * 64, kh * 704 + s * 64, bF + 8 * st);
      };
      auto loadA = [&](int s) { bulk_load(sR + (s % 6) * 32768, g_h + (rb * 172 + kh * 88 + s * 8) * 1024, abytes(s), bF + 8 * (s % 6)); };
      for (int s = 0; s < 6; s++) loadB(s);
      pdl_wait();
      for (int s = 0; s < 6; s++) loadA(s);
      for (int s = 6; s < 11; s++) { mbar_wait(bE + 8 * (s - 6), 0); loadB(s); loadA(s); }
    }
    __syncwarp();
    asm volatile("barrier.cluster.wait.aligned;" ::: "memory");
    asm volatile("barrier.cluster.arrive.release.aligned;" ::: "memory");
    asm volatile("barrier.cluster.wait.acquire.aligned;" ::: "memory");
    return;
  }
  pdl_wait();
  TS(5, 1);
  const int lrow = warp * 16 + g;
  uint32_t xr[16];
  float2 gb[8];
  const uint32_t* xp = (const uint32_t*)g_x1 + ((rb * 64 + ct * 16 + kh * 8) * 128 + lrow) * 4 + t;
#pragma unroll
  for (int j = 0; j < 8; j++) {
    xr[2 * j] = xp[j * 512]; xr[2 * j + 1] = xp[j * 512 + 32];
    gb[j] = *(const float2*)(g_mod + 2560 + ct * 128 + kh * 64 + j * 8 + t * 2);
  }
  float acc[64];
#pragma unroll 1
  for (int s = 0; s < 11; s++) {
    const int st = s % 6;
    mbar_wait(bF + 8 * st, s >= 6);
    const uint64_t da = mk_desc(sR + st * 32768 + (warp >> 2) * 1024, 2048, 128, 0), db = mk_desc(sR + st * 32768 + 16384, 8192, 1024, 1);
    if (s == 0) TS(5, 2);
    wg_fence();
    wgmma_ss_n128_t1(acc, da, db, s);
    wgmma_ss_n128_t1(acc, da + 256, db + 128, 1);
    wgmma_ss_n128_t1(acc, da + 512, db + 256, 1);
    wgmma_ss_n128_t1(acc, da + 768, db + 384, 1);
    wg_commit();
    wg_wait<1>();
    if (s > 0 && s < 6 && lane == 0) mbar_arrive(bE + 8 * (s - 1));
  }
  wg_wait<0>();
  reg_fence(acc);
  TS(5, 3);
  asm volatile("barrier.cluster.wait.aligned;" ::: "memory");
  uint32_t rem;
  asm("mapa.shared::cluster.u32 %0,%1,%2;" : "=r"(rem) : "r"(sX + tid * 16), "r"(kh ^ 1));
#pragma unroll
  for (int j = 0; j < 8; j++) {
    float v[4];
#pragma unroll
    for (int i = 0; i < 4; i++) { v[i] = kh ? acc[4 * j + i] : acc[32 + 4 * j + i]; acc[4 * j + i] = kh ? acc[32 + 4 * j + i] : acc[4 * j + i]; }
    asm volatile("st.shared::cluster.v4.f32 [%0],{%1,%2,%3,%4};" ::"r"(rem + j * 4096), "f"(v[0]), "f"(v[1]), "f"(v[2]), "f"(v[3]) : "memory");
  }
  asm volatile("barrier.cluster.arrive.release.aligned;" ::: "memory");
  asm volatile("barrier.cluster.wait.acquire.aligned;" ::: "memory");
  uint32_t* o = (uint32_t*)(out + (rb * 128 + lrow) * 512 + ct * 128 + kh * 64) + t;
#pragma unroll
  for (int j = 0; j < 8; j++) {
    const float4 p = *(const float4*)(smem + 6 * 32768 + j * 4096 + tid * 16);
    o[j * 4] = pack_rn(fmaf(gb[j].x, acc[4 * j] + p.x, blo(xr[2 * j])), fmaf(gb[j].y, acc[4 * j + 1] + p.y, bhi(xr[2 * j])));
    o[j * 4 + 2048] = pack_rn(fmaf(gb[j].x, acc[4 * j + 2] + p.z, blo(xr[2 * j + 1])), fmaf(gb[j].y, acc[4 * j + 3] + p.w, bhi(xr[2 * j + 1])));
  }
  TS(5, 4);
}

typedef CUresult (*EncFn)(CUtensorMap*, CUtensorMapDataType, cuuint32_t, void*, const cuuint64_t*, const cuuint64_t*, const cuuint32_t*,
                          const cuuint32_t*, CUtensorMapInterleave, CUtensorMapSwizzle, CUtensorMapL2promotion, CUtensorMapFloatOOBfill);
static void mk_map(EncFn f, CUtensorMap* m, const void* p, int rows, int cols, int box_rows) {
  cuuint64_t dim[2] = {(cuuint64_t)cols, (cuuint64_t)rows}, str[1] = {(cuuint64_t)cols * 2};
  cuuint32_t box[2] = {64, (cuuint32_t)box_rows}, es[2] = {1, 1};
  f(m, CU_TENSOR_MAP_DATA_TYPE_BFLOAT16, 2, (void*)p, dim, str, box, es, CU_TENSOR_MAP_INTERLEAVE_NONE, CU_TENSOR_MAP_SWIZZLE_128B,
    CU_TENSOR_MAP_L2_PROMOTION_L2_128B, CU_TENSOR_MAP_FLOAT_OOB_FILL_NONE);
}
template <typename... KA, typename... A>
static void launch(void (*k)(KA...), int grid, int block, int smem, bool pdl, A... args) {
  cudaLaunchConfig_t cfg = {};
  cfg.gridDim = dim3(grid); cfg.blockDim = dim3(block); cfg.dynamicSmemBytes = smem; cfg.stream = cudaStreamPerThread;
  cudaLaunchAttribute at[1];
  at[0].id = cudaLaunchAttributeProgrammaticStreamSerialization; at[0].val.programmaticStreamSerializationAllowed = 1;
  cfg.attrs = at; cfg.numAttrs = pdl ? 1 : 0;
  cudaLaunchKernelEx(&cfg, k, args...);
}
extern "C" void kernel_launch(void* const* d_in, const int* in_sizes, int n_in, void* d_out, int out_size) {
  const bf16 *x = (const bf16*)d_in[0], *wqkv = (const bf16*)d_in[1], *wo = (const bf16*)d_in[2], *w1 = (const bf16*)d_in[4],
             *w3 = (const bf16*)d_in[5], *w2 = (const bf16*)d_in[6], *c = (const bf16*)d_in[7], *wmod = (const bf16*)d_in[8];
  void* fp = nullptr;
  cudaDriverEntryPointQueryResult qr;
  cudaGetDriverEntryPoint("cuTensorMapEncodeTiled", &fp, cudaEnableDefault, &qr);
  EncFn f = (EncFn)fp;
  CUtensorMap mX, mQ, mO, m1, m3, m2;
  mk_map(f, &mX, x, S_, D_, 128); mk_map(f, &mQ, wqkv, D_, 3 * D_, 64); mk_map(f, &mO, wo, D_, D_, 64);
  mk_map(f, &m1, w1, D_, F_, 32); mk_map(f, &m3, w3, D_, F_, 32); mk_map(f, &m2, w2, F_, D_, 64);
  cudaFuncSetAttribute(k_lngemm<false>, cudaFuncAttributeMaxDynamicSharedMemorySize, LN_SMEM);
  cudaFuncSetAttribute(k_lngemm<true>, cudaFuncAttributeMaxDynamicSharedMemorySize, LN_SMEM);
  cudaFuncSetAttribute(k_attn, cudaFuncAttributeMaxDynamicSharedMemorySize, AT_SMEM);
  cudaFuncSetAttribute(k_wo, cudaFuncAttributeMaxDynamicSharedMemorySize, WO_SMEM);
  cudaFuncSetAttribute(k_w2, cudaFuncAttributeMaxDynamicSharedMemorySize, W2_SMEM);
  launch(k_lngemm<false>, 128, 384, LN_SMEM, false, mX, mQ, mQ, c, wmod);
  launch(k_attn, 128, 512, AT_SMEM, true, wo, w1, w3, w2, 0u);
  launch(k_wo, 128, 256, WO_SMEM, true, mO, x);
  launch(k_lngemm<true>, 128, 384, LN_SMEM, true, mX, m1, m3, c, wmod);
  launch(k_w2, 128, 288, W2_SMEM, true, m2, (bf16*)d_out);
}
```

```cpp
#include <cuda_runtime.h>
#include <cuda_bf16.h>
#include <cuda.h>
#include <stdint.h>
typedef __nv_bfloat16 bf16;
constexpr int S_ = 2048, D_ = 512, F_ = 1376;
__device__ __align__(1024) float g_mod[3072];
__device__ __align__(1024) uint32_t g_modv[1024 + 4096];
__device__ __align__(1024) bf16 g_qkv[192 * 2048 * 8];
__device__ __align__(1024) float g_kmax[32 * 128];
__device__ __align__(1024) bf16 g_o[16 * 64 * 128 * 8];
__device__ __align__(1024) bf16 g_x1[16 * 64 * 128 * 8];
__device__ __align__(1024) float2 g_st[2048 * 8];
__device__ __align__(1024) bf16 g_h[16 * 172 * 128 * 8];

__device__ __forceinline__ uint32_t smem_u32(const void* p) { return (uint32_t)__cvta_generic_to_shared(p); }
__device__ __forceinline__ void mbar_init(uint32_t b, int n) { asm volatile("mbarrier.init.shared::cta.b64 [%0],%1;" ::"r"(b), "r"(n) : "memory"); }
__device__ __forceinline__ void mbar_expect(uint32_t b, int bytes) { asm volatile("mbarrier.arrive.expect_tx.shared::cta.b64 _,[%0],%1;" ::"r"(b), "r"(bytes) : "memory"); }
__device__ __forceinline__ void mbar_arrive(uint32_t b) { asm volatile("mbarrier.arrive.shared::cta.b64 _,[%0];" ::"r"(b) : "memory"); }
__device__ __forceinline__ void mbar_wait(uint32_t b, int parity) {
  asm volatile("{\n.reg .pred p;\n.reg .u32 n;\nmov.u32 n,0;\nLW:\nmbarrier.try_wait.parity.shared::cta.b64 p,[%0],%1;\n@p bra LD;\n"
               "add.u32 n,n,1;\nsetp.lt.u32 p,n,4194304;\n@p bra LW;\nLD:\n}\n" ::"r"(b), "r"(parity) : "memory");
}
__device__ __forceinline__ void fence_init() { asm volatile("fence.mbarrier_init.release.cluster;" ::: "memory"); }
__device__ __forceinline__ void fence_async() { asm volatile("fence.proxy.async.shared::cta;" ::: "memory"); }
__device__ __forceinline__ void bulk_load(uint32_t dst, const void* src, int bytes, uint32_t bar) {
  asm volatile("cp.async.bulk.shared::cluster.global.mbarrier::complete_tx::bytes [%0],[%1],%2,[%3];" ::"r"(dst), "l"(src), "r"(bytes), "r"(bar) : "memory");
}
__device__ __forceinline__ void tma2d(uint32_t dst, const CUtensorMap* m, int c0, int c1, uint32_t bar) {
  asm volatile("cp.async.bulk.tensor.2d.shared::cluster.global.mbarrier::complete_tx::bytes [%0],[%1,{%3,%4}],[%2];" ::"r"(dst), "l"(m), "r"(bar), "r"(c0), "r"(c1) : "memory");
}
__device__ __forceinline__ void bulk_load_mc(uint32_t dst, const void* src, int bytes, uint32_t bar) {
  asm volatile("cp.async.bulk.shared::cluster.global.mbarrier::complete_tx::bytes.multicast::cluster [%0],[%1],%2,[%3],%4;" ::"r"(dst), "l"(src), "r"(bytes), "r"(bar), "h"((uint16_t)3) : "memory");
}
__device__ __forceinline__ void tma2d_mc(uint32_t dst, const CUtensorMap* m, int c0, int c1, uint32_t bar) {
  asm volatile("cp.async.bulk.tensor.2d.shared::cluster.global.mbarrier::complete_tx::bytes.multicast::cluster [%0],[%1,{%3,%4}],[%2],%5;" ::"r"(dst), "l"(m), "r"(bar), "r"(c0), "r"(c1), "h"((uint16_t)3) : "memory");
}
__device__ __forceinline__ void cluster_sync() { asm volatile("barrier.cluster.arrive.release.aligned;\nbarrier.cluster.wait.acquire.aligned;" ::: "memory"); }
__device__ __forceinline__ void l2_prefetch(const void* p, int bytes) { asm volatile("cp.async.bulk.prefetch.L2.global [%0],%1;" ::"l"(p), "r"(bytes) : "memory"); }
__device__ __forceinline__ void pdl_launch() { asm volatile("griddepcontrol.launch_dependents;" ::: "memory"); }
__device__ __forceinline__ void pdl_wait() { asm volatile("griddepcontrol.wait;" ::: "memory"); }
__device__ __forceinline__ void wg_fence() { asm volatile("wgmma.fence.sync.aligned;" ::: "memory"); }
__device__ __forceinline__ void wg_commit() { asm volatile("wgmma.commit_group.sync.aligned;" ::: "memory"); }
template <int N> __device__ __forceinline__ void wg_wait() { asm volatile("wgmma.wait_group.sync.aligned %0;" ::"n"(N) : "memory"); }
template <int N> __device__ __forceinline__ void reg_fence(float (&d)[N]) {
#pragma unroll
  for (int i = 0; i < N; i++) asm volatile("" : "+f"(d[i])::"memory");
}
template <int N> __device__ __forceinline__ void zero(float (&d)[N]) {
#pragma unroll
  for (int i = 0; i < N; i++) d[i] = 0.f;
  reg_fence(d);
}
__device__ __forceinline__ uint64_t mk_desc(uint32_t addr, uint32_t lbo, uint32_t sbo, uint32_t mode) {
  return (uint64_t)((addr >> 4) & 0x3FFF) | ((uint64_t)(lbo >> 4) << 16) | ((uint64_t)(sbo >> 4) << 32) | ((uint64_t)mode << 62);
}
__device__ __forceinline__ void ldsm4(uint32_t a, uint32_t (&r)[4]) {
  asm volatile("ldmatrix.sync.aligned.m8n8.x4.shared.b16 {%0,%1,%2,%3},[%4];" : "=r"(r[0]), "=r"(r[1]), "=r"(r[2]), "=r"(r[3]) : "r"(a) : "memory");
}
__device__ __forceinline__ uint32_t pack_rn(float lo, float hi) { uint32_t r; asm("cvt.rn.bf16x2.f32 %0,%1,%2;" : "=r"(r) : "f"(hi), "f"(lo)); return r; }
__device__ __forceinline__ uint32_t pack_rz(float lo, float hi) { uint32_t r; asm("cvt.rz.bf16x2.f32 %0,%1,%2;" : "=r"(r) : "f"(hi), "f"(lo)); return r; }
__device__ __forceinline__ float blo(uint32_t u) { return __uint_as_float(u << 16); }
__device__ __forceinline__ float bhi(uint32_t u) { return __uint_as_float(u & 0xFFFF0000u); }
__device__ __forceinline__ float rbf(float x) { return __bfloat162float(__float2bfloat16_rn(x)); }
__device__ __forceinline__ float qsum(float v) { v += __shfl_xor_sync(~0u, v, 1); return v + __shfl_xor_sync(~0u, v, 2); }
__device__ __forceinline__ float ex2(float x) { float r; asm("ex2.approx.ftz.f32 %0,%1;" : "=f"(r) : "f"(x)); return r; }
#define TS(k, i)
__device__ __forceinline__ void wgmma_rs_n176_t1(float (&d)[88],uint32_t a0,uint32_t a1,uint32_t a2,uint32_t a3,uint64_t db,int sc){
  asm volatile("{\n.reg .pred p;\nsetp.ne.b32 p,%93,0;\n"
    "wgmma.mma_async.sync.aligned.m64n176k16.f32.bf16.bf16 {%0,%1,%2,%3,%4,%5,%6,%7,%8,%9,%10,%11,%12,%13,%14,%15,%16,%17,%18,%19,%20,%21,%22,%23,%24,%25,%26,%27,%28,%29,%30,%31,%32,%33,%34,%35,%36,%37,%38,%39,%40,%41,%42,%43,%44,%45,%46,%47,%48,%49,%50,%51,%52,%53,%54,%55,%56,%57,%58,%59,%60,%61,%62,%63,%64,%65,%66,%67,%68,%69,%70,%71,%72,%73,%74,%75,%76,%77,%78,%79,%80,%81,%82,%83,%84,%85,%86,%87},{%88,%89,%90,%91},%92,p,1,1,1;\n}\n"
    :"+f"(d[0]),"+f"(d[1]),"+f"(d[2]),"+f"(d[3]),"+f"(d[4]),"+f"(d[5]),"+f"(d[6]),"+f"(d[7]),"+f"(d[8]),"+f"(d[9]),"+f"(d[10]),"+f"(d[11]),"+f"(d[12]),"+f"(d[13]),"+f"(d[14]),"+f"(d[15]),"+f"(d[16]),"+f"(d[17]),"+f"(d[18]),"+f"(d[19]),"+f"(d[20]),"+f"(d[21]),"+f"(d[22]),"+f"(d[23]),"+f"(d[24]),"+f"(d[25]),"+f"(d[26]),"+f"(d[27]),"+f"(d[28]),"+f"(d[29]),"+f"(d[30]),"+f"(d[31]),"+f"(d[32]),"+f"(d[33]),"+f"(d[34]),"+f"(d[35]),"+f"(d[36]),"+f"(d[37]),"+f"(d[38]),"+f"(d[39]),"+f"(d[40]),"+f"(d[41]),"+f"(d[42]),"+f"(d[43]),"+f"(d[44]),"+f"(d[45]),"+f"(d[46]),"+f"(d[47]),"+f"(d[48]),"+f"(d[49]),"+f"(d[50]),"+f"(d[51]),"+f"(d[52]),"+f"(d[53]),"+f"(d[54]),"+f"(d[55]),"+f"(d[56]),"+f"(d[57]),"+f"(d[58]),"+f"(d[59]),"+f"(d[60]),"+f"(d[61]),"+f"(d[62]),"+f"(d[63]),"+f"(d[64]),"+f"(d[65]),"+f"(d[66]),"+f"(d[67]),"+f"(d[68]),"+f"(d[69]),"+f"(d[70]),"+f"(d[71]),"+f"(d[72]),"+f"(d[73]),"+f"(d[74]),"+f"(d[75]),"+f"(d[76]),"+f"(d[77]),"+f"(d[78]),"+f"(d[79]),"+f"(d[80]),"+f"(d[81]),"+f"(d[82]),"+f"(d[83]),"+f"(d[84]),"+f"(d[85]),"+f"(d[86]),"+f"(d[87])
    :"r"(a0),"r"(a1),"r"(a2),"r"(a3),"l"(db),"r"(sc));
}
__device__ __forceinline__ void wgmma_rs_n192_t1(float (&d)[96],uint32_t a0,uint32_t a1,uint32_t a2,uint32_t a3,uint64_t db,int sc){
  asm volatile("{\n.reg .pred p;\nsetp.ne.b32 p,%101,0;\n"
    "wgmma.mma_async.sync.aligned.m64n192k16.f32.bf16.bf16 {%0,%1,%2,%3,%4,%5,%6,%7,%8,%9,%10,%11,%12,%13,%14,%15,%16,%17,%18,%19,%20,%21,%22,%23,%24,%25,%26,%27,%28,%29,%30,%31,%32,%33,%34,%35,%36,%37,%38,%39,%40,%41,%42,%43,%44,%45,%46,%47,%48,%49,%50,%51,%52,%53,%54,%55,%56,%57,%58,%59,%60,%61,%62,%63,%64,%65,%66,%67,%68,%69,%70,%71,%72,%73,%74,%75,%76,%77,%78,%79,%80,%81,%82,%83,%84,%85,%86,%87,%88,%89,%90,%91,%92,%93,%94,%95},{%96,%97,%98,%99},%100,p,1,1,1;\n}\n"
    :"+f"(d[0]),"+f"(d[1]),"+f"(d[2]),"+f"(d[3]),"+f"(d[4]),"+f"(d[5]),"+f"(d[6]),"+f"(d[7]),"+f"(d[8]),"+f"(d[9]),"+f"(d[10]),"+f"(d[11]),"+f"(d[12]),"+f"(d[13]),"+f"(d[14]),"+f"(d[15]),"+f"(d[16]),"+f"(d[17]),"+f"(d[18]),"+f"(d[19]),"+f"(d[20]),"+f"(d[21]),"+f"(d[22]),"+f"(d[23]),"+f"(d[24]),"+f"(d[25]),"+f"(d[26]),"+f"(d[27]),"+f"(d[28]),"+f"(d[29]),"+f"(d[30]),"+f"(d[31]),"+f"(d[32]),"+f"(d[33]),"+f"(d[34]),"+f"(d[35]),"+f"(d[36]),"+f"(d[37]),"+f"(d[38]),"+f"(d[39]),"+f"(d[40]),"+f"(d[41]),"+f"(d[42]),"+f"(d[43]),"+f"(d[44]),"+f"(d[45]),"+f"(d[46]),"+f"(d[47]),"+f"(d[48]),"+f"(d[49]),"+f"(d[50]),"+f"(d[51]),"+f"(d[52]),"+f"(d[53]),"+f"(d[54]),"+f"(d[55]),"+f"(d[56]),"+f"(d[57]),"+f"(d[58]),"+f"(d[59]),"+f"(d[60]),"+f"(d[61]),"+f"(d[62]),"+f"(d[63]),"+f"(d[64]),"+f"(d[65]),"+f"(d[66]),"+f"(d[67]),"+f"(d[68]),"+f"(d[69]),"+f"(d[70]),"+f"(d[71]),"+f"(d[72]),"+f"(d[73]),"+f"(d[74]),"+f"(d[75]),"+f"(d[76]),"+f"(d[77]),"+f"(d[78]),"+f"(d[79]),"+f"(d[80]),"+f"(d[81]),"+f"(d[82]),"+f"(d[83]),"+f"(d[84]),"+f"(d[85]),"+f"(d[86]),"+f"(d[87]),"+f"(d[88]),"+f"(d[89]),"+f"(d[90]),"+f"(d[91]),"+f"(d[92]),"+f"(d[93]),"+f"(d[94]),"+f"(d[95])
    :"r"(a0),"r"(a1),"r"(a2),"r"(a3),"l"(db),"r"(sc));
}
__device__ __forceinline__ void wgmma_rs_n24_t1(float (&d)[12],uint32_t a0,uint32_t a1,uint32_t a2,uint32_t a3,uint64_t db,int sc){
  asm volatile("{\n.reg .pred p;\nsetp.ne.b32 p,%17,0;\n"
    "wgmma.mma_async.sync.aligned.m64n24k16.f32.bf16.bf16 {%0,%1,%2,%3,%4,%5,%6,%7,%8,%9,%10,%11},{%12,%13,%14,%15},%16,p,1,1,1;\n}\n"
    :"+f"(d[0]),"+f"(d[1]),"+f"(d[2]),"+f"(d[3]),"+f"(d[4]),"+f"(d[5]),"+f"(d[6]),"+f"(d[7]),"+f"(d[8]),"+f"(d[9]),"+f"(d[10]),"+f"(d[11])
    :"r"(a0),"r"(a1),"r"(a2),"r"(a3),"l"(db),"r"(sc));
}
__device__ __forceinline__ void wgmma_rs_n64_t0(float (&d)[32],uint32_t a0,uint32_t a1,uint32_t a2,uint32_t a3,uint64_t db,int sc){
  asm volatile("{\n.reg .pred p;\nsetp.ne.b32 p,%37,0;\n"
    "wgmma.mma_async.sync.aligned.m64n64k16.f32.bf16.bf16 {%0,%1,%2,%3,%4,%5,%6,%7,%8,%9,%10,%11,%12,%13,%14,%15,%16,%17,%18,%19,%20,%21,%22,%23,%24,%25,%26,%27,%28,%29,%30,%31},{%32,%33,%34,%35},%36,p,1,1,0;\n}\n"
    :"+f"(d[0]),"+f"(d[1]),"+f"(d[2]),"+f"(d[3]),"+f"(d[4]),"+f"(d[5]),"+f"(d[6]),"+f"(d[7]),"+f"(d[8]),"+f"(d[9]),"+f"(d[10]),"+f"(d[11]),"+f"(d[12]),"+f"(d[13]),"+f"(d[14]),"+f"(d[15]),"+f"(d[16]),"+f"(d[17]),"+f"(d[18]),"+f"(d[19]),"+f"(d[20]),"+f"(d[21]),"+f"(d[22]),"+f"(d[23]),"+f"(d[24]),"+f"(d[25]),"+f"(d[26]),"+f"(d[27]),"+f"(d[28]),"+f"(d[29]),"+f"(d[30]),"+f"(d[31])
    :"r"(a0),"r"(a1),"r"(a2),"r"(a3),"l"(db),"r"(sc));
}
__device__ __forceinline__ void wgmma_ss_n128_t1(float (&d)[64],uint64_t da,uint64_t db,int sc){
  asm volatile("{\n.reg .pred p;\nsetp.ne.b32 p,%66,0;\n"
    "wgmma.mma_async.sync.aligned.m64n128k16.f32.bf16.bf16 {%0,%1,%2,%3,%4,%5,%6,%7,%8,%9,%10,%11,%12,%13,%14,%15,%16,%17,%18,%19,%20,%21,%22,%23,%24,%25,%26,%27,%28,%29,%30,%31,%32,%33,%34,%35,%36,%37,%38,%39,%40,%41,%42,%43,%44,%45,%46,%47,%48,%49,%50,%51,%52,%53,%54,%55,%56,%57,%58,%59,%60,%61,%62,%63},%64,%65,p,1,1,0,1;\n}\n"
    :"+f"(d[0]),"+f"(d[1]),"+f"(d[2]),"+f"(d[3]),"+f"(d[4]),"+f"(d[5]),"+f"(d[6]),"+f"(d[7]),"+f"(d[8]),"+f"(d[9]),"+f"(d[10]),"+f"(d[11]),"+f"(d[12]),"+f"(d[13]),"+f"(d[14]),"+f"(d[15]),"+f"(d[16]),"+f"(d[17]),"+f"(d[18]),"+f"(d[19]),"+f"(d[20]),"+f"(d[21]),"+f"(d[22]),"+f"(d[23]),"+f"(d[24]),"+f"(d[25]),"+f"(d[26]),"+f"(d[27]),"+f"(d[28]),"+f"(d[29]),"+f"(d[30]),"+f"(d[31]),"+f"(d[32]),"+f"(d[33]),"+f"(d[34]),"+f"(d[35]),"+f"(d[36]),"+f"(d[37]),"+f"(d[38]),"+f"(d[39]),"+f"(d[40]),"+f"(d[41]),"+f"(d[42]),"+f"(d[43]),"+f"(d[44]),"+f"(d[45]),"+f"(d[46]),"+f"(d[47]),"+f"(d[48]),"+f"(d[49]),"+f"(d[50]),"+f"(d[51]),"+f"(d[52]),"+f"(d[53]),"+f"(d[54]),"+f"(d[55]),"+f"(d[56]),"+f"(d[57]),"+f"(d[58]),"+f"(d[59]),"+f"(d[60]),"+f"(d[61]),"+f"(d[62]),"+f"(d[63])
    :"l"(da),"l"(db),"r"(sc));
}
__device__ __forceinline__ void wgmma_ss_n64_t1(float (&d)[32],uint64_t da,uint64_t db,int sc){
  asm volatile("{\n.reg .pred p;\nsetp.ne.b32 p,%34,0;\n"
    "wgmma.mma_async.sync.aligned.m64n64k16.f32.bf16.bf16 {%0,%1,%2,%3,%4,%5,%6,%7,%8,%9,%10,%11,%12,%13,%14,%15,%16,%17,%18,%19,%20,%21,%22,%23,%24,%25,%26,%27,%28,%29,%30,%31},%32,%33,p,1,1,0,1;\n}\n"
    :"+f"(d[0]),"+f"(d[1]),"+f"(d[2]),"+f"(d[3]),"+f"(d[4]),"+f"(d[5]),"+f"(d[6]),"+f"(d[7]),"+f"(d[8]),"+f"(d[9]),"+f"(d[10]),"+f"(d[11]),"+f"(d[12]),"+f"(d[13]),"+f"(d[14]),"+f"(d[15]),"+f"(d[16]),"+f"(d[17]),"+f"(d[18]),"+f"(d[19]),"+f"(d[20]),"+f"(d[21]),"+f"(d[22]),"+f"(d[23]),"+f"(d[24]),"+f"(d[25]),"+f"(d[26]),"+f"(d[27]),"+f"(d[28]),"+f"(d[29]),"+f"(d[30]),"+f"(d[31])
    :"l"(da),"l"(db),"r"(sc));
}

__device__ __forceinline__ float silu_bf(bf16 c) { const float x = __bfloat162float(c); return rbf(x / (1.f + __expf(-x))); }
__device__ __forceinline__ void fma8(float (&a)[8], float s, const uint4& v) {
  a[0] += s * blo(v.x); a[1] += s * bhi(v.x); a[2] += s * blo(v.y); a[3] += s * bhi(v.y);
  a[4] += s * blo(v.z); a[5] += s * bhi(v.z); a[6] += s * blo(v.w); a[7] += s * bhi(v.w);
}
__device__ __forceinline__ float red8(float (&a)[8], int lane) {
#pragma unroll
  for (int w = 4; w >= 1; w >>= 1) {
    const bool up = lane & (w * 4);
#pragma unroll
    for (int j = 0; j < w; j++) a[j] = (up ? a[j + w] : a[j]) + __shfl_xor_sync(~0u, up ? a[j] : a[j + w], w * 4);
  }
  return a[0];
}
__device__ __forceinline__ float mod_fin(float s, int n) { s = rbf(s); return ((n >> 9) == 1 || (n >> 9) == 4) ? rbf(1.f + s) : s; }
__device__ __forceinline__ uint2 poll2(const uint32_t* p) {
  uint2 v;
  asm volatile("{\n.reg .pred p;\n.reg .u32 n,t;\nmov.u32 n,0;\nLW:\nld.relaxed.gpu.global.v2.u32 {%0,%1},[%2];\nand.b32 t,%0,%1;\nand.b32 t,t,1;\n"
               "setp.ne.u32 p,t,0;\n@p bra LD;\nadd.u32 n,n,1;\nsetp.lt.u32 p,n,1048576;\n@p bra LW;\nLD:\n}\n" : "=r"(v.x), "=r"(v.y) : "l"(p) : "memory");
  return v;
}

constexpr int LN_SMEM = 131072 + 4 * 24576 + 2048 + 256 + 512;
template <bool FFN>
__global__ void __cluster_dims__(2, 1, 1) __launch_bounds__(384, 1) k_lngemm(const __grid_constant__ CUtensorMap mX, const __grid_constant__ CUtensorMap mB0,
                                                   const __grid_constant__ CUtensorMap mB1, const bf16* __restrict__ cv, const bf16* __restrict__ wm, const bf16* __restrict__ xg) {
  extern __shared__ __align__(1024) uint8_t smem[];
  const uint32_t sA = smem_u32(smem), sB = sA + 131072, sM = sB + 4 * 24576, bars = sM + 2048;
  const uint32_t bA = bars, bF = bars + 64, bE = bars + 96;
  const int tid = threadIdx.x, warp = tid >> 5, lane = tid & 31;
  const int rb = blockIdx.x >> 3, ct = blockIdx.x & 7;
  constexpr int NST = FFN ? 16 : 8, KS = FFN ? 2 : 4, BOX = FFN ? 4096 : 8192;
  TS(FFN ? 4 : 1, 0);
  pdl_launch();
  float* red = (float*)(smem + (bars - sA) + 256);
  uint4 wv0, wv1, xv[4];
  bf16 cv0, cv1;
  if (!FFN && tid < 256) {
    wv0 = __ldg((const uint4*)(wm + tid * 3072 + blockIdx.x * 8)); wv1 = __ldg((const uint4*)(wm + (tid + 256) * 3072 + blockIdx.x * 8));
    cv0 = cv[tid]; cv1 = cv[tid + 256];
#pragma unroll
    for (int i = 0; i < 4; i++) xv[i] = __ldg((const uint4*)(xg + (blockIdx.x * 16 + (tid >> 4)) * 512 + i * 128 + (tid & 15) * 8));
  }
  if (tid == 256) {
    for (int i = 0; i < 8; i++) mbar_init(bA + 8 * i, 1);
    for (int i = 0; i < 4; i++) { mbar_init(bF + 8 * i, 1); mbar_init(bE + 8 * i, 8); }
    fence_init();
  }
  cluster_sync();
  if (warp >= 8) {
    asm volatile("setmaxnreg.dec.sync.aligned.u32 40;");
    if (tid == 256) {
      auto loadB = [&](int s) {
        const uint32_t d = sB + (s & 3) * 24576, b = bF + (s & 3) * 8;
        mbar_expect(b, 24576);
        for (int j = 0; j < 3; j++) {
          if (FFN) { tma2d(d + j * BOX, &mB0, ct * 176 + j * 64, s * 32, b); tma2d(d + (3 + j) * BOX, &mB1, ct * 176 + j * 64, s * 32, b); }
          else tma2d(d + j * BOX, &mB0, ct * 192 + j * 64, s * 64, b);
        }
      };
      for (int i = 0; i < 8; i++) mbar_expect(bA + 8 * i, 16384);
      for (int s = 0; s < 4; s++) {
        const int i = s * 2 + (ct & 1);
        if (!FFN) tma2d_mc(sA + i * 16384, &mX, i * 64, rb * 128, bA + 8 * i);
        loadB(s);
      }
      if (FFN) {
        pdl_wait();
        for (int i = ct & 1; i < 8; i += 2) bulk_load_mc(sA + i * 16384, g_x1 + (rb * 64 + i * 8) * 1024, 16384, bA + 8 * i);
      }
      for (int s = 4; s < NST; s++) { mbar_wait(bE + (s & 3) * 8, ((s >> 2) - 1) & 1); loadB(s); }
    } else if (!FFN && warp > 8) {
      mbar_wait(bA + 56, 0);
      const int u = tid - 288, n0 = 1024 + blockIdx.x * 16;
      float a[8] = {0, 0, 0, 0, 0, 0, 0, 0};
#pragma unroll 3
      for (int r = u >> 1; r < 512; r += 48) fma8(a, silu_bf(cv[r]), __ldg((const uint4*)(wm + r * 3072 + n0 + (u & 1) * 8)));
      float s = red8(a, lane);
      s += __shfl_xor_sync(~0u, s, 2);
      if (!(lane & 2)) red[64 + (warp - 9) * 16 + (lane & 1) * 8 + (lane >> 2)] = s;
      asm volatile("bar.sync 2,96;" ::: "memory");
      if (u < 16) g_mod[n0 + u] = mod_fin(red[64 + u] + red[80 + u] + red[96 + u], n0 + u);
    }
  } else {
  asm volatile("setmaxnreg.inc.sync.aligned.u32 232;");
  const int g = lane >> 2, t = lane & 3;
  const int lr = warp * 16 + (lane & 7) + ((lane >> 3) & 1) * 8;
  auto aaddr = [&](int ks) -> uint32_t {
    if (FFN) return sA + (ks * 2 + (lane >> 4)) * 2048 + lr * 16;
    return sA + (ks >> 2) * 16384 + lr * 128 + ((((ks & 3) * 2 + (lane >> 4)) ^ (lr & 7)) << 4);
  };
  const int row0 = rb * 128 + warp * 16 + g;
  float2 msh, msc;
  float rs0, rs1, nm0, nm1;
  if (!FFN) {
    {
      float a[8] = {0, 0, 0, 0, 0, 0, 0, 0};
      fma8(a, silu_bf(cv0), wv0); fma8(a, silu_bf(cv1), wv1);
      const float s = qsum(red8(a, lane));
      if (t == 0) red[warp * 8 + g] = s;
      asm volatile("bar.sync 1,256;" ::: "memory");
      if (tid < 8) {
        float r = 0;
#pragma unroll
        for (int i = 0; i < 8; i++) r += red[i * 8 + tid];
        const int n = blockIdx.x * 8 + tid;
        asm volatile("st.relaxed.gpu.global.u32 [%0],%1;" ::"l"(g_modv + n), "r"(__float_as_uint(mod_fin(r, n)) | 1u) : "memory");
      }
      TS(0, 1);
    }
    {
      float v[32], s = 0, q = 0;
#pragma unroll
      for (int i = 0; i < 16; i++) { const uint32_t u = ((const uint32_t*)xv)[i]; v[2 * i] = blo(u); v[2 * i + 1] = bhi(u); s += v[2 * i] + v[2 * i + 1]; }
      s = qsum(s); s += __shfl_xor_sync(~0u, s, 4); s += __shfl_xor_sync(~0u, s, 8);
      const float m = s * (1.f / 512);
#pragma unroll
      for (int i = 0; i < 32; i++) q += (v[i] - m) * (v[i] - m);
      q = qsum(q); q += __shfl_xor_sync(~0u, q, 4); q += __shfl_xor_sync(~0u, q, 8);
      const float rs = rsqrtf(q * (1.f / 512) + 1e-5f);
      if ((tid & 15) == 0)
        asm volatile("st.relaxed.gpu.global.v2.u32 [%0],{%1,%2};" ::"l"(g_modv + 1024 + (blockIdx.x * 16 + (tid >> 4)) * 2), "r"(__float_as_uint(rs) | 1u), "r"(__float_as_uint(-m * rs) | 1u) : "memory");
    }
    const uint2 p0 = poll2(g_modv + 1024 + row0 * 2), p1 = poll2(g_modv + 1024 + row0 * 2 + 16);
    rs0 = __uint_as_float(p0.x); nm0 = __uint_as_float(p0.y); rs1 = __uint_as_float(p1.x); nm1 = __uint_as_float(p1.y);
    TS(1, 1);
  } else {
    pdl_wait();
    TS(4, 1);
    msh = *(const float2*)(g_mod + 1536 + tid * 2); msc = *(const float2*)(g_mod + 2048 + tid * 2);
    const float4 p0 = *(const float4*)(g_st + row0 * 8 + t * 2), p1 = *(const float4*)(g_st + (row0 + 8) * 8 + t * 2);
    const float m0 = qsum(p0.x + p0.z) * 0.125f, m1 = qsum(p1.x + p1.z) * 0.125f;
    const float v0 = qsum(p0.y + p0.w + 64.f * ((p0.x - m0) * (p0.x - m0) + (p0.z - m0) * (p0.z - m0)));
    const float v1 = qsum(p1.y + p1.w + 64.f * ((p1.x - m1) * (p1.x - m1) + (p1.z - m1) * (p1.z - m1)));
    rs0 = rsqrtf(v0 * (1.f / 512) + 1e-5f); rs1 = rsqrtf(v1 * (1.f / 512) + 1e-5f);
    nm0 = -m0 * rs0; nm1 = -m1 * rs1;
  }
  {
    uint32_t* m = (uint32_t*)(smem + (sM - sA)) + (tid >> 3) * 16 + (tid & 3) * 4 + ((tid >> 2) & 1);
    if (FFN) { m[0] = pack_rn(msc.x, msc.y); m[2] = pack_rn(msh.x, msh.y); }
    else { const uint2 sh = poll2(g_modv + tid * 2), sc = poll2(g_modv + 512 + tid * 2); m[0] = __byte_perm(sc.x, sc.y, 0x7632); m[2] = __byte_perm(sh.x, sh.y, 0x7632); }
    asm volatile("bar.sync 1,256;" ::: "memory");
  }
  constexpr int NA = FFN ? 88 : 96;
  float acc0[NA], acc1[FFN ? 88 : 1];
  uint32_t a[2][KS][4];
  auto prep = [&](int ks, uint32_t(&o)[4]) {
    if ((ks & 3) == 0) mbar_wait(bA + 2 * ks, 0);
    uint32_t r[4]; ldsm4(aaddr(ks), r);
    const uint4 m = *(const uint4*)(smem + (sM - sA) + ks * 64 + t * 16);
#pragma unroll
    for (int i = 0; i < 4; i++) {
      const float rs = (i & 1) ? rs1 : rs0, nm = (i & 1) ? nm1 : nm0;
      const uint32_t n = pack_rn(fmaf(blo(r[i]), rs, nm), fmaf(bhi(r[i]), rs, nm));
      asm("fma.rn.bf16x2 %0,%1,%2,%3;" : "=r"(o[i]) : "r"(n), "r"(i < 2 ? m.x : m.y), "r"(i < 2 ? m.z : m.w));
    }
  };
  auto stage = [&](int s, uint32_t(&c)[KS][4], uint32_t(&n)[KS][4]) {
    mbar_wait(bF + (s & 3) * 8, (s >> 2) & 1);
    const uint64_t db = mk_desc(sB + (s & 3) * 24576, BOX, 1024, 1);
    wg_fence();
#pragma unroll
    for (int k = 0; k < KS; k++) {
      if constexpr (FFN) {
        wgmma_rs_n176_t1(acc0, c[k][0], c[k][1], c[k][2], c[k][3], db + k * 128, s + k);
        wgmma_rs_n176_t1(acc1, c[k][0], c[k][1], c[k][2], c[k][3], db + k * 128 + 3 * BOX / 16, s + k);
      } else {
        wgmma_rs_n192_t1(acc0, c[k][0], c[k][1], c[k][2], c[k][3], db + k * 128, s + k);
      }
    }
    wg_commit();
    wg_wait<1>();
    if (s > 0 && lane == 0) mbar_arrive(bE + ((s - 1) & 3) * 8);
    if (s < NST - 1) {
#pragma unroll
      for (int k = 0; k < KS; k++) prep((s + 1) * KS + k, n[k]);
    }
  };
#pragma unroll
  for (int k = 0; k < KS; k++) prep(k, a[0][k]);
  TS(FFN ? 4 : 1, 2);
#pragma unroll 1
  for (int s = 0; s < NST; s += 2) { stage(s, a[0], a[1]); stage(s + 1, a[1], a[0]); }
  wg_wait<0>();
  reg_fence(acc0);
  TS(FFN ? 4 : 1, 3);
  if constexpr (FFN) {
    reg_fence(acc1);
    uint32_t* o = (uint32_t*)g_h + ((rb * 172 + ct * 22) * 128 + warp * 16 + g) * 4 + t;
#pragma unroll
    for (int j = 0; j < 22; j++) {
      if (ct * 22 + j < 172) {
        float h[4];
#pragma unroll
        for (int i = 0; i < 4; i++) { const float x = acc0[4 * j + i]; h[i] = __fdividef(x, 1.f + ex2(-1.4426950408889634f * x)) * acc1[4 * j + i]; }
        o[j * 512] = pack_rn(h[0], h[1]);
        o[j * 512 + 32] = pack_rn(h[2], h[3]);
      }
    }
  } else {
    uint32_t* o = (uint32_t*)g_qkv + (ct * 24 * 2048 + row0) * 4 + t;
#pragma unroll
    for (int j = 0; j < 24; j += 2) {
      const int G = ct * 24 + j;
      const float sc = G < 64 ? 0.25f * 1.4426950408889634f : 1.f;
      uint32_t p[4];
#pragma unroll
      for (int i = 0; i < 4; i++) p[i] = pack_rn(acc0[4 * j + 2 * i] * sc, acc0[4 * j + 2 * i + 1] * sc);
      o[j * 8192] = p[0]; o[j * 8192 + 32] = p[1]; o[(j + 1) * 8192] = p[2]; o[(j + 1) * 8192 + 32] = p[3];
      if (G >= 64 && G < 128) {
        float n0 = blo(p[0]) * blo(p[0]) + bhi(p[0]) * bhi(p[0]) + blo(p[2]) * blo(p[2]) + bhi(p[2]) * bhi(p[2]);
        float n1 = blo(p[1]) * blo(p[1]) + bhi(p[1]) * bhi(p[1]) + blo(p[3]) * blo(p[3]) + bhi(p[3]) * bhi(p[3]);
        n0 = qsum(n0); n1 = qsum(n1);
        const uint32_t mx = __reduce_max_sync(~0u, max(__float_as_uint(n0), __float_as_uint(n1)));
        if (lane == 0) g_kmax[((G - 64) >> 1) * 128 + rb * 8 + warp] = __uint_as_float(mx);
      }
    }
  }
  TS(FFN ? 4 : 1, 4);
}
}

#define SMASK 0xAAu
#define BRK 0
#define PACK 1
#define PP 1
constexpr int AT_SMEM = 5 * 32768 + 256;
__device__ __forceinline__ uint32_t exp2_pair_fma(float s0, float s1, float c, uint32_t ka, uint32_t kz) {
  uint32_t r;
  asm volatile("{\n.reg .b32 y0,y1,e,u,t;\n"
      "fma.rn.sat.f32 y0,%1,0f00000080,%3;\nfma.rn.sat.f32 y1,%2,0f00000080,%3;\n"
      "mad.lo.u32 e,y1,65536,y0;\n"
      "and.b32 u,e,0x007F007F;\n"
      "fma.rn.f16x2 u,u,%4,%5;\nfma.rn.f16x2 t,u,u,%6;\nfma.rn.f16x2 t,t,u,%7;\n"
      "lop3.b32 %0,t,0x007F007F,e,0xE2;\n}\n"
      : "=r"(r) : "f"(s0), "f"(s1), "f"(c), "r"(ka), "r"(0x36B236B2u), "r"(0x3C733C73u), "r"(0x47764776u), "r"(kz));
  return r;
}
__device__ __forceinline__ void attn_pass(float (&oa)[12], float (&ob)[12], const uint32_t (&q)[4], float m0, float m1, uint32_t sK, uint32_t bars, bool first, uint32_t kz) {
  const uint64_t dk = mk_desc(sK, 32768, 128, 0), dv = mk_desc(sK + 65536, 128, 32768, 0);
  const float c0 = (127.f - m0) * __uint_as_float(0x80u), c1 = (127.f - m1) * __uint_as_float(0x80u);
  const uint32_t ka = 0x7ACE7ACEu + kz;
  constexpr int NK = 64, NS = 32, NP = 16, NI = 32;
  auto qk = [&](float (&s)[NS], int i) { wgmma_rs_n64_t0(s, q[0], q[1], q[2], q[3], dk + i * NK, 0); };
  auto softmax = [&](float (&s)[NS], uint32_t (&p)[NP], uint32_t mask) {
    reg_fence(s);
    float e0, e1;
    int pend = -1;
#pragma unroll
    for (int t = 0; t < NP; t++) {
      const int j = (t & 3) * 4 + (t >> 2);
      if ((mask >> (t & 3)) & 1) {
        p[j] = exp2_pair_fma(s[2 * j], s[2 * j + 1], (j & 1) ? c1 : c0, ka, kz);
      } else {
        float f0, f1;
        asm volatile("ex2.approx.ftz.f32 %0,%2;\nex2.approx.ftz.f32 %1,%3;" : "=&f"(f0), "=f"(f1) : "f"(s[2 * j]), "f"(s[2 * j + 1]));
        if (pend >= 0) asm volatile("cvt.rn.bf16x2.f32 %0,%1,%2;" : "=r"(p[pend]) : "f"(e1), "f"(e0));
        e0 = f0; e1 = f1; pend = j;
      }
    }
    if (pend >= 0) asm volatile("cvt.rn.bf16x2.f32 %0,%1,%2;" : "=r"(p[pend]) : "f"(e1), "f"(e0));
#pragma unroll
    for (int j = 0; j < NP; j++) asm volatile("" : "+r"(p[j])::"memory");
  };
  auto pv = [&](uint32_t (&p)[NP], int i, uint32_t mask) {
#pragma unroll
    for (int k = 0; k < 4; k++) wgmma_rs_n24_t1(((mask >> k) & 1) ? ob : oa, p[4 * k], p[4 * k + 1], p[4 * k + 2], p[4 * k + 3], dv + i * NK + k * 16, 1);
  };
  auto ld = [&](int i) { if (first && (i & 3) == 0) mbar_wait(bars + i * 2, 0); };
  constexpr uint32_t M0 = SMASK & 15, M1 = SMASK >> 4;
  zero(oa); zero(ob);
  ld(0);
  if (first) TS(2, 2);
  float s[NS];
  zero(s);
  uint32_t p0[NP], p1[NP];
  wg_fence(); qk(s, 0); wg_commit(); wg_wait<0>(); softmax(s, p0, M0);
#pragma unroll 1
  for (int i = 0; i < NI - 2; i += 2) {
    wg_fence(); qk(s, i + 1); wg_commit(); pv(p0, i, M0); wg_commit(); wg_wait<1>(); softmax(s, p1, M1); wg_wait<0>();
    ld(i + 2);
    wg_fence(); qk(s, i + 2); wg_commit(); pv(p1, i + 1, M1); wg_commit(); wg_wait<1>(); softmax(s, p0, M0); wg_wait<0>();
  }
  wg_fence(); qk(s, NI - 1); wg_commit(); pv(p0, NI - 2, M0); wg_commit(); wg_wait<1>(); softmax(s, p1, M1); wg_wait<0>();
  wg_fence(); pv(p1, NI - 1, M1); wg_commit();
  wg_wait<0>();
  reg_fence(oa); reg_fence(ob);
}
__device__ __forceinline__ void mma16816(float (&d)[4], const uint32_t (&a)[4], uint32_t b0, uint32_t b1) {
  asm("mma.sync.aligned.m16n8k16.row.col.f32.bf16.bf16.f32 {%0,%1,%2,%3},{%4,%5,%6,%7},{%8,%9},{%0,%1,%2,%3};"
      : "+f"(d[0]), "+f"(d[1]), "+f"(d[2]), "+f"(d[3]) : "r"(a[0]), "r"(a[1]), "r"(a[2]), "r"(a[3]), "r"(b0), "r"(b1));
}
__device__ __forceinline__ void attn_safe(float (&o)[12], const uint32_t (&q)[4], uint32_t sK) {
  const int lane = threadIdx.x & 31;
  const uint32_t ka = sK + (lane >> 4) * 32768 + (lane & 15) * 16;
  float m0 = -INFINITY, m1 = -INFINITY;
#pragma unroll 2
  for (int i = 0; i < 128; i++) {
    uint32_t k[4]; ldsm4(ka + i * 256, k);
    float s0[4] = {0, 0, 0, 0}, s1[4] = {0, 0, 0, 0};
    mma16816(s0, q, k[0], k[2]); mma16816(s1, q, k[1], k[3]);
    m0 = fmaxf(fmaxf(m0, fmaxf(s0[0], s0[1])), fmaxf(s1[0], s1[1])); m1 = fmaxf(fmaxf(m1, fmaxf(s0[2], s0[3])), fmaxf(s1[2], s1[3]));
  }
  m0 = fmaxf(m0, __shfl_xor_sync(~0u, m0, 1)); m0 = fmaxf(m0, __shfl_xor_sync(~0u, m0, 2));
  m1 = fmaxf(m1, __shfl_xor_sync(~0u, m1, 1)); m1 = fmaxf(m1, __shfl_xor_sync(~0u, m1, 2));
  float o0[4] = {0, 0, 0, 0}, o1[4] = {0, 0, 0, 0}, o2[4] = {0, 0, 0, 0};
#pragma unroll 2
  for (int i = 0; i < 128; i++) {
    uint32_t k[4], v[4]; ldsm4(ka + i * 256, k);
    asm volatile("ldmatrix.sync.aligned.m8n8.x4.trans.shared.b16 {%0,%1,%2,%3},[%4];" : "=r"(v[0]), "=r"(v[1]), "=r"(v[2]), "=r"(v[3]) : "r"(ka + 65536 + i * 256) : "memory");
    float s0[4] = {0, 0, 0, 0}, s1[4] = {0, 0, 0, 0};
    mma16816(s0, q, k[0], k[2]); mma16816(s1, q, k[1], k[3]);
    const uint32_t p[4] = {pack_rn(ex2(s0[0] - m0), ex2(s0[1] - m0)), pack_rn(ex2(s0[2] - m1), ex2(s0[3] - m1)),
                           pack_rn(ex2(s1[0] - m0), ex2(s1[1] - m0)), pack_rn(ex2(s1[2] - m1), ex2(s1[3] - m1))};
    mma16816(o0, p, v[0], v[1]); mma16816(o1, p, v[2], v[3]); mma16816(o2, p, 0x3F803F80u, 0x3F803F80u);
  }
#pragma unroll
  for (int i = 0; i < 4; i++) { o[i] = o0[i]; o[4 + i] = o1[i]; o[8 + i] = o2[i]; }
}
__global__ void __cluster_dims__(2, 1, 1) __launch_bounds__(512, 1) k_attn(const bf16* wo, const bf16* w1, const bf16* w3, const bf16* w2, uint32_t kz) {
  extern __shared__ __align__(1024) uint8_t smem[];
  const uint32_t sK = smem_u32(smem), bars = sK + 5 * 32768;
  const int tid = threadIdx.x, warp = tid >> 5, lane = tid & 31, g = lane >> 2, t = lane & 3;
  const int h = blockIdx.x >> 2, qb = blockIdx.x & 3;
  TS(2, 0);
  pdl_launch();
  if (tid == 0) { for (int i = 0; i < 8; i++) { mbar_init(bars + 8 * i, 1); mbar_expect(bars + 8 * i, 16384); } fence_init(); }
#pragma unroll
  for (int i = 0; i < 4; i++) *(uint4*)(smem + 131072 + i * 8192 + tid * 16) = make_uint4(0x3F803F80u, 0x3F803F80u, 0x3F803F80u, 0x3F803F80u);
  fence_async();
  cluster_sync();
  pdl_wait();
  TS(2, 1);
  if (tid >= 472) g_modv[blockIdx.x * 40 + tid - 472] = 0;
  if (tid == 0) {
    for (int c = 0; c < 8; c++)
      for (int pl = qb & 1; pl < 4; pl += 2)
        bulk_load_mc(sK + pl * 32768 + c * 4096, g_qkv + ((64 + (pl >> 1) * 64 + h * 2 + (pl & 1)) * 2048 + c * 256) * 8, 4096, bars + 8 * c);
  }
  if (tid == 32) {
    l2_prefetch((const char*)wo + blockIdx.x * 4096, 4096);
    l2_prefetch((const char*)w1 + blockIdx.x * 11008, 11008);
    l2_prefetch((const char*)w3 + blockIdx.x * 11008, 11008);
    l2_prefetch((const char*)w2 + blockIdx.x * 11008, 11008);
  }
  const uint4 km4 = *(const uint4*)(g_kmax + h * 128 + lane * 4);
  const float kmax = __uint_as_float(__reduce_max_sync(~0u, max(max(km4.x, km4.y), max(km4.z, km4.w))));
#pragma unroll 1
  for (int tile = 0; tile < 2; tile++) {
    const int row = qb * 512 + tile * 256 + warp * 16 + g;
    const uint32_t* qp = (const uint32_t*)g_qkv + (h * 2 * 2048 + row) * 4 + t;
    uint32_t q[4] = {qp[0], qp[32], qp[8192], qp[8192 + 32]};
    const float n0 = qsum(blo(q[0]) * blo(q[0]) + bhi(q[0]) * bhi(q[0]) + blo(q[2]) * blo(q[2]) + bhi(q[2]) * bhi(q[2]));
    const float n1 = qsum(blo(q[1]) * blo(q[1]) + bhi(q[1]) * bhi(q[1]) + blo(q[3]) * blo(q[3]) + bhi(q[3]) * bhi(q[3]));
    const float b0 = sqrtf(n0 * kmax) * 1.001f, b1 = sqrtf(n1 * kmax) * 1.001f;
    const float m0 = fmaxf(ceilf(b0 - 100.f), 0.f), m1 = fmaxf(ceilf(b1 - 100.f), 0.f);
    float o[12], ob[12];
    attn_pass(o, ob, q, m0, m1, sK, bars, tile == 0, kz);
    const float f0 = ex2(-m0), f1 = ex2(-m1);
#pragma unroll
    for (int i = 0; i < 12; i++) o[i] = fmaf(o[i], (i & 2) ? f1 : f0, ob[i]);
    bool ok = b0 < 220.f && b1 < 220.f && o[8] >= 0x1p-90f && o[10] >= 0x1p-90f;
#pragma unroll
    for (int i = 0; i < 12; i++) ok = ok && fabsf(o[i]) < INFINITY;
    if (!__all_sync(~0u, ok)) attn_safe(o, q, sK);
    const float r0 = 1.f / o[8], r1 = 1.f / o[10];
    uint32_t* op = (uint32_t*)g_o + (((row >> 7) * 64 + h * 2) * 128 + (row & 127)) * 4 + t;
    op[0] = pack_rn(o[0] * r0, o[1] * r0); op[32] = pack_rn(o[2] * r1, o[3] * r1);
    op[512] = pack_rn(o[4] * r0, o[5] * r0); op[512 + 32] = pack_rn(o[6] * r1, o[7] * r1);
    TS(2, 3 + tile);
  }
}

constexpr int WO_SMEM = 131072 + 65536 + 256;
__global__ void __cluster_dims__(2, 1, 1) __launch_bounds__(256, 1) k_wo(const __grid_constant__ CUtensorMap mW, const bf16* __restrict__ x) {
  extern __shared__ __align__(1024) uint8_t smem[];
  const uint32_t sA = smem_u32(smem), sB = sA + 131072, bars = sB + 65536;
  const int tid = threadIdx.x, warp = tid >> 5, lane = tid & 31, g = lane >> 2, t = lane & 3;
  const int rb = blockIdx.x >> 3, ct = blockIdx.x & 7;
  TS(3, 0);
  pdl_launch();
  if (tid == 0) {
    for (int i = 0; i < 8; i++) mbar_init(bars + 8 * i, 1);
    fence_init();
    for (int i = 0; i < 8; i++) { mbar_expect(bars + 8 * i, 24576); tma2d(sB + i * 8192, &mW, ct * 64, i * 64, bars + 8 * i); }
  }
  const int lrow = warp * 16 + g;
  uint32_t xr[16];
  const uint32_t* xp = (const uint32_t*)(x + (rb * 128 + lrow) * 512 + ct * 64) + t;
#pragma unroll
  for (int j = 0; j < 8; j++) { xr[2 * j] = __ldg(xp + j * 4); xr[2 * j + 1] = __ldg(xp + j * 4 + 8 * 256); }
  cluster_sync();
  pdl_wait();
  TS(3, 1);
  if (tid == 0) for (int i = ct & 1; i < 8; i += 2) bulk_load_mc(sA + i * 16384, g_o + (rb * 64 + i * 8) * 1024, 16384, bars + 8 * i);
  float2 ga[8];
#pragma unroll
  for (int j = 0; j < 8; j++) ga[j] = *(const float2*)(g_mod + 1024 + ct * 64 + j * 8 + t * 2);
  float acc[32];
  const uint64_t da = mk_desc(sA + (warp >> 2) * 1024, 2048, 128, 0), db = mk_desc(sB, 8192, 1024, 1);
#pragma unroll
  for (int c = 0; c < 8; c++) {
    mbar_wait(bars + 8 * c, 0);
    if (c == 0) TS(3, 2);
    wg_fence();
#pragma unroll
    for (int k = 0; k < 4; k++) wgmma_ss_n64_t1(acc, da + (c * 4 + k) * 256, db + (c * 4 + k) * 128, c + k);
    wg_commit();
  }
  wg_wait<0>();
  reg_fence(acc);
  TS(3, 3);
  uint32_t* o = (uint32_t*)g_x1 + ((rb * 64 + ct * 8) * 128 + lrow) * 4 + t;
  float s0 = 0, s1 = 0;
#pragma unroll
  for (int j = 0; j < 8; j++) {
    xr[2 * j] = pack_rn(fmaf(ga[j].x, acc[4 * j], blo(xr[2 * j])), fmaf(ga[j].y, acc[4 * j + 1], bhi(xr[2 * j])));
    xr[2 * j + 1] = pack_rn(fmaf(ga[j].x, acc[4 * j + 2], blo(xr[2 * j + 1])), fmaf(ga[j].y, acc[4 * j + 3], bhi(xr[2 * j + 1])));
    o[j * 512] = xr[2 * j]; o[j * 512 + 32] = xr[2 * j + 1];
    s0 += blo(xr[2 * j]) + bhi(xr[2 * j]); s1 += blo(xr[2 * j + 1]) + bhi(xr[2 * j + 1]);
  }
  const float m0 = qsum(s0) * (1.f / 64), m1 = qsum(s1) * (1.f / 64);
  float v0 = 0, v1 = 0;
#pragma unroll
  for (int j = 0; j < 8; j++) {
    float d;
    d = blo(xr[2 * j]) - m0; v0 += d * d; d = bhi(xr[2 * j]) - m0; v0 += d * d;
    d = blo(xr[2 * j + 1]) - m1; v1 += d * d; d = bhi(xr[2 * j + 1]) - m1; v1 += d * d;
  }
  v0 = qsum(v0); v1 = qsum(v1);
  if (t == 0) g_st[(rb * 128 + lrow) * 8 + ct] = make_float2(m0, v0);
  if (t == 1) g_st[(rb * 128 + lrow + 8) * 8 + ct] = make_float2(m1, v1);
  TS(3, 4);
}

constexpr int W2_SMEM = 6 * 32768 + 32768 + 256;
__global__ void __cluster_dims__(2, 1, 1) __launch_bounds__(288, 1) k_w2(const __grid_constant__ CUtensorMap mW, bf16* __restrict__ out) {
  extern __shared__ __align__(1024) uint8_t smem[];
  const uint32_t sR = smem_u32(smem), sX = sR + 6 * 32768, bF = sX + 32768, bE = bF + 48;
  const int tid = threadIdx.x, warp = tid >> 5, lane = tid & 31, g = lane >> 2, t = lane & 3;
  const int kh = blockIdx.x & 1, ct = (blockIdx.x >> 1) & 3, rb = blockIdx.x >> 3;
  TS(5, 0);
  pdl_launch();
  if (tid == 256) {
    for (int i = 0; i < 6; i++) { mbar_init(bF + 8 * i, 1); mbar_init(bE + 8 * i, 8); }
    fence_init();
  }
  __syncthreads();
  asm volatile("barrier.cluster.arrive.relaxed.aligned;" ::: "memory");
  if (warp == 8) {
    if (lane == 0) {
      auto abytes = [&](int s) { return (kh == 1 && s == 10) ? 8192 : 16384; };
      auto loadB = [&](int s) {
        const int st = s % 6;
        mbar_expect(bF + 8 * st, 16384 + abytes(s));
        for (int j = 0; j < 2; j++) tma2d(sR + st * 32768 + 16384 + j * 8192, &mW, ct * 128 + j * 64, kh * 704 + s * 64, bF + 8 * st);
      };
      auto loadA = [&](int s) { bulk_load(sR + (s % 6) * 32768, g_h + (rb * 172 + kh * 88 + s * 8) * 1024, abytes(s), bF + 8 * (s % 6)); };
      for (int s = 0; s < 6; s++) loadB(s);
      pdl_wait();
      for (int s = 0; s < 6; s++) loadA(s);
      for (int s = 6; s < 11; s++) { mbar_wait(bE + 8 * (s - 6), 0); loadB(s); loadA(s); }
    }
    __syncwarp();
    asm volatile("barrier.cluster.wait.aligned;" ::: "memory");
    asm volatile("barrier.cluster.arrive.release.aligned;" ::: "memory");
    asm volatile("barrier.cluster.wait.acquire.aligned;" ::: "memory");
    return;
  }
  pdl_wait();
  TS(5, 1);
  const int lrow = warp * 16 + g;
  uint32_t xr[16];
  float2 gb[8];
  const uint32_t* xp = (const uint32_t*)g_x1 + ((rb * 64 + ct * 16 + kh * 8) * 128 + lrow) * 4 + t;
#pragma unroll
  for (int j = 0; j < 8; j++) {
    xr[2 * j] = xp[j * 512]; xr[2 * j + 1] = xp[j * 512 + 32];
    gb[j] = *(const float2*)(g_mod + 2560 + ct * 128 + kh * 64 + j * 8 + t * 2);
  }
  float acc[64];
#pragma unroll 1
  for (int s = 0; s < 11; s++) {
    const int st = s % 6;
    mbar_wait(bF + 8 * st, s >= 6);
    const uint64_t da = mk_desc(sR + st * 32768 + (warp >> 2) * 1024, 2048, 128, 0), db = mk_desc(sR + st * 32768 + 16384, 8192, 1024, 1);
    if (s == 0) TS(5, 2);
    wg_fence();
    wgmma_ss_n128_t1(acc, da, db, s);
    wgmma_ss_n128_t1(acc, da + 256, db + 128, 1);
    wgmma_ss_n128_t1(acc, da + 512, db + 256, 1);
    wgmma_ss_n128_t1(acc, da + 768, db + 384, 1);
    wg_commit();
    wg_wait<1>();
    if (s > 0 && s < 6 && lane == 0) mbar_arrive(bE + 8 * (s - 1));
  }
  wg_wait<0>();
  reg_fence(acc);
  TS(5, 3);
  asm volatile("barrier.cluster.wait.aligned;" ::: "memory");
  uint32_t rem;
  asm("mapa.shared::cluster.u32 %0,%1,%2;" : "=r"(rem) : "r"(sX + tid * 16), "r"(kh ^ 1));
#pragma unroll
  for (int j = 0; j < 8; j++) {
    float v[4];
#pragma unroll
    for (int i = 0; i < 4; i++) { v[i] = kh ? acc[4 * j + i] : acc[32 + 4 * j + i]; acc[4 * j + i] = kh ? acc[32 + 4 * j + i] : acc[4 * j + i]; }
    asm volatile("st.shared::cluster.v4.f32 [%0],{%1,%2,%3,%4};" ::"r"(rem + j * 4096), "f"(v[0]), "f"(v[1]), "f"(v[2]), "f"(v[3]) : "memory");
  }
  asm volatile("barrier.cluster.arrive.release.aligned;" ::: "memory");
  asm volatile("barrier.cluster.wait.acquire.aligned;" ::: "memory");
  uint32_t* o = (uint32_t*)(out + (rb * 128 + lrow) * 512 + ct * 128 + kh * 64) + t;
#pragma unroll
  for (int j = 0; j < 8; j++) {
    const float4 p = *(const float4*)(smem + 6 * 32768 + j * 4096 + tid * 16);
    o[j * 4] = pack_rn(fmaf(gb[j].x, acc[4 * j] + p.x, blo(xr[2 * j])), fmaf(gb[j].y, acc[4 * j + 1] + p.y, bhi(xr[2 * j])));
    o[j * 4 + 2048] = pack_rn(fmaf(gb[j].x, acc[4 * j + 2] + p.z, blo(xr[2 * j + 1])), fmaf(gb[j].y, acc[4 * j + 3] + p.w, bhi(xr[2 * j + 1])));
  }
  TS(5, 4);
}

typedef CUresult (*EncFn)(CUtensorMap*, CUtensorMapDataType, cuuint32_t, void*, const cuuint64_t*, const cuuint64_t*, const cuuint32_t*,
                          const cuuint32_t*, CUtensorMapInterleave, CUtensorMapSwizzle, CUtensorMapL2promotion, CUtensorMapFloatOOBfill);
static void mk_map(EncFn f, CUtensorMap* m, const void* p, int rows, int cols, int box_rows) {
  cuuint64_t dim[2] = {(cuuint64_t)cols, (cuuint64_t)rows}, str[1] = {(cuuint64_t)cols * 2};
  cuuint32_t box[2] = {64, (cuuint32_t)box_rows}, es[2] = {1, 1};
  f(m, CU_TENSOR_MAP_DATA_TYPE_BFLOAT16, 2, (void*)p, dim, str, box, es, CU_TENSOR_MAP_INTERLEAVE_NONE, CU_TENSOR_MAP_SWIZZLE_128B,
    CU_TENSOR_MAP_L2_PROMOTION_L2_128B, CU_TENSOR_MAP_FLOAT_OOB_FILL_NONE);
}
template <typename... KA, typename... A>
static void launch(void (*k)(KA...), int grid, int block, int smem, bool pdl, A... args) {
  cudaLaunchConfig_t cfg = {};
  cfg.gridDim = dim3(grid); cfg.blockDim = dim3(block); cfg.dynamicSmemBytes = smem; cfg.stream = cudaStreamPerThread;
  cudaLaunchAttribute at[1];
  at[0].id = cudaLaunchAttributeProgrammaticStreamSerialization; at[0].val.programmaticStreamSerializationAllowed = 1;
  cfg.attrs = at; cfg.numAttrs = pdl ? 1 : 0;
  cudaLaunchKernelEx(&cfg, k, args...);
}
extern "C" void kernel_launch(void* const* d_in, const int* in_sizes, int n_in, void* d_out, int out_size) {
  const bf16 *x = (const bf16*)d_in[0], *wqkv = (const bf16*)d_in[1], *wo = (const bf16*)d_in[2], *w1 = (const bf16*)d_in[4],
             *w3 = (const bf16*)d_in[5], *w2 = (const bf16*)d_in[6], *c = (const bf16*)d_in[7], *wmod = (const bf16*)d_in[8];
  void* fp = nullptr;
  cudaDriverEntryPointQueryResult qr;
  cudaGetDriverEntryPoint("cuTensorMapEncodeTiled", &fp, cudaEnableDefault, &qr);
  EncFn f = (EncFn)fp;
  CUtensorMap mX, mQ, mO, m1, m3, m2;
  mk_map(f, &mX, x, S_, D_, 128); mk_map(f, &mQ, wqkv, D_, 3 * D_, 64); mk_map(f, &mO, wo, D_, D_, 64);
  mk_map(f, &m1, w1, D_, F_, 32); mk_map(f, &m3, w3, D_, F_, 32); mk_map(f, &m2, w2, F_, D_, 64);
  cudaFuncSetAttribute(k_lngemm<false>, cudaFuncAttributeMaxDynamicSharedMemorySize, LN_SMEM);
  cudaFuncSetAttribute(k_lngemm<true>, cudaFuncAttributeMaxDynamicSharedMemorySize, LN_SMEM);
  cudaFuncSetAttribute(k_attn, cudaFuncAttributeMaxDynamicSharedMemorySize, AT_SMEM);
  cudaFuncSetAttribute(k_wo, cudaFuncAttributeMaxDynamicSharedMemorySize, WO_SMEM);
  cudaFuncSetAttribute(k_w2, cudaFuncAttributeMaxDynamicSharedMemorySize, W2_SMEM);
  launch(k_lngemm<false>, 128, 384, LN_SMEM, false, mX, mQ, mQ, c, wmod, x);
  launch(k_attn, 128, 512, AT_SMEM, true, wo, w1, w3, w2, 0u);
  launch(k_wo, 128, 256, WO_SMEM, true, mO, x);
  launch(k_lngemm<true>, 128, 384, LN_SMEM, true, mX, m1, m3, c, wmod, x);
  launch(k_w2, 128, 288, W2_SMEM, true, m2, (bf16*)d_out);
}
```

```cpp
#include <cuda_runtime.h>
#include <cuda_bf16.h>
#include <cuda.h>
#include <stdint.h>
typedef __nv_bfloat16 bf16;
constexpr int S_ = 2048, D_ = 512, F_ = 1376;
__device__ __align__(1024) float g_mod[3072];
__device__ __align__(1024) uint32_t g_modv[1024 + 4096];
__device__ __align__(1024) bf16 g_qkv[192 * 2048 * 8];
__device__ __align__(1024) float g_kmax[32 * 128];
__device__ __align__(1024) bf16 g_o[16 * 64 * 128 * 8];
__device__ __align__(1024) bf16 g_x1[16 * 64 * 128 * 8];
__device__ __align__(1024) float2 g_st[2048 * 8];
__device__ __align__(1024) bf16 g_h[16 * 172 * 128 * 8];

__device__ __forceinline__ uint32_t smem_u32(const void* p) { return (uint32_t)__cvta_generic_to_shared(p); }
__device__ __forceinline__ void mbar_init(uint32_t b, int n) { asm volatile("mbarrier.init.shared::cta.b64 [%0],%1;" ::"r"(b), "r"(n) : "memory"); }
__device__ __forceinline__ void mbar_expect(uint32_t b, int bytes) { asm volatile("mbarrier.arrive.expect_tx.shared::cta.b64 _,[%0],%1;" ::"r"(b), "r"(bytes) : "memory"); }
__device__ __forceinline__ void mbar_arrive(uint32_t b) { asm volatile("mbarrier.arrive.shared::cta.b64 _,[%0];" ::"r"(b) : "memory"); }
__device__ __forceinline__ void mbar_wait(uint32_t b, int parity) {
  asm volatile("{\n.reg .pred p;\n.reg .u32 n;\nmov.u32 n,0;\nLW:\nmbarrier.try_wait.parity.shared::cta.b64 p,[%0],%1;\n@p bra LD;\n"
               "add.u32 n,n,1;\nsetp.lt.u32 p,n,4194304;\n@p bra LW;\nLD:\n}\n" ::"r"(b), "r"(parity) : "memory");
}
__device__ __forceinline__ void fence_init() { asm volatile("fence.mbarrier_init.release.cluster;" ::: "memory"); }
__device__ __forceinline__ void fence_async() { asm volatile("fence.proxy.async.shared::cta;" ::: "memory"); }
__device__ __forceinline__ void bulk_load(uint32_t dst, const void* src, int bytes, uint32_t bar) {
  asm volatile("cp.async.bulk.shared::cluster.global.mbarrier::complete_tx::bytes [%0],[%1],%2,[%3];" ::"r"(dst), "l"(src), "r"(bytes), "r"(bar) : "memory");
}
__device__ __forceinline__ void tma2d(uint32_t dst, const CUtensorMap* m, int c0, int c1, uint32_t bar) {
  asm volatile("cp.async.bulk.tensor.2d.shared::cluster.global.mbarrier::complete_tx::bytes [%0],[%1,{%3,%4}],[%2];" ::"r"(dst), "l"(m), "r"(bar), "r"(c0), "r"(c1) : "memory");
}
__device__ __forceinline__ void bulk_load_mc(uint32_t dst, const void* src, int bytes, uint32_t bar) {
  asm volatile("cp.async.bulk.shared::cluster.global.mbarrier::complete_tx::bytes.multicast::cluster [%0],[%1],%2,[%3],%4;" ::"r"(dst), "l"(src), "r"(bytes), "r"(bar), "h"((uint16_t)3) : "memory");
}
__device__ __forceinline__ void tma2d_mc(uint32_t dst, const CUtensorMap* m, int c0, int c1, uint32_t bar) {
  asm volatile("cp.async.bulk.tensor.2d.shared::cluster.global.mbarrier::complete_tx::bytes.multicast::cluster [%0],[%1,{%3,%4}],[%2],%5;" ::"r"(dst), "l"(m), "r"(bar), "r"(c0), "r"(c1), "h"((uint16_t)3) : "memory");
}
__device__ __forceinline__ void cluster_sync() { asm volatile("barrier.cluster.arrive.release.aligned;\nbarrier.cluster.wait.acquire.aligned;" ::: "memory"); }
__device__ __forceinline__ void l2_prefetch(const void* p, int bytes) { asm volatile("cp.async.bulk.prefetch.L2.global [%0],%1;" ::"l"(p), "r"(bytes) : "memory"); }
__device__ __forceinline__ void pdl_launch() { asm volatile("griddepcontrol.launch_dependents;" ::: "memory"); }
__device__ __forceinline__ void pdl_wait() { asm volatile("griddepcontrol.wait;" ::: "memory"); }
__device__ __forceinline__ void wg_fence() { asm volatile("wgmma.fence.sync.aligned;" ::: "memory"); }
__device__ __forceinline__ void wg_commit() { asm volatile("wgmma.commit_group.sync.aligned;" ::: "memory"); }
template <int N> __device__ __forceinline__ void wg_wait() { asm volatile("wgmma.wait_group.sync.aligned %0;" ::"n"(N) : "memory"); }
template <int N> __device__ __forceinline__ void reg_fence(float (&d)[N]) {
#pragma unroll
  for (int i = 0; i < N; i++) asm volatile("" : "+f"(d[i])::"memory");
}
template <int N> __device__ __forceinline__ void zero(float (&d)[N]) {
#pragma unroll
  for (int i = 0; i < N; i++) d[i] = 0.f;
  reg_fence(d);
}
__device__ __forceinline__ uint64_t mk_desc(uint32_t addr, uint32_t lbo, uint32_t sbo, uint32_t mode) {
  return (uint64_t)((addr >> 4) & 0x3FFF) | ((uint64_t)(lbo >> 4) << 16) | ((uint64_t)(sbo >> 4) << 32) | ((uint64_t)mode << 62);
}
__device__ __forceinline__ void ldsm4(uint32_t a, uint32_t (&r)[4]) {
  asm volatile("ldmatrix.sync.aligned.m8n8.x4.shared.b16 {%0,%1,%2,%3},[%4];" : "=r"(r[0]), "=r"(r[1]), "=r"(r[2]), "=r"(r[3]) : "r"(a) : "memory");
}
__device__ __forceinline__ uint32_t pack_rn(float lo, float hi) { uint32_t r; asm("cvt.rn.bf16x2.f32 %0,%1,%2;" : "=r"(r) : "f"(hi), "f"(lo)); return r; }
__device__ __forceinline__ uint32_t pack_rz(float lo, float hi) { uint32_t r; asm("cvt.rz.bf16x2.f32 %0,%1,%2;" : "=r"(r) : "f"(hi), "f"(lo)); return r; }
__device__ __forceinline__ float blo(uint32_t u) { return __uint_as_float(u << 16); }
__device__ __forceinline__ float bhi(uint32_t u) { return __uint_as_float(u & 0xFFFF0000u); }
__device__ __forceinline__ float rbf(float x) { return __bfloat162float(__float2bfloat16_rn(x)); }
__device__ __forceinline__ float qsum(float v) { v += __shfl_xor_sync(~0u, v, 1); return v + __shfl_xor_sync(~0u, v, 2); }
__device__ __forceinline__ float ex2(float x) { float r; asm("ex2.approx.ftz.f32 %0,%1;" : "=f"(r) : "f"(x)); return r; }
#define TS(k, i)
__device__ __forceinline__ void wgmma_rs_n176_t1(float (&d)[88],uint32_t a0,uint32_t a1,uint32_t a2,uint32_t a3,uint64_t db,int sc){
  asm volatile("{\n.reg .pred p;\nsetp.ne.b32 p,%93,0;\n"
    "wgmma.mma_async.sync.aligned.m64n176k16.f32.bf16.bf16 {%0,%1,%2,%3,%4,%5,%6,%7,%8,%9,%10,%11,%12,%13,%14,%15,%16,%17,%18,%19,%20,%21,%22,%23,%24,%25,%26,%27,%28,%29,%30,%31,%32,%33,%34,%35,%36,%37,%38,%39,%40,%41,%42,%43,%44,%45,%46,%47,%48,%49,%50,%51,%52,%53,%54,%55,%56,%57,%58,%59,%60,%61,%62,%63,%64,%65,%66,%67,%68,%69,%70,%71,%72,%73,%74,%75,%76,%77,%78,%79,%80,%81,%82,%83,%84,%85,%86,%87},{%88,%89,%90,%91},%92,p,1,1,1;\n}\n"
    :"+f"(d[0]),"+f"(d[1]),"+f"(d[2]),"+f"(d[3]),"+f"(d[4]),"+f"(d[5]),"+f"(d[6]),"+f"(d[7]),"+f"(d[8]),"+f"(d[9]),"+f"(d[10]),"+f"(d[11]),"+f"(d[12]),"+f"(d[13]),"+f"(d[14]),"+f"(d[15]),"+f"(d[16]),"+f"(d[17]),"+f"(d[18]),"+f"(d[19]),"+f"(d[20]),"+f"(d[21]),"+f"(d[22]),"+f"(d[23]),"+f"(d[24]),"+f"(d[25]),"+f"(d[26]),"+f"(d[27]),"+f"(d[28]),"+f"(d[29]),"+f"(d[30]),"+f"(d[31]),"+f"(d[32]),"+f"(d[33]),"+f"(d[34]),"+f"(d[35]),"+f"(d[36]),"+f"(d[37]),"+f"(d[38]),"+f"(d[39]),"+f"(d[40]),"+f"(d[41]),"+f"(d[42]),"+f"(d[43]),"+f"(d[44]),"+f"(d[45]),"+f"(d[46]),"+f"(d[47]),"+f"(d[48]),"+f"(d[49]),"+f"(d[50]),"+f"(d[51]),"+f"(d[52]),"+f"(d[53]),"+f"(d[54]),"+f"(d[55]),"+f"(d[56]),"+f"(d[57]),"+f"(d[58]),"+f"(d[59]),"+f"(d[60]),"+f"(d[61]),"+f"(d[62]),"+f"(d[63]),"+f"(d[64]),"+f"(d[65]),"+f"(d[66]),"+f"(d[67]),"+f"(d[68]),"+f"(d[69]),"+f"(d[70]),"+f"(d[71]),"+f"(d[72]),"+f"(d[73]),"+f"(d[74]),"+f"(d[75]),"+f"(d[76]),"+f"(d[77]),"+f"(d[78]),"+f"(d[79]),"+f"(d[80]),"+f"(d[81]),"+f"(d[82]),"+f"(d[83]),"+f"(d[84]),"+f"(d[85]),"+f"(d[86]),"+f"(d[87])
    :"r"(a0),"r"(a1),"r"(a2),"r"(a3),"l"(db),"r"(sc));
}
__device__ __forceinline__ void wgmma_rs_n192_t1(float (&d)[96],uint32_t a0,uint32_t a1,uint32_t a2,uint32_t a3,uint64_t db,int sc){
  asm volatile("{\n.reg .pred p;\nsetp.ne.b32 p,%101,0;\n"
    "wgmma.mma_async.sync.aligned.m64n192k16.f32.bf16.bf16 {%0,%1,%2,%3,%4,%5,%6,%7,%8,%9,%10,%11,%12,%13,%14,%15,%16,%17,%18,%19,%20,%21,%22,%23,%24,%25,%26,%27,%28,%29,%30,%31,%32,%33,%34,%35,%36,%37,%38,%39,%40,%41,%42,%43,%44,%45,%46,%47,%48,%49,%50,%51,%52,%53,%54,%55,%56,%57,%58,%59,%60,%61,%62,%63,%64,%65,%66,%67,%68,%69,%70,%71,%72,%73,%74,%75,%76,%77,%78,%79,%80,%81,%82,%83,%84,%85,%86,%87,%88,%89,%90,%91,%92,%93,%94,%95},{%96,%97,%98,%99},%100,p,1,1,1;\n}\n"
    :"+f"(d[0]),"+f"(d[1]),"+f"(d[2]),"+f"(d[3]),"+f"(d[4]),"+f"(d[5]),"+f"(d[6]),"+f"(d[7]),"+f"(d[8]),"+f"(d[9]),"+f"(d[10]),"+f"(d[11]),"+f"(d[12]),"+f"(d[13]),"+f"(d[14]),"+f"(d[15]),"+f"(d[16]),"+f"(d[17]),"+f"(d[18]),"+f"(d[19]),"+f"(d[20]),"+f"(d[21]),"+f"(d[22]),"+f"(d[23]),"+f"(d[24]),"+f"(d[25]),"+f"(d[26]),"+f"(d[27]),"+f"(d[28]),"+f"(d[29]),"+f"(d[30]),"+f"(d[31]),"+f"(d[32]),"+f"(d[33]),"+f"(d[34]),"+f"(d[35]),"+f"(d[36]),"+f"(d[37]),"+f"(d[38]),"+f"(d[39]),"+f"(d[40]),"+f"(d[41]),"+f"(d[42]),"+f"(d[43]),"+f"(d[44]),"+f"(d[45]),"+f"(d[46]),"+f"(d[47]),"+f"(d[48]),"+f"(d[49]),"+f"(d[50]),"+f"(d[51]),"+f"(d[52]),"+f"(d[53]),"+f"(d[54]),"+f"(d[55]),"+f"(d[56]),"+f"(d[57]),"+f"(d[58]),"+f"(d[59]),"+f"(d[60]),"+f"(d[61]),"+f"(d[62]),"+f"(d[63]),"+f"(d[64]),"+f"(d[65]),"+f"(d[66]),"+f"(d[67]),"+f"(d[68]),"+f"(d[69]),"+f"(d[70]),"+f"(d[71]),"+f"(d[72]),"+f"(d[73]),"+f"(d[74]),"+f"(d[75]),"+f"(d[76]),"+f"(d[77]),"+f"(d[78]),"+f"(d[79]),"+f"(d[80]),"+f"(d[81]),"+f"(d[82]),"+f"(d[83]),"+f"(d[84]),"+f"(d[85]),"+f"(d[86]),"+f"(d[87]),"+f"(d[88]),"+f"(d[89]),"+f"(d[90]),"+f"(d[91]),"+f"(d[92]),"+f"(d[93]),"+f"(d[94]),"+f"(d[95])
    :"r"(a0),"r"(a1),"r"(a2),"r"(a3),"l"(db),"r"(sc));
}
__device__ __forceinline__ void wgmma_rs_n24_t1(float (&d)[12],uint32_t a0,uint32_t a1,uint32_t a2,uint32_t a3,uint64_t db,int sc){
  asm volatile("{\n.reg .pred p;\nsetp.ne.b32 p,%17,0;\n"
    "wgmma.mma_async.sync.aligned.m64n24k16.f32.bf16.bf16 {%0,%1,%2,%3,%4,%5,%6,%7,%8,%9,%10,%11},{%12,%13,%14,%15},%16,p,1,1,1;\n}\n"
    :"+f"(d[0]),"+f"(d[1]),"+f"(d[2]),"+f"(d[3]),"+f"(d[4]),"+f"(d[5]),"+f"(d[6]),"+f"(d[7]),"+f"(d[8]),"+f"(d[9]),"+f"(d[10]),"+f"(d[11])
    :"r"(a0),"r"(a1),"r"(a2),"r"(a3),"l"(db),"r"(sc));
}
__device__ __forceinline__ void wgmma_rs_n64_t0(float (&d)[32],uint32_t a0,uint32_t a1,uint32_t a2,uint32_t a3,uint64_t db,int sc){
  asm volatile("{\n.reg .pred p;\nsetp.ne.b32 p,%37,0;\n"
    "wgmma.mma_async.sync.aligned.m64n64k16.f32.bf16.bf16 {%0,%1,%2,%3,%4,%5,%6,%7,%8,%9,%10,%11,%12,%13,%14,%15,%16,%17,%18,%19,%20,%21,%22,%23,%24,%25,%26,%27,%28,%29,%30,%31},{%32,%33,%34,%35},%36,p,1,1,0;\n}\n"
    :"+f"(d[0]),"+f"(d[1]),"+f"(d[2]),"+f"(d[3]),"+f"(d[4]),"+f"(d[5]),"+f"(d[6]),"+f"(d[7]),"+f"(d[8]),"+f"(d[9]),"+f"(d[10]),"+f"(d[11]),"+f"(d[12]),"+f"(d[13]),"+f"(d[14]),"+f"(d[15]),"+f"(d[16]),"+f"(d[17]),"+f"(d[18]),"+f"(d[19]),"+f"(d[20]),"+f"(d[21]),"+f"(d[22]),"+f"(d[23]),"+f"(d[24]),"+f"(d[25]),"+f"(d[26]),"+f"(d[27]),"+f"(d[28]),"+f"(d[29]),"+f"(d[30]),"+f"(d[31])
    :"r"(a0),"r"(a1),"r"(a2),"r"(a3),"l"(db),"r"(sc));
}
__device__ __forceinline__ void wgmma_ss_n128_t1(float (&d)[64],uint64_t da,uint64_t db,int sc){
  asm volatile("{\n.reg .pred p;\nsetp.ne.b32 p,%66,0;\n"
    "wgmma.mma_async.sync.aligned.m64n128k16.f32.bf16.bf16 {%0,%1,%2,%3,%4,%5,%6,%7,%8,%9,%10,%11,%12,%13,%14,%15,%16,%17,%18,%19,%20,%21,%22,%23,%24,%25,%26,%27,%28,%29,%30,%31,%32,%33,%34,%35,%36,%37,%38,%39,%40,%41,%42,%43,%44,%45,%46,%47,%48,%49,%50,%51,%52,%53,%54,%55,%56,%57,%58,%59,%60,%61,%62,%63},%64,%65,p,1,1,0,1;\n}\n"
    :"+f"(d[0]),"+f"(d[1]),"+f"(d[2]),"+f"(d[3]),"+f"(d[4]),"+f"(d[5]),"+f"(d[6]),"+f"(d[7]),"+f"(d[8]),"+f"(d[9]),"+f"(d[10]),"+f"(d[11]),"+f"(d[12]),"+f"(d[13]),"+f"(d[14]),"+f"(d[15]),"+f"(d[16]),"+f"(d[17]),"+f"(d[18]),"+f"(d[19]),"+f"(d[20]),"+f"(d[21]),"+f"(d[22]),"+f"(d[23]),"+f"(d[24]),"+f"(d[25]),"+f"(d[26]),"+f"(d[27]),"+f"(d[28]),"+f"(d[29]),"+f"(d[30]),"+f"(d[31]),"+f"(d[32]),"+f"(d[33]),"+f"(d[34]),"+f"(d[35]),"+f"(d[36]),"+f"(d[37]),"+f"(d[38]),"+f"(d[39]),"+f"(d[40]),"+f"(d[41]),"+f"(d[42]),"+f"(d[43]),"+f"(d[44]),"+f"(d[45]),"+f"(d[46]),"+f"(d[47]),"+f"(d[48]),"+f"(d[49]),"+f"(d[50]),"+f"(d[51]),"+f"(d[52]),"+f"(d[53]),"+f"(d[54]),"+f"(d[55]),"+f"(d[56]),"+f"(d[57]),"+f"(d[58]),"+f"(d[59]),"+f"(d[60]),"+f"(d[61]),"+f"(d[62]),"+f"(d[63])
    :"l"(da),"l"(db),"r"(sc));
}
__device__ __forceinline__ void wgmma_ss_n64_t1(float (&d)[32],uint64_t da,uint64_t db,int sc){
  asm volatile("{\n.reg .pred p;\nsetp.ne.b32 p,%34,0;\n"
    "wgmma.mma_async.sync.aligned.m64n64k16.f32.bf16.bf16 {%0,%1,%2,%3,%4,%5,%6,%7,%8,%9,%10,%11,%12,%13,%14,%15,%16,%17,%18,%19,%20,%21,%22,%23,%24,%25,%26,%27,%28,%29,%30,%31},%32,%33,p,1,1,0,1;\n}\n"
    :"+f"(d[0]),"+f"(d[1]),"+f"(d[2]),"+f"(d[3]),"+f"(d[4]),"+f"(d[5]),"+f"(d[6]),"+f"(d[7]),"+f"(d[8]),"+f"(d[9]),"+f"(d[10]),"+f"(d[11]),"+f"(d[12]),"+f"(d[13]),"+f"(d[14]),"+f"(d[15]),"+f"(d[16]),"+f"(d[17]),"+f"(d[18]),"+f"(d[19]),"+f"(d[20]),"+f"(d[21]),"+f"(d[22]),"+f"(d[23]),"+f"(d[24]),"+f"(d[25]),"+f"(d[26]),"+f"(d[27]),"+f"(d[28]),"+f"(d[29]),"+f"(d[30]),"+f"(d[31])
    :"l"(da),"l"(db),"r"(sc));
}

__device__ __forceinline__ float silu_bf(bf16 c) { const float x = __bfloat162float(c); return rbf(x / (1.f + __expf(-x))); }
__device__ __forceinline__ void fma8(float (&a)[8], float s, const uint4& v) {
  a[0] += s * blo(v.x); a[1] += s * bhi(v.x); a[2] += s * blo(v.y); a[3] += s * bhi(v.y);
  a[4] += s * blo(v.z); a[5] += s * bhi(v.z); a[6] += s * blo(v.w); a[7] += s * bhi(v.w);
}
__device__ __forceinline__ float red8(float (&a)[8], int lane) {
#pragma unroll
  for (int w = 4; w >= 1; w >>= 1) {
    const bool up = lane & (w * 4);
#pragma unroll
    for (int j = 0; j < w; j++) a[j] = (up ? a[j + w] : a[j]) + __shfl_xor_sync(~0u, up ? a[j] : a[j + w], w * 4);
  }
  return a[0];
}
__device__ __forceinline__ float mod_fin(float s, int n) { s = rbf(s); return ((n >> 9) == 1 || (n >> 9) == 4) ? rbf(1.f + s) : s; }
__device__ __forceinline__ void poll4(uint2& a, uint2& b, uint2& c, uint2& d, const uint32_t* p, const uint32_t* q) {
  asm volatile("{\n.reg .pred p;\n.reg .u32 n,t;\nmov.u32 n,0;\nLW:\nld.relaxed.gpu.global.v2.u32 {%0,%1},[%8];\nld.relaxed.gpu.global.v2.u32 {%2,%3},[%8+64];\n"
               "ld.relaxed.gpu.global.v2.u32 {%4,%5},[%9];\nld.relaxed.gpu.global.v2.u32 {%6,%7},[%9+2048];\n"
               "lop3.b32 t,%0,%1,%2,0x80;\nlop3.b32 t,t,%3,%4,0x80;\nlop3.b32 t,t,%5,%6,0x80;\nlop3.b32 t,t,%7,1,0x80;\n"
               "setp.ne.u32 p,t,0;\n@p bra LD;\nadd.u32 n,n,1;\nsetp.lt.u32 p,n,1048576;\n@p bra LW;\nLD:\n}\n"
               : "=&r"(a.x), "=&r"(a.y), "=&r"(b.x), "=&r"(b.y), "=&r"(c.x), "=&r"(c.y), "=&r"(d.x), "=&r"(d.y) : "l"(p), "l"(q) : "memory");
}

constexpr int LN_SMEM = 131072 + 4 * 24576 + 2048 + 256 + 512;
template <bool FFN>
__global__ void __cluster_dims__(2, 1, 1) __launch_bounds__(384, 1) k_lngemm(const __grid_constant__ CUtensorMap mX, const __grid_constant__ CUtensorMap mB0,
                                                   const __grid_constant__ CUtensorMap mB1, const bf16* __restrict__ cv, const bf16* __restrict__ wm, const bf16* __restrict__ xg) {
  extern __shared__ __align__(1024) uint8_t smem[];
  const uint32_t sA = smem_u32(smem), sB = sA + 131072, sM = sB + 4 * 24576, bars = sM + 2048;
  const uint32_t bA = bars, bF = bars + 64, bE = bars + 96;
  const int tid = threadIdx.x, warp = tid >> 5, lane = tid & 31;
  const int rb = blockIdx.x >> 3, ct = blockIdx.x & 7;
  constexpr int NST = FFN ? 16 : 8, KS = FFN ? 2 : 4, BOX = FFN ? 4096 : 8192;
  TS(FFN ? 4 : 1, 0);
  pdl_launch();
  float* red = (float*)(smem + (bars - sA) + 256);
  uint4 wv0, wv1, xv[4];
  bf16 cv0, cv1;
  if (!FFN && tid < 256) {
    wv0 = __ldg((const uint4*)(wm + tid * 3072 + blockIdx.x * 8)); wv1 = __ldg((const uint4*)(wm + (tid + 256) * 3072 + blockIdx.x * 8));
    cv0 = cv[tid]; cv1 = cv[tid + 256];
#pragma unroll
    for (int i = 0; i < 4; i++) xv[i] = __ldg((const uint4*)(xg + (blockIdx.x * 16 + (tid >> 4)) * 512 + i * 128 + (tid & 15) * 8));
  }
  if (tid == 256) {
    for (int i = 0; i < 8; i++) mbar_init(bA + 8 * i, 1);
    for (int i = 0; i < 4; i++) { mbar_init(bF + 8 * i, 1); mbar_init(bE + 8 * i, 8); }
    fence_init();
  }
  cluster_sync();
  if (!FFN) TS(0, 2);
  if (warp >= 8) {
    asm volatile("setmaxnreg.dec.sync.aligned.u32 40;");
    if (tid == 256) {
      auto loadB = [&](int s) {
        const uint32_t d = sB + (s & 3) * 24576, b = bF + (s & 3) * 8;
        mbar_expect(b, 24576);
        for (int j = 0; j < 3; j++) {
          if (FFN) { tma2d(d + j * BOX, &mB0, ct * 176 + j * 64, s * 32, b); tma2d(d + (3 + j) * BOX, &mB1, ct * 176 + j * 64, s * 32, b); }
          else tma2d(d + j * BOX, &mB0, ct * 192 + j * 64, s * 64, b);
        }
      };
      for (int i = 0; i < 8; i++) mbar_expect(bA + 8 * i, 16384);
      for (int s = 0; s < 4; s++) {
        const int i = s * 2 + (ct & 1);
        if (!FFN) tma2d_mc(sA + i * 16384, &mX, i * 64, rb * 128, bA + 8 * i);
        loadB(s);
      }
      if (FFN) {
        pdl_wait();
        for (int i = ct & 1; i < 8; i += 2) bulk_load_mc(sA + i * 16384, g_x1 + (rb * 64 + i * 8) * 1024, 16384, bA + 8 * i);
      }
      for (int s = 4; s < NST; s++) { mbar_wait(bE + (s & 3) * 8, ((s >> 2) - 1) & 1); loadB(s); }
    }
  } else {
  asm volatile("setmaxnreg.inc.sync.aligned.u32 232;");
  const int g = lane >> 2, t = lane & 3;
  const int lr = warp * 16 + (lane & 7) + ((lane >> 3) & 1) * 8;
  auto aaddr = [&](int ks) -> uint32_t {
    if (FFN) return sA + (ks * 2 + (lane >> 4)) * 2048 + lr * 16;
    return sA + (ks >> 2) * 16384 + lr * 128 + ((((ks & 3) * 2 + (lane >> 4)) ^ (lr & 7)) << 4);
  };
  const int row0 = rb * 128 + warp * 16 + g;
  float2 msh, msc;
  uint2 sh, sc;
  float rs0, rs1, nm0, nm1;
  if (!FFN) {
    {
      float a[8] = {0, 0, 0, 0, 0, 0, 0, 0};
      fma8(a, silu_bf(cv0), wv0); fma8(a, silu_bf(cv1), wv1);
      if (a[0] != 123.f) TS(0, 3);
      const float s = qsum(red8(a, lane));
      if (t == 0) red[warp * 8 + g] = s;
      asm volatile("bar.sync 1,256;" ::: "memory");
      if (tid < 8) {
        float r = 0;
#pragma unroll
        for (int i = 0; i < 8; i++) r += red[i * 8 + tid];
        const int n = blockIdx.x * 8 + tid;
        asm volatile("st.relaxed.gpu.global.u32 [%0],%1;" ::"l"(g_modv + n), "r"(__float_as_uint(mod_fin(r, n)) | 1u) : "memory");
      }
      TS(0, 1);
    }
    {
      float v[32], s = 0, q = 0;
#pragma unroll
      for (int i = 0; i < 16; i++) { const uint32_t u = ((const uint32_t*)xv)[i]; v[2 * i] = blo(u); v[2 * i + 1] = bhi(u); s += v[2 * i] + v[2 * i + 1]; }
      s = qsum(s); s += __shfl_xor_sync(~0u, s, 4); s += __shfl_xor_sync(~0u, s, 8);
      const float m = s * (1.f / 512);
#pragma unroll
      for (int i = 0; i < 32; i++) q += (v[i] - m) * (v[i] - m);
      q = qsum(q); q += __shfl_xor_sync(~0u, q, 4); q += __shfl_xor_sync(~0u, q, 8);
      const float rs = rsqrtf(q * (1.f / 512) + 1e-5f);
      if ((tid & 15) == 0)
        asm volatile("st.relaxed.gpu.global.v2.u32 [%0],{%1,%2};" ::"l"(g_modv + 1024 + (blockIdx.x * 16 + (tid >> 4)) * 2), "r"(__float_as_uint(rs) | 1u), "r"(__float_as_uint(-m * rs) | 1u) : "memory");
    }
    TS(0, 4);
    uint2 p0, p1;
    poll4(p0, p1, sh, sc, g_modv + 1024 + row0 * 2, g_modv + tid * 2);
    rs0 = __uint_as_float(p0.x); nm0 = __uint_as_float(p0.y); rs1 = __uint_as_float(p1.x); nm1 = __uint_as_float(p1.y);
    TS(1, 1);
  } else {
    pdl_wait();
    TS(4, 1);
    msh = *(const float2*)(g_mod + 1536 + tid * 2); msc = *(const float2*)(g_mod + 2048 + tid * 2);
    const float4 p0 = *(const float4*)(g_st + row0 * 8 + t * 2), p1 = *(const float4*)(g_st + (row0 + 8) * 8 + t * 2);
    const float m0 = qsum(p0.x + p0.z) * 0.125f, m1 = qsum(p1.x + p1.z) * 0.125f;
    const float v0 = qsum(p0.y + p0.w + 64.f * ((p0.x - m0) * (p0.x - m0) + (p0.z - m0) * (p0.z - m0)));
    const float v1 = qsum(p1.y + p1.w + 64.f * ((p1.x - m1) * (p1.x - m1) + (p1.z - m1) * (p1.z - m1)));
    rs0 = rsqrtf(v0 * (1.f / 512) + 1e-5f); rs1 = rsqrtf(v1 * (1.f / 512) + 1e-5f);
    nm0 = -m0 * rs0; nm1 = -m1 * rs1;
  }
  {
    uint32_t* m = (uint32_t*)(smem + (sM - sA)) + (tid >> 3) * 16 + (tid & 3) * 4 + ((tid >> 2) & 1);
    if (FFN) { m[0] = pack_rn(msc.x, msc.y); m[2] = pack_rn(msh.x, msh.y); }
    else { m[0] = __byte_perm(sc.x, sc.y, 0x7632); m[2] = __byte_perm(sh.x, sh.y, 0x7632); }
    asm volatile("bar.sync 1,256;" ::: "memory");
  }
  constexpr int NA = FFN ? 88 : 96;
  float acc0[NA], acc1[FFN ? 88 : 1];
  uint32_t a[2][KS][4];
  auto prep = [&](int ks, uint32_t(&o)[4]) {
    if ((ks & 3) == 0) mbar_wait(bA + 2 * ks, 0);
    uint32_t r[4]; ldsm4(aaddr(ks), r);
    const uint4 m = *(const uint4*)(smem + (sM - sA) + ks * 64 + t * 16);
#pragma unroll
    for (int i = 0; i < 4; i++) {
      const float rs = (i & 1) ? rs1 : rs0, nm = (i & 1) ? nm1 : nm0;
      const uint32_t n = pack_rn(fmaf(blo(r[i]), rs, nm), fmaf(bhi(r[i]), rs, nm));
      asm("fma.rn.bf16x2 %0,%1,%2,%3;" : "=r"(o[i]) : "r"(n), "r"(i < 2 ? m.x : m.y), "r"(i < 2 ? m.z : m.w));
    }
  };
  auto stage = [&](int s, uint32_t(&c)[KS][4], uint32_t(&n)[KS][4]) {
    mbar_wait(bF + (s & 3) * 8, (s >> 2) & 1);
    const uint64_t db = mk_desc(sB + (s & 3) * 24576, BOX, 1024, 1);
    wg_fence();
#pragma unroll
    for (int k = 0; k < KS; k++) {
      if constexpr (FFN) {
        wgmma_rs_n176_t1(acc0, c[k][0], c[k][1], c[k][2], c[k][3], db + k * 128, s + k);
        wgmma_rs_n176_t1(acc1, c[k][0], c[k][1], c[k][2], c[k][3], db + k * 128 + 3 * BOX / 16, s + k);
      } else {
        wgmma_rs_n192_t1(acc0, c[k][0], c[k][1], c[k][2], c[k][3], db + k * 128, s + k);
      }
    }
    wg_commit();
    wg_wait<1>();
    if (s > 0 && lane == 0) mbar_arrive(bE + ((s - 1) & 3) * 8);
    if (s < NST - 1) {
#pragma unroll
      for (int k = 0; k < KS; k++) prep((s + 1) * KS + k, n[k]);
    }
  };
#pragma unroll
  for (int k = 0; k < KS; k++) prep(k, a[0][k]);
  TS(FFN ? 4 : 1, 2);
#pragma unroll 1
  for (int s = 0; s < NST; s += 2) { stage(s, a[0], a[1]); stage(s + 1, a[1], a[0]); }
  wg_wait<0>();
  reg_fence(acc0);
  TS(FFN ? 4 : 1, 3);
  if constexpr (FFN) {
    reg_fence(acc1);
    uint32_t* o = (uint32_t*)g_h + ((rb * 172 + ct * 22) * 128 + warp * 16 + g) * 4 + t;
#pragma unroll
    for (int j = 0; j < 22; j++) {
      if (ct * 22 + j < 172) {
        float h[4];
#pragma unroll
        for (int i = 0; i < 4; i++) { const float x = acc0[4 * j + i]; h[i] = __fdividef(x, 1.f + ex2(-1.4426950408889634f * x)) * acc1[4 * j + i]; }
        o[j * 512] = pack_rn(h[0], h[1]);
        o[j * 512 + 32] = pack_rn(h[2], h[3]);
      }
    }
  } else {
    uint32_t* o = (uint32_t*)g_qkv + (ct * 24 * 2048 + row0) * 4 + t;
#pragma unroll
    for (int j = 0; j < 24; j += 2) {
      const int G = ct * 24 + j;
      const float sc = G < 64 ? 0.25f * 1.4426950408889634f : 1.f;
      uint32_t p[4];
#pragma unroll
      for (int i = 0; i < 4; i++) p[i] = pack_rn(acc0[4 * j + 2 * i] * sc, acc0[4 * j + 2 * i + 1] * sc);
      o[j * 8192] = p[0]; o[j * 8192 + 32] = p[1]; o[(j + 1) * 8192] = p[2]; o[(j + 1) * 8192 + 32] = p[3];
      if (G >= 64 && G < 128) {
        float n0 = blo(p[0]) * blo(p[0]) + bhi(p[0]) * bhi(p[0]) + blo(p[2]) * blo(p[2]) + bhi(p[2]) * bhi(p[2]);
        float n1 = blo(p[1]) * blo(p[1]) + bhi(p[1]) * bhi(p[1]) + blo(p[3]) * blo(p[3]) + bhi(p[3]) * bhi(p[3]);
        n0 = qsum(n0); n1 = qsum(n1);
        const uint32_t mx = __reduce_max_sync(~0u, max(__float_as_uint(n0), __float_as_uint(n1)));
        if (lane == 0) g_kmax[((G - 64) >> 1) * 128 + rb * 8 + warp] = __uint_as_float(mx);
      }
    }
  }
  TS(FFN ? 4 : 1, 4);
}
}

#define SMASK 0xAAu
#define BRK 0
#define PACK 1
#define PP 1
constexpr int AT_SMEM = 5 * 32768 + 256;
__device__ __forceinline__ uint32_t exp2_pair_fma(float s0, float s1, float c, uint32_t ka, uint32_t kz) {
  uint32_t r;
  asm volatile("{\n.reg .b32 y0,y1,e,u,t;\n"
      "fma.rn.sat.f32 y0,%1,0f00000080,%3;\nfma.rn.sat.f32 y1,%2,0f00000080,%3;\n"
      "mad.lo.u32 e,y1,65536,y0;\n"
      "and.b32 u,e,0x007F007F;\n"
      "fma.rn.f16x2 u,u,%4,%5;\nfma.rn.f16x2 t,u,u,%6;\nfma.rn.f16x2 t,t,u,%7;\n"
      "lop3.b32 %0,t,0x007F007F,e,0xE2;\n}\n"
      : "=r"(r) : "f"(s0), "f"(s1), "f"(c), "r"(ka), "r"(0x36B236B2u), "r"(0x3C733C73u), "r"(0x47764776u), "r"(kz));
  return r;
}
__device__ __forceinline__ void attn_pass(float (&oa)[12], float (&ob)[12], const uint32_t (&q)[4], float m0, float m1, uint32_t sK, uint32_t bars, bool first, uint32_t kz) {
  const uint64_t dk = mk_desc(sK, 32768, 128, 0), dv = mk_desc(sK + 65536, 128, 32768, 0);
  const float c0 = (127.f - m0) * __uint_as_float(0x80u), c1 = (127.f - m1) * __uint_as_float(0x80u);
  const uint32_t ka = 0x7ACE7ACEu + kz;
  constexpr int NK = 64, NS = 32, NP = 16, NI = 32;
  auto qk = [&](float (&s)[NS], int i) { wgmma_rs_n64_t0(s, q[0], q[1], q[2], q[3], dk + i * NK, 0); };
  auto softmax = [&](float (&s)[NS], uint32_t (&p)[NP], uint32_t mask) {
    reg_fence(s);
    float e0, e1;
    int pend = -1;
#pragma unroll
    for (int t = 0; t < NP; t++) {
      const int j = (t & 3) * 4 + (t >> 2);
      if ((mask >> (t & 3)) & 1) {
        p[j] = exp2_pair_fma(s[2 * j], s[2 * j + 1], (j & 1) ? c1 : c0, ka, kz);
      } else {
        float f0, f1;
        asm volatile("ex2.approx.ftz.f32 %0,%2;\nex2.approx.ftz.f32 %1,%3;" : "=&f"(f0), "=f"(f1) : "f"(s[2 * j]), "f"(s[2 * j + 1]));
        if (pend >= 0) asm volatile("cvt.rn.bf16x2.f32 %0,%1,%2;" : "=r"(p[pend]) : "f"(e1), "f"(e0));
        e0 = f0; e1 = f1; pend = j;
      }
    }
    if (pend >= 0) asm volatile("cvt.rn.bf16x2.f32 %0,%1,%2;" : "=r"(p[pend]) : "f"(e1), "f"(e0));
#pragma unroll
    for (int j = 0; j < NP; j++) asm volatile("" : "+r"(p[j])::"memory");
  };
  auto pv = [&](uint32_t (&p)[NP], int i, uint32_t mask) {
#pragma unroll
    for (int k = 0; k < 4; k++) wgmma_rs_n24_t1(((mask >> k) & 1) ? ob : oa, p[4 * k], p[4 * k + 1], p[4 * k + 2], p[4 * k + 3], dv + i * NK + k * 16, 1);
  };
  auto ld = [&](int i) { if (first && (i & 3) == 0) mbar_wait(bars + i * 2, 0); };
  constexpr uint32_t M0 = SMASK & 15, M1 = SMASK >> 4;
  zero(oa); zero(ob);
  ld(0);
  if (first) TS(2, 2);
  float s[NS];
  zero(s);
  uint32_t p0[NP], p1[NP];
  wg_fence(); qk(s, 0); wg_commit(); wg_wait<0>(); softmax(s, p0, M0);
#pragma unroll 1
  for (int i = 0; i < NI - 2; i += 2) {
    wg_fence(); qk(s, i + 1); wg_commit(); pv(p0, i, M0); wg_commit(); wg_wait<1>(); softmax(s, p1, M1); wg_wait<0>();
    ld(i + 2);
    wg_fence(); qk(s, i + 2); wg_commit(); pv(p1, i + 1, M1); wg_commit(); wg_wait<1>(); softmax(s, p0, M0); wg_wait<0>();
  }
  wg_fence(); qk(s, NI - 1); wg_commit(); pv(p0, NI - 2, M0); wg_commit(); wg_wait<1>(); softmax(s, p1, M1); wg_wait<0>();
  wg_fence(); pv(p1, NI - 1, M1); wg_commit();
  wg_wait<0>();
  reg_fence(oa); reg_fence(ob);
}
__device__ __forceinline__ void mma16816(float (&d)[4], const uint32_t (&a)[4], uint32_t b0, uint32_t b1) {
  asm("mma.sync.aligned.m16n8k16.row.col.f32.bf16.bf16.f32 {%0,%1,%2,%3},{%4,%5,%6,%7},{%8,%9},{%0,%1,%2,%3};"
      : "+f"(d[0]), "+f"(d[1]), "+f"(d[2]), "+f"(d[3]) : "r"(a[0]), "r"(a[1]), "r"(a[2]), "r"(a[3]), "r"(b0), "r"(b1));
}
__device__ __forceinline__ void attn_safe(float (&o)[12], const uint32_t (&q)[4], uint32_t sK) {
  const int lane = threadIdx.x & 31;
  const uint32_t ka = sK + (lane >> 4) * 32768 + (lane & 15) * 16;
  float m0 = -INFINITY, m1 = -INFINITY;
#pragma unroll 2
  for (int i = 0; i < 128; i++) {
    uint32_t k[4]; ldsm4(ka + i * 256, k);
    float s0[4] = {0, 0, 0, 0}, s1[4] = {0, 0, 0, 0};
    mma16816(s0, q, k[0], k[2]); mma16816(s1, q, k[1], k[3]);
    m0 = fmaxf(fmaxf(m0, fmaxf(s0[0], s0[1])), fmaxf(s1[0], s1[1])); m1 = fmaxf(fmaxf(m1, fmaxf(s0[2], s0[3])), fmaxf(s1[2], s1[3]));
  }
  m0 = fmaxf(m0, __shfl_xor_sync(~0u, m0, 1)); m0 = fmaxf(m0, __shfl_xor_sync(~0u, m0, 2));
  m1 = fmaxf(m1, __shfl_xor_sync(~0u, m1, 1)); m1 = fmaxf(m1, __shfl_xor_sync(~0u, m1, 2));
  float o0[4] = {0, 0, 0, 0}, o1[4] = {0, 0, 0, 0}, o2[4] = {0, 0, 0, 0};
#pragma unroll 2
  for (int i = 0; i < 128; i++) {
    uint32_t k[4], v[4]; ldsm4(ka + i * 256, k);
    asm volatile("ldmatrix.sync.aligned.m8n8.x4.trans.shared.b16 {%0,%1,%2,%3},[%4];" : "=r"(v[0]), "=r"(v[1]), "=r"(v[2]), "=r"(v[3]) : "r"(ka + 65536 + i * 256) : "memory");
    float s0[4] = {0, 0, 0, 0}, s1[4] = {0, 0, 0, 0};
    mma16816(s0, q, k[0], k[2]); mma16816(s1, q, k[1], k[3]);
    const uint32_t p[4] = {pack_rn(ex2(s0[0] - m0), ex2(s0[1] - m0)), pack_rn(ex2(s0[2] - m1), ex2(s0[3] - m1)),
                           pack_rn(ex2(s1[0] - m0), ex2(s1[1] - m0)), pack_rn(ex2(s1[2] - m1), ex2(s1[3] - m1))};
    mma16816(o0, p, v[0], v[1]); mma16816(o1, p, v[2], v[3]); mma16816(o2, p, 0x3F803F80u, 0x3F803F80u);
  }
#pragma unroll
  for (int i = 0; i < 4; i++) { o[i] = o0[i]; o[4 + i] = o1[i]; o[8 + i] = o2[i]; }
}
__global__ void __cluster_dims__(2, 1, 1) __launch_bounds__(512, 1) k_attn(const bf16* wo, const bf16* w1, const bf16* w3, const bf16* w2, const bf16* __restrict__ cv, const bf16* __restrict__ wm, uint32_t kz) {
  extern __shared__ __align__(1024) uint8_t smem[];
  const uint32_t sK = smem_u32(smem), bars = sK + 5 * 32768;
  const int tid = threadIdx.x, warp = tid >> 5, lane = tid & 31, g = lane >> 2, t = lane & 3;
  pdl_launch();
  if (blockIdx.x < 4) {
    float* cs = (float*)smem;
    cs[tid] = silu_bf(cv[tid]);
    __syncthreads();
    const int n0 = 1024 + blockIdx.x * 512, r0 = (tid >> 6) * 64;
    float a[8] = {0, 0, 0, 0, 0, 0, 0, 0};
#pragma unroll 16
    for (int r = r0; r < r0 + 64; r++) fma8(a, cs[r], __ldg((const uint4*)(wm + r * 3072 + n0 + (tid & 63) * 8)));
    float4* rp = (float4*)(cs + 512 + tid * 8);
    rp[0] = make_float4(a[0], a[1], a[2], a[3]); rp[1] = make_float4(a[4], a[5], a[6], a[7]);
    __syncthreads();
    float s = 0;
#pragma unroll
    for (int i = 0; i < 8; i++) s += cs[512 + i * 512 + tid];
    g_mod[n0 + tid] = mod_fin(s, n0 + tid);
    return;
  }
  const int bid = blockIdx.x - 4, h = bid >> 2, qb = bid & 3;
  TS(2, 0);
  if (tid == 0) { for (int i = 0; i < 8; i++) { mbar_init(bars + 8 * i, 1); mbar_expect(bars + 8 * i, 16384); } fence_init(); }
#pragma unroll
  for (int i = 0; i < 4; i++) *(uint4*)(smem + 131072 + i * 8192 + tid * 16) = make_uint4(0x3F803F80u, 0x3F803F80u, 0x3F803F80u, 0x3F803F80u);
  fence_async();
  cluster_sync();
  pdl_wait();
  TS(2, 1);
  if (tid >= 472) g_modv[bid * 40 + tid - 472] = 0;
  if (tid == 0) {
    for (int c = 0; c < 8; c++)
      for (int pl = qb & 1; pl < 4; pl += 2)
        bulk_load_mc(sK + pl * 32768 + c * 4096, g_qkv + ((64 + (pl >> 1) * 64 + h * 2 + (pl & 1)) * 2048 + c * 256) * 8, 4096, bars + 8 * c);
  }
  if (tid == 32) {
    l2_prefetch((const char*)wo + bid * 4096, 4096);
    l2_prefetch((const char*)w1 + bid * 11008, 11008);
    l2_prefetch((const char*)w3 + bid * 11008, 11008);
    l2_prefetch((const char*)w2 + bid * 11008, 11008);
  }
  const uint4 km4 = *(const uint4*)(g_kmax + h * 128 + lane * 4);
  const float kmax = __uint_as_float(__reduce_max_sync(~0u, max(max(km4.x, km4.y), max(km4.z, km4.w))));
#pragma unroll 1
  for (int tile = 0; tile < 2; tile++) {
    const int row = qb * 512 + tile * 256 + warp * 16 + g;
    const uint32_t* qp = (const uint32_t*)g_qkv + (h * 2 * 2048 + row) * 4 + t;
    uint32_t q[4] = {qp[0], qp[32], qp[8192], qp[8192 + 32]};
    const float n0 = qsum(blo(q[0]) * blo(q[0]) + bhi(q[0]) * bhi(q[0]) + blo(q[2]) * blo(q[2]) + bhi(q[2]) * bhi(q[2]));
    const float n1 = qsum(blo(q[1]) * blo(q[1]) + bhi(q[1]) * bhi(q[1]) + blo(q[3]) * blo(q[3]) + bhi(q[3]) * bhi(q[3]));
    const float b0 = sqrtf(n0 * kmax) * 1.001f, b1 = sqrtf(n1 * kmax) * 1.001f;
    const float m0 = fmaxf(ceilf(b0 - 100.f), 0.f), m1 = fmaxf(ceilf(b1 - 100.f), 0.f);
    float o[12], ob[12];
    attn_pass(o, ob, q, m0, m1, sK, bars, tile == 0, kz);
    const float f0 = ex2(-m0), f1 = ex2(-m1);
#pragma unroll
    for (int i = 0; i < 12; i++) o[i] = fmaf(o[i], (i & 2) ? f1 : f0, ob[i]);
    bool ok = b0 < 220.f && b1 < 220.f && o[8] >= 0x1p-90f && o[10] >= 0x1p-90f;
#pragma unroll
    for (int i = 0; i < 12; i++) ok = ok && fabsf(o[i]) < INFINITY;
    if (!__all_sync(~0u, ok)) attn_safe(o, q, sK);
    const float r0 = 1.f / o[8], r1 = 1.f / o[10];
    uint32_t* op = (uint32_t*)g_o + (((row >> 7) * 64 + h * 2) * 128 + (row & 127)) * 4 + t;
    op[0] = pack_rn(o[0] * r0, o[1] * r0); op[32] = pack_rn(o[2] * r1, o[3] * r1);
    op[512] = pack_rn(o[4] * r0, o[5] * r0); op[512 + 32] = pack_rn(o[6] * r1, o[7] * r1);
    TS(2, 3 + tile);
  }
}

constexpr int WO_SMEM = 131072 + 65536 + 256;
__global__ void __cluster_dims__(2, 1, 1) __launch_bounds__(256, 1) k_wo(const __grid_constant__ CUtensorMap mW, const bf16* __restrict__ x) {
  extern __shared__ __align__(1024) uint8_t smem[];
  const uint32_t sA = smem_u32(smem), sB = sA + 131072, bars = sB + 65536;
  const int tid = threadIdx.x, warp = tid >> 5, lane = tid & 31, g = lane >> 2, t = lane & 3;
  const int rb = blockIdx.x >> 3, ct = blockIdx.x & 7;
  TS(3, 0);
  pdl_launch();
  if (tid == 0) {
    for (int i = 0; i < 8; i++) mbar_init(bars + 8 * i, 1);
    fence_init();
    for (int i = 0; i < 8; i++) { mbar_expect(bars + 8 * i, 24576); tma2d(sB + i * 8192, &mW, ct * 64, i * 64, bars + 8 * i); }
  }
  const int lrow = warp * 16 + g;
  uint32_t xr[16];
  const uint32_t* xp = (const uint32_t*)(x + (rb * 128 + lrow) * 512 + ct * 64) + t;
#pragma unroll
  for (int j = 0; j < 8; j++) { xr[2 * j] = __ldg(xp + j * 4); xr[2 * j + 1] = __ldg(xp + j * 4 + 8 * 256); }
  cluster_sync();
  pdl_wait();
  TS(3, 1);
  if (tid == 0) for (int i = ct & 1; i < 8; i += 2) bulk_load_mc(sA + i * 16384, g_o + (rb * 64 + i * 8) * 1024, 16384, bars + 8 * i);
  float2 ga[8];
#pragma unroll
  for (int j = 0; j < 8; j++) ga[j] = *(const float2*)(g_mod + 1024 + ct * 64 + j * 8 + t * 2);
  float acc[32];
  const uint64_t da = mk_desc(sA + (warp >> 2) * 1024, 2048, 128, 0), db = mk_desc(sB, 8192, 1024, 1);
#pragma unroll
  for (int c = 0; c < 8; c++) {
    mbar_wait(bars + 8 * c, 0);
    if (c == 0) TS(3, 2);
    wg_fence();
#pragma unroll
    for (int k = 0; k < 4; k++) wgmma_ss_n64_t1(acc, da + (c * 4 + k) * 256, db + (c * 4 + k) * 128, c + k);
    wg_commit();
  }
  wg_wait<0>();
  reg_fence(acc);
  TS(3, 3);
  uint32_t* o = (uint32_t*)g_x1 + ((rb * 64 + ct * 8) * 128 + lrow) * 4 + t;
  float s0 = 0, s1 = 0;
#pragma unroll
  for (int j = 0; j < 8; j++) {
    xr[2 * j] = pack_rn(fmaf(ga[j].x, acc[4 * j], blo(xr[2 * j])), fmaf(ga[j].y, acc[4 * j + 1], bhi(xr[2 * j])));
    xr[2 * j + 1] = pack_rn(fmaf(ga[j].x, acc[4 * j + 2], blo(xr[2 * j + 1])), fmaf(ga[j].y, acc[4 * j + 3], bhi(xr[2 * j + 1])));
    o[j * 512] = xr[2 * j]; o[j * 512 + 32] = xr[2 * j + 1];
    s0 += blo(xr[2 * j]) + bhi(xr[2 * j]); s1 += blo(xr[2 * j + 1]) + bhi(xr[2 * j + 1]);
  }
  const float m0 = qsum(s0) * (1.f / 64), m1 = qsum(s1) * (1.f / 64);
  float v0 = 0, v1 = 0;
#pragma unroll
  for (int j = 0; j < 8; j++) {
    float d;
    d = blo(xr[2 * j]) - m0; v0 += d * d; d = bhi(xr[2 * j]) - m0; v0 += d * d;
    d = blo(xr[2 * j + 1]) - m1; v1 += d * d; d = bhi(xr[2 * j + 1]) - m1; v1 += d * d;
  }
  v0 = qsum(v0); v1 = qsum(v1);
  if (t == 0) g_st[(rb * 128 + lrow) * 8 + ct] = make_float2(m0, v0);
  if (t == 1) g_st[(rb * 128 + lrow + 8) * 8 + ct] = make_float2(m1, v1);
  TS(3, 4);
}

constexpr int W2_SMEM = 6 * 32768 + 32768 + 256;
__global__ void __cluster_dims__(2, 1, 1) __launch_bounds__(288, 1) k_w2(const __grid_constant__ CUtensorMap mW, bf16* __restrict__ out) {
  extern __shared__ __align__(1024) uint8_t smem[];
  const uint32_t sR = smem_u32(smem), sX = sR + 6 * 32768, bF = sX + 32768, bE = bF + 48;
  const int tid = threadIdx.x, warp = tid >> 5, lane = tid & 31, g = lane >> 2, t = lane & 3;
  const int kh = blockIdx.x & 1, ct = (blockIdx.x >> 1) & 3, rb = blockIdx.x >> 3;
  TS(5, 0);
  pdl_launch();
  if (tid == 256) {
    for (int i = 0; i < 6; i++) { mbar_init(bF + 8 * i, 1); mbar_init(bE + 8 * i, 8); }
    fence_init();
  }
  __syncthreads();
  asm volatile("barrier.cluster.arrive.relaxed.aligned;" ::: "memory");
  if (warp == 8) {
    if (lane == 0) {
      auto abytes = [&](int s) { return (kh == 1 && s == 10) ? 8192 : 16384; };
      auto loadB = [&](int s) {
        const int st = s % 6;
        mbar_expect(bF + 8 * st, 16384 + abytes(s));
        for (int j = 0; j < 2; j++) tma2d(sR + st * 32768 + 16384 + j * 8192, &mW, ct * 128 + j * 64, kh * 704 + s * 64, bF + 8 * st);
      };
      auto loadA = [&](int s) { bulk_load(sR + (s % 6) * 32768, g_h + (rb * 172 + kh * 88 + s * 8) * 1024, abytes(s), bF + 8 * (s % 6)); };
      for (int s = 0; s < 6; s++) loadB(s);
      pdl_wait();
      for (int s = 0; s < 6; s++) loadA(s);
      for (int s = 6; s < 11; s++) { mbar_wait(bE + 8 * (s - 6), 0); loadB(s); loadA(s); }
    }
    __syncwarp();
    asm volatile("barrier.cluster.wait.aligned;" ::: "memory");
    asm volatile("barrier.cluster.arrive.release.aligned;" ::: "memory");
    asm volatile("barrier.cluster.wait.acquire.aligned;" ::: "memory");
    return;
  }
  pdl_wait();
  TS(5, 1);
  const int lrow = warp * 16 + g;
  uint32_t xr[16];
  float2 gb[8];
  const uint32_t* xp = (const uint32_t*)g_x1 + ((rb * 64 + ct * 16 + kh * 8) * 128 + lrow) * 4 + t;
#pragma unroll
  for (int j = 0; j < 8; j++) {
    xr[2 * j] = xp[j * 512]; xr[2 * j + 1] = xp[j * 512 + 32];
    gb[j] = *(const float2*)(g_mod + 2560 + ct * 128 + kh * 64 + j * 8 + t * 2);
  }
  float acc[64];
#pragma unroll 1
  for (int s = 0; s < 11; s++) {
    const int st = s % 6;
    mbar_wait(bF + 8 * st, s >= 6);
    const uint64_t da = mk_desc(sR + st * 32768 + (warp >> 2) * 1024, 2048, 128, 0), db = mk_desc(sR + st * 32768 + 16384, 8192, 1024, 1);
    if (s == 0) TS(5, 2);
    wg_fence();
    wgmma_ss_n128_t1(acc, da, db, s);
    wgmma_ss_n128_t1(acc, da + 256, db + 128, 1);
    wgmma_ss_n128_t1(acc, da + 512, db + 256, 1);
    wgmma_ss_n128_t1(acc, da + 768, db + 384, 1);
    wg_commit();
    wg_wait<1>();
    if (s > 0 && s < 6 && lane == 0) mbar_arrive(bE + 8 * (s - 1));
  }
  wg_wait<0>();
  reg_fence(acc);
  TS(5, 3);
  asm volatile("barrier.cluster.wait.aligned;" ::: "memory");
  uint32_t rem;
  asm("mapa.shared::cluster.u32 %0,%1,%2;" : "=r"(rem) : "r"(sX + tid * 16), "r"(kh ^ 1));
#pragma unroll
  for (int j = 0; j < 8; j++) {
    float v[4];
#pragma unroll
    for (int i = 0; i < 4; i++) { v[i] = kh ? acc[4 * j + i] : acc[32 + 4 * j + i]; acc[4 * j + i] = kh ? acc[32 + 4 * j + i] : acc[4 * j + i]; }
    asm volatile("st.shared::cluster.v4.f32 [%0],{%1,%2,%3,%4};" ::"r"(rem + j * 4096), "f"(v[0]), "f"(v[1]), "f"(v[2]), "f"(v[3]) : "memory");
  }
  asm volatile("barrier.cluster.arrive.release.aligned;" ::: "memory");
  asm volatile("barrier.cluster.wait.acquire.aligned;" ::: "memory");
  uint32_t* o = (uint32_t*)(out + (rb * 128 + lrow) * 512 + ct * 128 + kh * 64) + t;
#pragma unroll
  for (int j = 0; j < 8; j++) {
    const float4 p = *(const float4*)(smem + 6 * 32768 + j * 4096 + tid * 16);
    o[j * 4] = pack_rn(fmaf(gb[j].x, acc[4 * j] + p.x, blo(xr[2 * j])), fmaf(gb[j].y, acc[4 * j + 1] + p.y, bhi(xr[2 * j])));
    o[j * 4 + 2048] = pack_rn(fmaf(gb[j].x, acc[4 * j + 2] + p.z, blo(xr[2 * j + 1])), fmaf(gb[j].y, acc[4 * j + 3] + p.w, bhi(xr[2 * j + 1])));
  }
  TS(5, 4);
}

typedef CUresult (*EncFn)(CUtensorMap*, CUtensorMapDataType, cuuint32_t, void*, const cuuint64_t*, const cuuint64_t*, const cuuint32_t*,
                          const cuuint32_t*, CUtensorMapInterleave, CUtensorMapSwizzle, CUtensorMapL2promotion, CUtensorMapFloatOOBfill);
static void mk_map(EncFn f, CUtensorMap* m, const void* p, int rows, int cols, int box_rows) {
  cuuint64_t dim[2] = {(cuuint64_t)cols, (cuuint64_t)rows}, str[1] = {(cuuint64_t)cols * 2};
  cuuint32_t box[2] = {64, (cuuint32_t)box_rows}, es[2] = {1, 1};
  f(m, CU_TENSOR_MAP_DATA_TYPE_BFLOAT16, 2, (void*)p, dim, str, box, es, CU_TENSOR_MAP_INTERLEAVE_NONE, CU_TENSOR_MAP_SWIZZLE_128B,
    CU_TENSOR_MAP_L2_PROMOTION_L2_128B, CU_TENSOR_MAP_FLOAT_OOB_FILL_NONE);
}
template <typename... KA, typename... A>
static void launch(void (*k)(KA...), int grid, int block, int smem, bool pdl, A... args) {
  cudaLaunchConfig_t cfg = {};
  cfg.gridDim = dim3(grid); cfg.blockDim = dim3(block); cfg.dynamicSmemBytes = smem; cfg.stream = cudaStreamPerThread;
  cudaLaunchAttribute at[1];
  at[0].id = cudaLaunchAttributeProgrammaticStreamSerialization; at[0].val.programmaticStreamSerializationAllowed = 1;
  cfg.attrs = at; cfg.numAttrs = pdl ? 1 : 0;
  cudaLaunchKernelEx(&cfg, k, args...);
}
extern "C" void kernel_launch(void* const* d_in, const int* in_sizes, int n_in, void* d_out, int out_size) {
  const bf16 *x = (const bf16*)d_in[0], *wqkv = (const bf16*)d_in[1], *wo = (const bf16*)d_in[2], *w1 = (const bf16*)d_in[4],
             *w3 = (const bf16*)d_in[5], *w2 = (const bf16*)d_in[6], *c = (const bf16*)d_in[7], *wmod = (const bf16*)d_in[8];
  void* fp = nullptr;
  cudaDriverEntryPointQueryResult qr;
  cudaGetDriverEntryPoint("cuTensorMapEncodeTiled", &fp, cudaEnableDefault, &qr);
  EncFn f = (EncFn)fp;
  CUtensorMap mX, mQ, mO, m1, m3, m2;
  mk_map(f, &mX, x, S_, D_, 128); mk_map(f, &mQ, wqkv, D_, 3 * D_, 64); mk_map(f, &mO, wo, D_, D_, 64);
  mk_map(f, &m1, w1, D_, F_, 32); mk_map(f, &m3, w3, D_, F_, 32); mk_map(f, &m2, w2, F_, D_, 64);
  cudaFuncSetAttribute(k_lngemm<false>, cudaFuncAttributeMaxDynamicSharedMemorySize, LN_SMEM);
  cudaFuncSetAttribute(k_lngemm<true>, cudaFuncAttributeMaxDynamicSharedMemorySize, LN_SMEM);
  cudaFuncSetAttribute(k_attn, cudaFuncAttributeMaxDynamicSharedMemorySize, AT_SMEM);
  cudaFuncSetAttribute(k_wo, cudaFuncAttributeMaxDynamicSharedMemorySize, WO_SMEM);
  cudaFuncSetAttribute(k_w2, cudaFuncAttributeMaxDynamicSharedMemorySize, W2_SMEM);
  launch(k_lngemm<false>, 128, 384, LN_SMEM, false, mX, mQ, mQ, c, wmod, x);
  launch(k_attn, 132, 512, AT_SMEM, true, wo, w1, w3, w2, c, wmod, 0u);
  launch(k_wo, 128, 256, WO_SMEM, true, mO, x);
  launch(k_lngemm<true>, 128, 384, LN_SMEM, true, mX, m1, m3, c, wmod, x);
  launch(k_w2, 128, 288, W2_SMEM, true, m2, (bf16*)d_out);
}
```

```cpp
#include <cuda_runtime.h>
#include <cuda_bf16.h>
#include <cuda.h>
#include <stdint.h>
typedef __nv_bfloat16 bf16;
constexpr int S_ = 2048, D_ = 512, F_ = 1376;
__device__ __align__(1024) float g_mod[3072];
__device__ __align__(1024) uint32_t g_modv[1024 + 4096];
__device__ __align__(1024) bf16 g_qkv[192 * 2048 * 8];
__device__ __align__(1024) float g_kmax[32 * 128];
__device__ __align__(1024) bf16 g_o[16 * 64 * 128 * 8];
__device__ __align__(1024) bf16 g_x1[16 * 64 * 128 * 8];
__device__ __align__(1024) float2 g_st[2048 * 8];
__device__ __align__(1024) bf16 g_h[16 * 172 * 128 * 8];

__device__ __forceinline__ uint32_t smem_u32(const void* p) { return (uint32_t)__cvta_generic_to_shared(p); }
__device__ __forceinline__ void mbar_init(uint32_t b, int n) { asm volatile("mbarrier.init.shared::cta.b64 [%0],%1;" ::"r"(b), "r"(n) : "memory"); }
__device__ __forceinline__ void mbar_expect(uint32_t b, int bytes) { asm volatile("mbarrier.arrive.expect_tx.shared::cta.b64 _,[%0],%1;" ::"r"(b), "r"(bytes) : "memory"); }
__device__ __forceinline__ void mbar_arrive(uint32_t b) { asm volatile("mbarrier.arrive.shared::cta.b64 _,[%0];" ::"r"(b) : "memory"); }
__device__ __forceinline__ void mbar_wait(uint32_t b, int parity) {
  asm volatile("{\n.reg .pred p;\n.reg .u32 n;\nmov.u32 n,0;\nLW:\nmbarrier.try_wait.parity.shared::cta.b64 p,[%0],%1;\n@p bra LD;\n"
               "add.u32 n,n,1;\nsetp.lt.u32 p,n,4194304;\n@p bra LW;\nLD:\n}\n" ::"r"(b), "r"(parity) : "memory");
}
__device__ __forceinline__ void fence_init() { asm volatile("fence.mbarrier_init.release.cluster;" ::: "memory"); }
__device__ __forceinline__ void fence_async() { asm volatile("fence.proxy.async.shared::cta;" ::: "memory"); }
__device__ __forceinline__ void bulk_load(uint32_t dst, const void* src, int bytes, uint32_t bar) {
  asm volatile("cp.async.bulk.shared::cluster.global.mbarrier::complete_tx::bytes [%0],[%1],%2,[%3];" ::"r"(dst), "l"(src), "r"(bytes), "r"(bar) : "memory");
}
__device__ __forceinline__ void tma2d(uint32_t dst, const CUtensorMap* m, int c0, int c1, uint32_t bar) {
  asm volatile("cp.async.bulk.tensor.2d.shared::cluster.global.mbarrier::complete_tx::bytes [%0],[%1,{%3,%4}],[%2];" ::"r"(dst), "l"(m), "r"(bar), "r"(c0), "r"(c1) : "memory");
}
__device__ __forceinline__ void bulk_load_mc(uint32_t dst, const void* src, int bytes, uint32_t bar) {
  asm volatile("cp.async.bulk.shared::cluster.global.mbarrier::complete_tx::bytes.multicast::cluster [%0],[%1],%2,[%3],%4;" ::"r"(dst), "l"(src), "r"(bytes), "r"(bar), "h"((uint16_t)3) : "memory");
}
__device__ __forceinline__ void tma2d_mc(uint32_t dst, const CUtensorMap* m, int c0, int c1, uint32_t bar) {
  asm volatile("cp.async.bulk.tensor.2d.shared::cluster.global.mbarrier::complete_tx::bytes.multicast::cluster [%0],[%1,{%3,%4}],[%2],%5;" ::"r"(dst), "l"(m), "r"(bar), "r"(c0), "r"(c1), "h"((uint16_t)3) : "memory");
}
__device__ __forceinline__ void cluster_arrive() { asm volatile("barrier.cluster.arrive.relaxed.aligned;" ::: "memory"); }
__device__ __forceinline__ void cluster_wait() { asm volatile("barrier.cluster.wait.aligned;" ::: "memory"); }
__device__ __forceinline__ void cluster_sync() { asm volatile("barrier.cluster.arrive.release.aligned;\nbarrier.cluster.wait.acquire.aligned;" ::: "memory"); }
__device__ __forceinline__ void l2_prefetch(const void* p, int bytes) { asm volatile("cp.async.bulk.prefetch.L2.global [%0],%1;" ::"l"(p), "r"(bytes) : "memory"); }
__device__ __forceinline__ void pdl_launch() { asm volatile("griddepcontrol.launch_dependents;" ::: "memory"); }
__device__ __forceinline__ void pdl_wait() { asm volatile("griddepcontrol.wait;" ::: "memory"); }
__device__ __forceinline__ void wg_fence() { asm volatile("wgmma.fence.sync.aligned;" ::: "memory"); }
__device__ __forceinline__ void wg_commit() { asm volatile("wgmma.commit_group.sync.aligned;" ::: "memory"); }
template <int N> __device__ __forceinline__ void wg_wait() { asm volatile("wgmma.wait_group.sync.aligned %0;" ::"n"(N) : "memory"); }
template <int N> __device__ __forceinline__ void reg_fence(float (&d)[N]) {
#pragma unroll
  for (int i = 0; i < N; i++) asm volatile("" : "+f"(d[i])::"memory");
}
template <int N> __device__ __forceinline__ void zero(float (&d)[N]) {
#pragma unroll
  for (int i = 0; i < N; i++) d[i] = 0.f;
  reg_fence(d);
}
__device__ __forceinline__ uint64_t mk_desc(uint32_t addr, uint32_t lbo, uint32_t sbo, uint32_t mode) {
  return (uint64_t)((addr >> 4) & 0x3FFF) | ((uint64_t)(lbo >> 4) << 16) | ((uint64_t)(sbo >> 4) << 32) | ((uint64_t)mode << 62);
}
__device__ __forceinline__ void ldsm4(uint32_t a, uint32_t (&r)[4]) {
  asm volatile("ldmatrix.sync.aligned.m8n8.x4.shared.b16 {%0,%1,%2,%3},[%4];" : "=r"(r[0]), "=r"(r[1]), "=r"(r[2]), "=r"(r[3]) : "r"(a) : "memory");
}
__device__ __forceinline__ uint32_t pack_rn(float lo, float hi) { uint32_t r; asm("cvt.rn.bf16x2.f32 %0,%1,%2;" : "=r"(r) : "f"(hi), "f"(lo)); return r; }
__device__ __forceinline__ uint32_t pack_rz(float lo, float hi) { uint32_t r; asm("cvt.rz.bf16x2.f32 %0,%1,%2;" : "=r"(r) : "f"(hi), "f"(lo)); return r; }
__device__ __forceinline__ float blo(uint32_t u) { return __uint_as_float(u << 16); }
__device__ __forceinline__ float bhi(uint32_t u) { return __uint_as_float(u & 0xFFFF0000u); }
__device__ __forceinline__ float rbf(float x) { return __bfloat162float(__float2bfloat16_rn(x)); }
__device__ __forceinline__ float qsum(float v) { v += __shfl_xor_sync(~0u, v, 1); return v + __shfl_xor_sync(~0u, v, 2); }
__device__ __forceinline__ float ex2(float x) { float r; asm("ex2.approx.ftz.f32 %0,%1;" : "=f"(r) : "f"(x)); return r; }
#define TS(k, i)
__device__ __forceinline__ void wgmma_rs_n176_t1(float (&d)[88],uint32_t a0,uint32_t a1,uint32_t a2,uint32_t a3,uint64_t db,int sc){
  asm volatile("{\n.reg .pred p;\nsetp.ne.b32 p,%93,0;\n"
    "wgmma.mma_async.sync.aligned.m64n176k16.f32.bf16.bf16 {%0,%1,%2,%3,%4,%5,%6,%7,%8,%9,%10,%11,%12,%13,%14,%15,%16,%17,%18,%19,%20,%21,%22,%23,%24,%25,%26,%27,%28,%29,%30,%31,%32,%33,%34,%35,%36,%37,%38,%39,%40,%41,%42,%43,%44,%45,%46,%47,%48,%49,%50,%51,%52,%53,%54,%55,%56,%57,%58,%59,%60,%61,%62,%63,%64,%65,%66,%67,%68,%69,%70,%71,%72,%73,%74,%75,%76,%77,%78,%79,%80,%81,%82,%83,%84,%85,%86,%87},{%88,%89,%90,%91},%92,p,1,1,1;\n}\n"
    :"+f"(d[0]),"+f"(d[1]),"+f"(d[2]),"+f"(d[3]),"+f"(d[4]),"+f"(d[5]),"+f"(d[6]),"+f"(d[7]),"+f"(d[8]),"+f"(d[9]),"+f"(d[10]),"+f"(d[11]),"+f"(d[12]),"+f"(d[13]),"+f"(d[14]),"+f"(d[15]),"+f"(d[16]),"+f"(d[17]),"+f"(d[18]),"+f"(d[19]),"+f"(d[20]),"+f"(d[21]),"+f"(d[22]),"+f"(d[23]),"+f"(d[24]),"+f"(d[25]),"+f"(d[26]),"+f"(d[27]),"+f"(d[28]),"+f"(d[29]),"+f"(d[30]),"+f"(d[31]),"+f"(d[32]),"+f"(d[33]),"+f"(d[34]),"+f"(d[35]),"+f"(d[36]),"+f"(d[37]),"+f"(d[38]),"+f"(d[39]),"+f"(d[40]),"+f"(d[41]),"+f"(d[42]),"+f"(d[43]),"+f"(d[44]),"+f"(d[45]),"+f"(d[46]),"+f"(d[47]),"+f"(d[48]),"+f"(d[49]),"+f"(d[50]),"+f"(d[51]),"+f"(d[52]),"+f"(d[53]),"+f"(d[54]),"+f"(d[55]),"+f"(d[56]),"+f"(d[57]),"+f"(d[58]),"+f"(d[59]),"+f"(d[60]),"+f"(d[61]),"+f"(d[62]),"+f"(d[63]),"+f"(d[64]),"+f"(d[65]),"+f"(d[66]),"+f"(d[67]),"+f"(d[68]),"+f"(d[69]),"+f"(d[70]),"+f"(d[71]),"+f"(d[72]),"+f"(d[73]),"+f"(d[74]),"+f"(d[75]),"+f"(d[76]),"+f"(d[77]),"+f"(d[78]),"+f"(d[79]),"+f"(d[80]),"+f"(d[81]),"+f"(d[82]),"+f"(d[83]),"+f"(d[84]),"+f"(d[85]),"+f"(d[86]),"+f"(d[87])
    :"r"(a0),"r"(a1),"r"(a2),"r"(a3),"l"(db),"r"(sc));
}
__device__ __forceinline__ void wgmma_rs_n192_t1(float (&d)[96],uint32_t a0,uint32_t a1,uint32_t a2,uint32_t a3,uint64_t db,int sc){
  asm volatile("{\n.reg .pred p;\nsetp.ne.b32 p,%101,0;\n"
    "wgmma.mma_async.sync.aligned.m64n192k16.f32.bf16.bf16 {%0,%1,%2,%3,%4,%5,%6,%7,%8,%9,%10,%11,%12,%13,%14,%15,%16,%17,%18,%19,%20,%21,%22,%23,%24,%25,%26,%27,%28,%29,%30,%31,%32,%33,%34,%35,%36,%37,%38,%39,%40,%41,%42,%43,%44,%45,%46,%47,%48,%49,%50,%51,%52,%53,%54,%55,%56,%57,%58,%59,%60,%61,%62,%63,%64,%65,%66,%67,%68,%69,%70,%71,%72,%73,%74,%75,%76,%77,%78,%79,%80,%81,%82,%83,%84,%85,%86,%87,%88,%89,%90,%91,%92,%93,%94,%95},{%96,%97,%98,%99},%100,p,1,1,1;\n}\n"
    :"+f"(d[0]),"+f"(d[1]),"+f"(d[2]),"+f"(d[3]),"+f"(d[4]),"+f"(d[5]),"+f"(d[6]),"+f"(d[7]),"+f"(d[8]),"+f"(d[9]),"+f"(d[10]),"+f"(d[11]),"+f"(d[12]),"+f"(d[13]),"+f"(d[14]),"+f"(d[15]),"+f"(d[16]),"+f"(d[17]),"+f"(d[18]),"+f"(d[19]),"+f"(d[20]),"+f"(d[21]),"+f"(d[22]),"+f"(d[23]),"+f"(d[24]),"+f"(d[25]),"+f"(d[26]),"+f"(d[27]),"+f"(d[28]),"+f"(d[29]),"+f"(d[30]),"+f"(d[31]),"+f"(d[32]),"+f"(d[33]),"+f"(d[34]),"+f"(d[35]),"+f"(d[36]),"+f"(d[37]),"+f"(d[38]),"+f"(d[39]),"+f"(d[40]),"+f"(d[41]),"+f"(d[42]),"+f"(d[43]),"+f"(d[44]),"+f"(d[45]),"+f"(d[46]),"+f"(d[47]),"+f"(d[48]),"+f"(d[49]),"+f"(d[50]),"+f"(d[51]),"+f"(d[52]),"+f"(d[53]),"+f"(d[54]),"+f"(d[55]),"+f"(d[56]),"+f"(d[57]),"+f"(d[58]),"+f"(d[59]),"+f"(d[60]),"+f"(d[61]),"+f"(d[62]),"+f"(d[63]),"+f"(d[64]),"+f"(d[65]),"+f"(d[66]),"+f"(d[67]),"+f"(d[68]),"+f"(d[69]),"+f"(d[70]),"+f"(d[71]),"+f"(d[72]),"+f"(d[73]),"+f"(d[74]),"+f"(d[75]),"+f"(d[76]),"+f"(d[77]),"+f"(d[78]),"+f"(d[79]),"+f"(d[80]),"+f"(d[81]),"+f"(d[82]),"+f"(d[83]),"+f"(d[84]),"+f"(d[85]),"+f"(d[86]),"+f"(d[87]),"+f"(d[88]),"+f"(d[89]),"+f"(d[90]),"+f"(d[91]),"+f"(d[92]),"+f"(d[93]),"+f"(d[94]),"+f"(d[95])
    :"r"(a0),"r"(a1),"r"(a2),"r"(a3),"l"(db),"r"(sc));
}
__device__ __forceinline__ void wgmma_rs_n24_t1(float (&d)[12],uint32_t a0,uint32_t a1,uint32_t a2,uint32_t a3,uint64_t db,int sc){
  asm volatile("{\n.reg .pred p;\nsetp.ne.b32 p,%17,0;\n"
    "wgmma.mma_async.sync.aligned.m64n24k16.f32.bf16.bf16 {%0,%1,%2,%3,%4,%5,%6,%7,%8,%9,%10,%11},{%12,%13,%14,%15},%16,p,1,1,1;\n}\n"
    :"+f"(d[0]),"+f"(d[1]),"+f"(d[2]),"+f"(d[3]),"+f"(d[4]),"+f"(d[5]),"+f"(d[6]),"+f"(d[7]),"+f"(d[8]),"+f"(d[9]),"+f"(d[10]),"+f"(d[11])
    :"r"(a0),"r"(a1),"r"(a2),"r"(a3),"l"(db),"r"(sc));
}
__device__ __forceinline__ void wgmma_rs_n64_t0(float (&d)[32],uint32_t a0,uint32_t a1,uint32_t a2,uint32_t a3,uint64_t db,int sc){
  asm volatile("{\n.reg .pred p;\nsetp.ne.b32 p,%37,0;\n"
    "wgmma.mma_async.sync.aligned.m64n64k16.f32.bf16.bf16 {%0,%1,%2,%3,%4,%5,%6,%7,%8,%9,%10,%11,%12,%13,%14,%15,%16,%17,%18,%19,%20,%21,%22,%23,%24,%25,%26,%27,%28,%29,%30,%31},{%32,%33,%34,%35},%36,p,1,1,0;\n}\n"
    :"+f"(d[0]),"+f"(d[1]),"+f"(d[2]),"+f"(d[3]),"+f"(d[4]),"+f"(d[5]),"+f"(d[6]),"+f"(d[7]),"+f"(d[8]),"+f"(d[9]),"+f"(d[10]),"+f"(d[11]),"+f"(d[12]),"+f"(d[13]),"+f"(d[14]),"+f"(d[15]),"+f"(d[16]),"+f"(d[17]),"+f"(d[18]),"+f"(d[19]),"+f"(d[20]),"+f"(d[21]),"+f"(d[22]),"+f"(d[23]),"+f"(d[24]),"+f"(d[25]),"+f"(d[26]),"+f"(d[27]),"+f"(d[28]),"+f"(d[29]),"+f"(d[30]),"+f"(d[31])
    :"r"(a0),"r"(a1),"r"(a2),"r"(a3),"l"(db),"r"(sc));
}
__device__ __forceinline__ void wgmma_ss_n128_t1(float (&d)[64],uint64_t da,uint64_t db,int sc){
  asm volatile("{\n.reg .pred p;\nsetp.ne.b32 p,%66,0;\n"
    "wgmma.mma_async.sync.aligned.m64n128k16.f32.bf16.bf16 {%0,%1,%2,%3,%4,%5,%6,%7,%8,%9,%10,%11,%12,%13,%14,%15,%16,%17,%18,%19,%20,%21,%22,%23,%24,%25,%26,%27,%28,%29,%30,%31,%32,%33,%34,%35,%36,%37,%38,%39,%40,%41,%42,%43,%44,%45,%46,%47,%48,%49,%50,%51,%52,%53,%54,%55,%56,%57,%58,%59,%60,%61,%62,%63},%64,%65,p,1,1,0,1;\n}\n"
    :"+f"(d[0]),"+f"(d[1]),"+f"(d[2]),"+f"(d[3]),"+f"(d[4]),"+f"(d[5]),"+f"(d[6]),"+f"(d[7]),"+f"(d[8]),"+f"(d[9]),"+f"(d[10]),"+f"(d[11]),"+f"(d[12]),"+f"(d[13]),"+f"(d[14]),"+f"(d[15]),"+f"(d[16]),"+f"(d[17]),"+f"(d[18]),"+f"(d[19]),"+f"(d[20]),"+f"(d[21]),"+f"(d[22]),"+f"(d[23]),"+f"(d[24]),"+f"(d[25]),"+f"(d[26]),"+f"(d[27]),"+f"(d[28]),"+f"(d[29]),"+f"(d[30]),"+f"(d[31]),"+f"(d[32]),"+f"(d[33]),"+f"(d[34]),"+f"(d[35]),"+f"(d[36]),"+f"(d[37]),"+f"(d[38]),"+f"(d[39]),"+f"(d[40]),"+f"(d[41]),"+f"(d[42]),"+f"(d[43]),"+f"(d[44]),"+f"(d[45]),"+f"(d[46]),"+f"(d[47]),"+f"(d[48]),"+f"(d[49]),"+f"(d[50]),"+f"(d[51]),"+f"(d[52]),"+f"(d[53]),"+f"(d[54]),"+f"(d[55]),"+f"(d[56]),"+f"(d[57]),"+f"(d[58]),"+f"(d[59]),"+f"(d[60]),"+f"(d[61]),"+f"(d[62]),"+f"(d[63])
    :"l"(da),"l"(db),"r"(sc));
}
__device__ __forceinline__ void wgmma_ss_n64_t1(float (&d)[32],uint64_t da,uint64_t db,int sc){
  asm volatile("{\n.reg .pred p;\nsetp.ne.b32 p,%34,0;\n"
    "wgmma.mma_async.sync.aligned.m64n64k16.f32.bf16.bf16 {%0,%1,%2,%3,%4,%5,%6,%7,%8,%9,%10,%11,%12,%13,%14,%15,%16,%17,%18,%19,%20,%21,%22,%23,%24,%25,%26,%27,%28,%29,%30,%31},%32,%33,p,1,1,0,1;\n}\n"
    :"+f"(d[0]),"+f"(d[1]),"+f"(d[2]),"+f"(d[3]),"+f"(d[4]),"+f"(d[5]),"+f"(d[6]),"+f"(d[7]),"+f"(d[8]),"+f"(d[9]),"+f"(d[10]),"+f"(d[11]),"+f"(d[12]),"+f"(d[13]),"+f"(d[14]),"+f"(d[15]),"+f"(d[16]),"+f"(d[17]),"+f"(d[18]),"+f"(d[19]),"+f"(d[20]),"+f"(d[21]),"+f"(d[22]),"+f"(d[23]),"+f"(d[24]),"+f"(d[25]),"+f"(d[26]),"+f"(d[27]),"+f"(d[28]),"+f"(d[29]),"+f"(d[30]),"+f"(d[31])
    :"l"(da),"l"(db),"r"(sc));
}

__device__ __forceinline__ float silu_bf(bf16 c) { const float x = __bfloat162float(c); return rbf(x / (1.f + __expf(-x))); }
__device__ __forceinline__ void fma8(float (&a)[8], float s, const uint4& v) {
  a[0] += s * blo(v.x); a[1] += s * bhi(v.x); a[2] += s * blo(v.y); a[3] += s * bhi(v.y);
  a[4] += s * blo(v.z); a[5] += s * bhi(v.z); a[6] += s * blo(v.w); a[7] += s * bhi(v.w);
}
__device__ __forceinline__ float red8(float (&a)[8], int lane) {
#pragma unroll
  for (int w = 4; w >= 1; w >>= 1) {
    const bool up = lane & (w * 4);
#pragma unroll
    for (int j = 0; j < w; j++) a[j] = (up ? a[j + w] : a[j]) + __shfl_xor_sync(~0u, up ? a[j] : a[j + w], w * 4);
  }
  return a[0];
}
__device__ __forceinline__ float mod_fin(float s, int n) { s = rbf(s); return ((n >> 9) == 1 || (n >> 9) == 4) ? rbf(1.f + s) : s; }
__device__ __forceinline__ void poll4(uint2& a, uint2& b, uint2& c, uint2& d, const uint32_t* p, const uint32_t* q) {
  asm volatile("{\n.reg .pred p;\n.reg .u32 n,t;\nmov.u32 n,0;\nLW:\nld.relaxed.gpu.global.v2.u32 {%0,%1},[%8];\nld.relaxed.gpu.global.v2.u32 {%2,%3},[%8+64];\n"
               "ld.relaxed.gpu.global.v2.u32 {%4,%5},[%9];\nld.relaxed.gpu.global.v2.u32 {%6,%7},[%9+2048];\n"
               "lop3.b32 t,%0,%1,%2,0x80;\nlop3.b32 t,t,%3,%4,0x80;\nlop3.b32 t,t,%5,%6,0x80;\nlop3.b32 t,t,%7,1,0x80;\n"
               "setp.ne.u32 p,t,0;\n@p bra LD;\nadd.u32 n,n,1;\nsetp.lt.u32 p,n,1048576;\n@p bra LW;\nLD:\n}\n"
               : "=&r"(a.x), "=&r"(a.y), "=&r"(b.x), "=&r"(b.y), "=&r"(c.x), "=&r"(c.y), "=&r"(d.x), "=&r"(d.y) : "l"(p), "l"(q) : "memory");
}

constexpr int LN_SMEM = 131072 + 4 * 24576 + 2048 + 256 + 512;
template <bool FFN>
__global__ void __cluster_dims__(2, 1, 1) __launch_bounds__(384, 1) k_lngemm(const __grid_constant__ CUtensorMap mX, const __grid_constant__ CUtensorMap mB0,
                                                   const __grid_constant__ CUtensorMap mB1, const bf16* __restrict__ cv, const bf16* __restrict__ wm, const bf16* __restrict__ xg) {
  extern __shared__ __align__(1024) uint8_t smem[];
  const uint32_t sA = smem_u32(smem), sB = sA + 131072, sM = sB + 4 * 24576, bars = sM + 2048;
  const uint32_t bA = bars, bF = bars + 64, bE = bars + 96;
  const int tid = threadIdx.x, warp = tid >> 5, lane = tid & 31;
  const int rb = blockIdx.x >> 3, ct = blockIdx.x & 7;
  constexpr int NST = FFN ? 16 : 8, KS = FFN ? 2 : 4, BOX = FFN ? 4096 : 8192;
  TS(FFN ? 4 : 1, 0);
  pdl_launch();
  float* red = (float*)(smem + (bars - sA) + 256);
  if (tid == 256) {
    for (int i = 0; i < 8; i++) mbar_init(bA + 8 * i, 1);
    for (int i = 0; i < 4; i++) { mbar_init(bF + 8 * i, 1); mbar_init(bE + 8 * i, 8); }
    fence_init();
  }
  __syncwarp();
  cluster_arrive();
  uint4 wv0, wv1, xv[4];
  bf16 cv0, cv1;
  if (!FFN && tid < 256) {
    wv0 = __ldg((const uint4*)(wm + tid * 3072 + blockIdx.x * 8)); wv1 = __ldg((const uint4*)(wm + (tid + 256) * 3072 + blockIdx.x * 8));
    cv0 = cv[tid]; cv1 = cv[tid + 256];
#pragma unroll
    for (int i = 0; i < 4; i++) xv[i] = __ldg((const uint4*)(xg + (blockIdx.x * 16 + (tid >> 4)) * 512 + i * 128 + (tid & 15) * 8));
  }
  cluster_wait();
  if (!FFN) TS(0, 2);
  if (warp >= 8) {
    asm volatile("setmaxnreg.dec.sync.aligned.u32 40;");
    if (tid == 256) {
      auto loadB = [&](int s) {
        const uint32_t d = sB + (s & 3) * 24576, b = bF + (s & 3) * 8;
        mbar_expect(b, 24576);
        for (int j = 0; j < 3; j++) {
          if (FFN) { tma2d(d + j * BOX, &mB0, ct * 176 + j * 64, s * 32, b); tma2d(d + (3 + j) * BOX, &mB1, ct * 176 + j * 64, s * 32, b); }
          else tma2d(d + j * BOX, &mB0, ct * 192 + j * 64, s * 64, b);
        }
      };
      for (int i = 0; i < 8; i++) mbar_expect(bA + 8 * i, 16384);
      for (int s = 0; s < 4; s++) {
        const int i = s * 2 + (ct & 1);
        if (!FFN) tma2d_mc(sA + i * 16384, &mX, i * 64, rb * 128, bA + 8 * i);
        loadB(s);
      }
      if (FFN) {
        pdl_wait();
        for (int i = ct & 1; i < 8; i += 2) bulk_load_mc(sA + i * 16384, g_x1 + (rb * 64 + i * 8) * 1024, 16384, bA + 8 * i);
      }
      for (int s = 4; s < NST; s++) { mbar_wait(bE + (s & 3) * 8, ((s >> 2) - 1) & 1); loadB(s); }
    }
  } else {
  asm volatile("setmaxnreg.inc.sync.aligned.u32 232;");
  const int g = lane >> 2, t = lane & 3;
  const int lr = warp * 16 + (lane & 7) + ((lane >> 3) & 1) * 8;
  auto aaddr = [&](int ks) -> uint32_t {
    if (FFN) return sA + (ks * 2 + (lane >> 4)) * 2048 + lr * 16;
    return sA + (ks >> 2) * 16384 + lr * 128 + ((((ks & 3) * 2 + (lane >> 4)) ^ (lr & 7)) << 4);
  };
  const int row0 = rb * 128 + warp * 16 + g;
  float2 msh, msc;
  uint2 sh, sc;
  float rs0, rs1, nm0, nm1;
  if (!FFN) {
    {
      float a[8] = {0, 0, 0, 0, 0, 0, 0, 0};
      fma8(a, silu_bf(cv0), wv0); fma8(a, silu_bf(cv1), wv1);
      if (a[0] != 123.f) TS(0, 3);
      const float s = qsum(red8(a, lane));
      if (t == 0) red[warp * 8 + g] = s;
      asm volatile("bar.sync 1,256;" ::: "memory");
      if (tid < 8) {
        float r = 0;
#pragma unroll
        for (int i = 0; i < 8; i++) r += red[i * 8 + tid];
        const int n = blockIdx.x * 8 + tid;
        asm volatile("st.relaxed.gpu.global.u32 [%0],%1;" ::"l"(g_modv + n), "r"(__float_as_uint(mod_fin(r, n)) | 1u) : "memory");
      }
      TS(0, 1);
    }
    {
      float v[32], s = 0, q = 0;
#pragma unroll
      for (int i = 0; i < 16; i++) { const uint32_t u = ((const uint32_t*)xv)[i]; v[2 * i] = blo(u); v[2 * i + 1] = bhi(u); s += v[2 * i] + v[2 * i + 1]; }
      s = qsum(s); s += __shfl_xor_sync(~0u, s, 4); s += __shfl_xor_sync(~0u, s, 8);
      const float m = s * (1.f / 512);
#pragma unroll
      for (int i = 0; i < 32; i++) q += (v[i] - m) * (v[i] - m);
      q = qsum(q); q += __shfl_xor_sync(~0u, q, 4); q += __shfl_xor_sync(~0u, q, 8);
      const float rs = rsqrtf(q * (1.f / 512) + 1e-5f);
      if ((tid & 15) == 0)
        asm volatile("st.relaxed.gpu.global.v2.u32 [%0],{%1,%2};" ::"l"(g_modv + 1024 + (blockIdx.x * 16 + (tid >> 4)) * 2), "r"(__float_as_uint(rs) | 1u), "r"(__float_as_uint(-m * rs) | 1u) : "memory");
    }
    TS(0, 4);
    uint2 p0, p1;
    poll4(p0, p1, sh, sc, g_modv + 1024 + row0 * 2, g_modv + tid * 2);
    rs0 = __uint_as_float(p0.x); nm0 = __uint_as_float(p0.y); rs1 = __uint_as_float(p1.x); nm1 = __uint_as_float(p1.y);
    TS(1, 1);
  } else {
    pdl_wait();
    TS(4, 1);
    msh = *(const float2*)(g_mod + 1536 + tid * 2); msc = *(const float2*)(g_mod + 2048 + tid * 2);
    const float4 p0 = *(const float4*)(g_st + row0 * 8 + t * 2), p1 = *(const float4*)(g_st + (row0 + 8) * 8 + t * 2);
    const float m0 = qsum(p0.x + p0.z) * 0.125f, m1 = qsum(p1.x + p1.z) * 0.125f;
    const float v0 = qsum(p0.y + p0.w + 64.f * ((p0.x - m0) * (p0.x - m0) + (p0.z - m0) * (p0.z - m0)));
    const float v1 = qsum(p1.y + p1.w + 64.f * ((p1.x - m1) * (p1.x - m1) + (p1.z - m1) * (p1.z - m1)));
    rs0 = rsqrtf(v0 * (1.f / 512) + 1e-5f); rs1 = rsqrtf(v1 * (1.f / 512) + 1e-5f);
    nm0 = -m0 * rs0; nm1 = -m1 * rs1;
  }
  {
    uint32_t* m = (uint32_t*)(smem + (sM - sA)) + (tid >> 3) * 16 + (tid & 3) * 4 + ((tid >> 2) & 1);
    if (FFN) { m[0] = pack_rn(msc.x, msc.y); m[2] = pack_rn(msh.x, msh.y); }
    else { m[0] = __byte_perm(sc.x, sc.y, 0x7632); m[2] = __byte_perm(sh.x, sh.y, 0x7632); }
    asm volatile("bar.sync 1,256;" ::: "memory");
  }
  constexpr int NA = FFN ? 88 : 96;
  float acc0[NA], acc1[FFN ? 88 : 1];
  uint32_t a[2][KS][4];
  auto prep = [&](int ks, uint32_t(&o)[4]) {
    if ((ks & 3) == 0) mbar_wait(bA + 2 * ks, 0);
    uint32_t r[4]; ldsm4(aaddr(ks), r);
    const uint4 m = *(const uint4*)(smem + (sM - sA) + ks * 64 + t * 16);
#pragma unroll
    for (int i = 0; i < 4; i++) {
      const float rs = (i & 1) ? rs1 : rs0, nm = (i & 1) ? nm1 : nm0;
      const uint32_t n = pack_rn(fmaf(blo(r[i]), rs, nm), fmaf(bhi(r[i]), rs, nm));
      asm("fma.rn.bf16x2 %0,%1,%2,%3;" : "=r"(o[i]) : "r"(n), "r"(i < 2 ? m.x : m.y), "r"(i < 2 ? m.z : m.w));
    }
  };
  auto stage = [&](int s, uint32_t(&c)[KS][4], uint32_t(&n)[KS][4]) {
    mbar_wait(bF + (s & 3) * 8, (s >> 2) & 1);
    const uint64_t db = mk_desc(sB + (s & 3) * 24576, BOX, 1024, 1);
    wg_fence();
#pragma unroll
    for (int k = 0; k < KS; k++) {
      if constexpr (FFN) {
        wgmma_rs_n176_t1(acc0, c[k][0], c[k][1], c[k][2], c[k][3], db + k * 128, s + k);
        wgmma_rs_n176_t1(acc1, c[k][0], c[k][1], c[k][2], c[k][3], db + k * 128 + 3 * BOX / 16, s + k);
      } else {
        wgmma_rs_n192_t1(acc0, c[k][0], c[k][1], c[k][2], c[k][3], db + k * 128, s + k);
      }
    }
    wg_commit();
    wg_wait<1>();
    if (s > 0 && lane == 0) mbar_arrive(bE + ((s - 1) & 3) * 8);
    if (s < NST - 1) {
#pragma unroll
      for (int k = 0; k < KS; k++) prep((s + 1) * KS + k, n[k]);
    }
  };
#pragma unroll
  for (int k = 0; k < KS; k++) prep(k, a[0][k]);
  TS(FFN ? 4 : 1, 2);
#pragma unroll 1
  for (int s = 0; s < NST; s += 2) { stage(s, a[0], a[1]); stage(s + 1, a[1], a[0]); }
  wg_wait<0>();
  reg_fence(acc0);
  TS(FFN ? 4 : 1, 3);
  if constexpr (FFN) {
    reg_fence(acc1);
    uint32_t* o = (uint32_t*)g_h + ((rb * 172 + ct * 22) * 128 + warp * 16 + g) * 4 + t;
#pragma unroll
    for (int j = 0; j < 22; j++) {
      if (ct * 22 + j < 172) {
        float h[4];
#pragma unroll
        for (int i = 0; i < 4; i++) { const float x = acc0[4 * j + i]; h[i] = __fdividef(x, 1.f + ex2(-1.4426950408889634f * x)) * acc1[4 * j + i]; }
        o[j * 512] = pack_rn(h[0], h[1]);
        o[j * 512 + 32] = pack_rn(h[2], h[3]);
      }
    }
  } else {
    uint32_t* o = (uint32_t*)g_qkv + (ct * 24 * 2048 + row0) * 4 + t;
#pragma unroll
    for (int j = 0; j < 24; j += 2) {
      const int G = ct * 24 + j;
      const float sc = G < 64 ? 0.25f * 1.4426950408889634f : 1.f;
      uint32_t p[4];
#pragma unroll
      for (int i = 0; i < 4; i++) p[i] = pack_rn(acc0[4 * j + 2 * i] * sc, acc0[4 * j + 2 * i + 1] * sc);
      o[j * 8192] = p[0]; o[j * 8192 + 32] = p[1]; o[(j + 1) * 8192] = p[2]; o[(j + 1) * 8192 + 32] = p[3];
      if (G >= 64 && G < 128) {
        float n0 = blo(p[0]) * blo(p[0]) + bhi(p[0]) * bhi(p[0]) + blo(p[2]) * blo(p[2]) + bhi(p[2]) * bhi(p[2]);
        float n1 = blo(p[1]) * blo(p[1]) + bhi(p[1]) * bhi(p[1]) + blo(p[3]) * blo(p[3]) + bhi(p[3]) * bhi(p[3]);
        n0 = qsum(n0); n1 = qsum(n1);
        const uint32_t mx = __reduce_max_sync(~0u, max(__float_as_uint(n0), __float_as_uint(n1)));
        if (lane == 0) g_kmax[((G - 64) >> 1) * 128 + rb * 8 + warp] = __uint_as_float(mx);
      }
    }
  }
  TS(FFN ? 4 : 1, 4);
}
}

#define SMASK 0xAAu
#define BRK 0
#define PACK 1
#define PP 1
constexpr int AT_SMEM = 5 * 32768 + 256;
__device__ __forceinline__ uint32_t exp2_pair_fma(float s0, float s1, float c, uint32_t ka, uint32_t kz) {
  uint32_t r;
  asm volatile("{\n.reg .b32 y0,y1,e,u,t;\n"
      "fma.rn.sat.f32 y0,%1,0f00000080,%3;\nfma.rn.sat.f32 y1,%2,0f00000080,%3;\n"
      "mad.lo.u32 e,y1,65536,y0;\n"
      "and.b32 u,e,0x007F007F;\n"
      "fma.rn.f16x2 u,u,%4,%5;\nfma.rn.f16x2 t,u,u,%6;\nfma.rn.f16x2 t,t,u,%7;\n"
      "lop3.b32 %0,t,0x007F007F,e,0xE2;\n}\n"
      : "=r"(r) : "f"(s0), "f"(s1), "f"(c), "r"(ka), "r"(0x36B236B2u), "r"(0x3C733C73u), "r"(0x47764776u), "r"(kz));
  return r;
}
__device__ __forceinline__ void attn_pass(float (&oa)[12], float (&ob)[12], const uint32_t (&q)[4], float m0, float m1, uint32_t sK, uint32_t bars, bool first, uint32_t kz) {
  const uint64_t dk = mk_desc(sK, 32768, 128, 0), dv = mk_desc(sK + 65536, 128, 32768, 0);
  const float c0 = (127.f - m0) * __uint_as_float(0x80u), c1 = (127.f - m1) * __uint_as_float(0x80u);
  const uint32_t ka = 0x7ACE7ACEu + kz;
  constexpr int NK = 64, NS = 32, NP = 16, NI = 32;
  auto qk = [&](float (&s)[NS], int i) { wgmma_rs_n64_t0(s, q[0], q[1], q[2], q[3], dk + i * NK, 0); };
  auto softmax = [&](float (&s)[NS], uint32_t (&p)[NP], uint32_t mask) {
    reg_fence(s);
    float e0, e1;
    int pend = -1;
#pragma unroll
    for (int t = 0; t < NP; t++) {
      const int j = (t & 3) * 4 + (t >> 2);
      if ((mask >> (t & 3)) & 1) {
        p[j] = exp2_pair_fma(s[2 * j], s[2 * j + 1], (j & 1) ? c1 : c0, ka, kz);
      } else {
        float f0, f1;
        asm volatile("ex2.approx.ftz.f32 %0,%2;\nex2.approx.ftz.f32 %1,%3;" : "=&f"(f0), "=f"(f1) : "f"(s[2 * j]), "f"(s[2 * j + 1]));
        if (pend >= 0) asm volatile("cvt.rn.bf16x2.f32 %0,%1,%2;" : "=r"(p[pend]) : "f"(e1), "f"(e0));
        e0 = f0; e1 = f1; pend = j;
      }
    }
    if (pend >= 0) asm volatile("cvt.rn.bf16x2.f32 %0,%1,%2;" : "=r"(p[pend]) : "f"(e1), "f"(e0));
#pragma unroll
    for (int j = 0; j < NP; j++) asm volatile("" : "+r"(p[j])::"memory");
  };
  auto pv = [&](uint32_t (&p)[NP], int i, uint32_t mask) {
#pragma unroll
    for (int k = 0; k < 4; k++) wgmma_rs_n24_t1(((mask >> k) & 1) ? ob : oa, p[4 * k], p[4 * k + 1], p[4 * k + 2], p[4 * k + 3], dv + i * NK + k * 16, 1);
  };
  auto ld = [&](int i) { if (first && (i & 3) == 0) mbar_wait(bars + i * 2, 0); };
  constexpr uint32_t M0 = SMASK & 15, M1 = SMASK >> 4;
  zero(oa); zero(ob);
  ld(0);
  if (first) TS(2, 2);
  float s[NS];
  zero(s);
  uint32_t p0[NP], p1[NP];
  wg_fence(); qk(s, 0); wg_commit(); wg_wait<0>(); softmax(s, p0, M0);
#pragma unroll 1
  for (int i = 0; i < NI - 2; i += 2) {
    wg_fence(); qk(s, i + 1); wg_commit(); pv(p0, i, M0); wg_commit(); wg_wait<1>(); softmax(s, p1, M1); wg_wait<0>();
    ld(i + 2);
    wg_fence(); qk(s, i + 2); wg_commit(); pv(p1, i + 1, M1); wg_commit(); wg_wait<1>(); softmax(s, p0, M0); wg_wait<0>();
  }
  wg_fence(); qk(s, NI - 1); wg_commit(); pv(p0, NI - 2, M0); wg_commit(); wg_wait<1>(); softmax(s, p1, M1); wg_wait<0>();
  wg_fence(); pv(p1, NI - 1, M1); wg_commit();
  wg_wait<0>();
  reg_fence(oa); reg_fence(ob);
}
__device__ __forceinline__ void mma16816(float (&d)[4], const uint32_t (&a)[4], uint32_t b0, uint32_t b1) {
  asm("mma.sync.aligned.m16n8k16.row.col.f32.bf16.bf16.f32 {%0,%1,%2,%3},{%4,%5,%6,%7},{%8,%9},{%0,%1,%2,%3};"
      : "+f"(d[0]), "+f"(d[1]), "+f"(d[2]), "+f"(d[3]) : "r"(a[0]), "r"(a[1]), "r"(a[2]), "r"(a[3]), "r"(b0), "r"(b1));
}
__device__ __forceinline__ void attn_safe(float (&o)[12], const uint32_t (&q)[4], uint32_t sK) {
  const int lane = threadIdx.x & 31;
  const uint32_t ka = sK + (lane >> 4) * 32768 + (lane & 15) * 16;
  float m0 = -INFINITY, m1 = -INFINITY;
#pragma unroll 2
  for (int i = 0; i < 128; i++) {
    uint32_t k[4]; ldsm4(ka + i * 256, k);
    float s0[4] = {0, 0, 0, 0}, s1[4] = {0, 0, 0, 0};
    mma16816(s0, q, k[0], k[2]); mma16816(s1, q, k[1], k[3]);
    m0 = fmaxf(fmaxf(m0, fmaxf(s0[0], s0[1])), fmaxf(s1[0], s1[1])); m1 = fmaxf(fmaxf(m1, fmaxf(s0[2], s0[3])), fmaxf(s1[2], s1[3]));
  }
  m0 = fmaxf(m0, __shfl_xor_sync(~0u, m0, 1)); m0 = fmaxf(m0, __shfl_xor_sync(~0u, m0, 2));
  m1 = fmaxf(m1, __shfl_xor_sync(~0u, m1, 1)); m1 = fmaxf(m1, __shfl_xor_sync(~0u, m1, 2));
  float o0[4] = {0, 0, 0, 0}, o1[4] = {0, 0, 0, 0}, o2[4] = {0, 0, 0, 0};
#pragma unroll 2
  for (int i = 0; i < 128; i++) {
    uint32_t k[4], v[4]; ldsm4(ka + i * 256, k);
    asm volatile("ldmatrix.sync.aligned.m8n8.x4.trans.shared.b16 {%0,%1,%2,%3},[%4];" : "=r"(v[0]), "=r"(v[1]), "=r"(v[2]), "=r"(v[3]) : "r"(ka + 65536 + i * 256) : "memory");
    float s0[4] = {0, 0, 0, 0}, s1[4] = {0, 0, 0, 0};
    mma16816(s0, q, k[0], k[2]); mma16816(s1, q, k[1], k[3]);
    const uint32_t p[4] = {pack_rn(ex2(s0[0] - m0), ex2(s0[1] - m0)), pack_rn(ex2(s0[2] - m1), ex2(s0[3] - m1)),
                           pack_rn(ex2(s1[0] - m0), ex2(s1[1] - m0)), pack_rn(ex2(s1[2] - m1), ex2(s1[3] - m1))};
    mma16816(o0, p, v[0], v[1]); mma16816(o1, p, v[2], v[3]); mma16816(o2, p, 0x3F803F80u, 0x3F803F80u);
  }
#pragma unroll
  for (int i = 0; i < 4; i++) { o[i] = o0[i]; o[4 + i] = o1[i]; o[8 + i] = o2[i]; }
}
__global__ void __cluster_dims__(2, 1, 1) __launch_bounds__(512, 1) k_attn(const bf16* wo, const bf16* w1, const bf16* w3, const bf16* w2, const bf16* __restrict__ cv, const bf16* __restrict__ wm, uint32_t kz) {
  extern __shared__ __align__(1024) uint8_t smem[];
  const uint32_t sK = smem_u32(smem), bars = sK + 5 * 32768;
  const int tid = threadIdx.x, warp = tid >> 5, lane = tid & 31, g = lane >> 2, t = lane & 3;
  pdl_launch();
  if (blockIdx.x < 4) {
    float* cs = (float*)smem;
    cs[tid] = silu_bf(cv[tid]);
    __syncthreads();
    const int n0 = 1024 + blockIdx.x * 512, r0 = (tid >> 6) * 64;
    float a[8] = {0, 0, 0, 0, 0, 0, 0, 0};
#pragma unroll 16
    for (int r = r0; r < r0 + 64; r++) fma8(a, cs[r], __ldg((const uint4*)(wm + r * 3072 + n0 + (tid & 63) * 8)));
    float4* rp = (float4*)(cs + 512 + tid * 8);
    rp[0] = make_float4(a[0], a[1], a[2], a[3]); rp[1] = make_float4(a[4], a[5], a[6], a[7]);
    __syncthreads();
    float s = 0;
#pragma unroll
    for (int i = 0; i < 8; i++) s += cs[512 + i * 512 + tid];
    g_mod[n0 + tid] = mod_fin(s, n0 + tid);
    return;
  }
  const int bid = blockIdx.x - 4, h = bid >> 2, qb = bid & 3;
  TS(2, 0);
  if (tid == 0) { for (int i = 0; i < 8; i++) { mbar_init(bars + 8 * i, 1); mbar_expect(bars + 8 * i, 16384); } fence_init(); }
#pragma unroll
  for (int i = 0; i < 4; i++) *(uint4*)(smem + 131072 + i * 8192 + tid * 16) = make_uint4(0x3F803F80u, 0x3F803F80u, 0x3F803F80u, 0x3F803F80u);
  fence_async();
  cluster_sync();
  pdl_wait();
  TS(2, 1);
  if (tid >= 472) g_modv[bid * 40 + tid - 472] = 0;
  if (tid == 0) {
    for (int c = 0; c < 8; c++)
      for (int pl = qb & 1; pl < 4; pl += 2)
        bulk_load_mc(sK + pl * 32768 + c * 4096, g_qkv + ((64 + (pl >> 1) * 64 + h * 2 + (pl & 1)) * 2048 + c * 256) * 8, 4096, bars + 8 * c);
  }
  if (tid == 32) {
    l2_prefetch((const char*)wo + bid * 4096, 4096);
    l2_prefetch((const char*)w1 + bid * 11008, 11008);
    l2_prefetch((const char*)w3 + bid * 11008, 11008);
    l2_prefetch((const char*)w2 + bid * 11008, 11008);
  }
  const uint4 km4 = *(const uint4*)(g_kmax + h * 128 + lane * 4);
  const float kmax = __uint_as_float(__reduce_max_sync(~0u, max(max(km4.x, km4.y), max(km4.z, km4.w))));
#pragma unroll 1
  for (int tile = 0; tile < 2; tile++) {
    const int row = qb * 512 + tile * 256 + warp * 16 + g;
    const uint32_t* qp = (const uint32_t*)g_qkv + (h * 2 * 2048 + row) * 4 + t;
    uint32_t q[4] = {qp[0], qp[32], qp[8192], qp[8192 + 32]};
    const float n0 = qsum(blo(q[0]) * blo(q[0]) + bhi(q[0]) * bhi(q[0]) + blo(q[2]) * blo(q[2]) + bhi(q[2]) * bhi(q[2]));
    const float n1 = qsum(blo(q[1]) * blo(q[1]) + bhi(q[1]) * bhi(q[1]) + blo(q[3]) * blo(q[3]) + bhi(q[3]) * bhi(q[3]));
    const float b0 = sqrtf(n0 * kmax) * 1.001f, b1 = sqrtf(n1 * kmax) * 1.001f;
    const float m0 = fmaxf(ceilf(b0 - 100.f), 0.f), m1 = fmaxf(ceilf(b1 - 100.f), 0.f);
    float o[12], ob[12];
    attn_pass(o, ob, q, m0, m1, sK, bars, tile == 0, kz);
    const float f0 = ex2(-m0), f1 = ex2(-m1);
#pragma unroll
    for (int i = 0; i < 12; i++) o[i] = fmaf(o[i], (i & 2) ? f1 : f0, ob[i]);
    bool ok = b0 < 220.f && b1 < 220.f && o[8] >= 0x1p-90f && o[10] >= 0x1p-90f;
#pragma unroll
    for (int i = 0; i < 12; i++) ok = ok && fabsf(o[i]) < INFINITY;
    if (!__all_sync(~0u, ok)) attn_safe(o, q, sK);
    const float r0 = 1.f / o[8], r1 = 1.f / o[10];
    uint32_t* op = (uint32_t*)g_o + (((row >> 7) * 64 + h * 2) * 128 + (row & 127)) * 4 + t;
    op[0] = pack_rn(o[0] * r0, o[1] * r0); op[32] = pack_rn(o[2] * r1, o[3] * r1);
    op[512] = pack_rn(o[4] * r0, o[5] * r0); op[512 + 32] = pack_rn(o[6] * r1, o[7] * r1);
    TS(2, 3 + tile);
  }
}

constexpr int WO_SMEM = 131072 + 65536 + 256;
__global__ void __cluster_dims__(2, 1, 1) __launch_bounds__(256, 1) k_wo(const __grid_constant__ CUtensorMap mW, const bf16* __restrict__ x) {
  extern __shared__ __align__(1024) uint8_t smem[];
  const uint32_t sA = smem_u32(smem), sB = sA + 131072, bars = sB + 65536;
  const int tid = threadIdx.x, warp = tid >> 5, lane = tid & 31, g = lane >> 2, t = lane & 3;
  const int rb = blockIdx.x >> 3, ct = blockIdx.x & 7;
  TS(3, 0);
  pdl_launch();
  if (tid == 0) {
    for (int i = 0; i < 8; i++) mbar_init(bars + 8 * i, 1);
    fence_init();
    for (int i = 0; i < 8; i++) { mbar_expect(bars + 8 * i, 24576); tma2d(sB + i * 8192, &mW, ct * 64, i * 64, bars + 8 * i); }
  }
  __syncwarp();
  cluster_arrive();
  const int lrow = warp * 16 + g;
  uint32_t xr[16];
  const uint32_t* xp = (const uint32_t*)(x + (rb * 128 + lrow) * 512 + ct * 64) + t;
#pragma unroll
  for (int j = 0; j < 8; j++) { xr[2 * j] = __ldg(xp + j * 4); xr[2 * j + 1] = __ldg(xp + j * 4 + 8 * 256); }
  cluster_wait();
  pdl_wait();
  TS(3, 1);
  if (tid == 0) for (int i = ct & 1; i < 8; i += 2) bulk_load_mc(sA + i * 16384, g_o + (rb * 64 + i * 8) * 1024, 16384, bars + 8 * i);
  float2 ga[8];
#pragma unroll
  for (int j = 0; j < 8; j++) ga[j] = *(const float2*)(g_mod + 1024 + ct * 64 + j * 8 + t * 2);
  float acc[32];
  const uint64_t da = mk_desc(sA + (warp >> 2) * 1024, 2048, 128, 0), db = mk_desc(sB, 8192, 1024, 1);
#pragma unroll
  for (int c = 0; c < 8; c++) {
    mbar_wait(bars + 8 * c, 0);
    if (c == 0) TS(3, 2);
    wg_fence();
#pragma unroll
    for (int k = 0; k < 4; k++) wgmma_ss_n64_t1(acc, da + (c * 4 + k) * 256, db + (c * 4 + k) * 128, c + k);
    wg_commit();
  }
  wg_wait<0>();
  reg_fence(acc);
  TS(3, 3);
  uint32_t* o = (uint32_t*)g_x1 + ((rb * 64 + ct * 8) * 128 + lrow) * 4 + t;
  float s0 = 0, s1 = 0;
#pragma unroll
  for (int j = 0; j < 8; j++) {
    xr[2 * j] = pack_rn(fmaf(ga[j].x, acc[4 * j], blo(xr[2 * j])), fmaf(ga[j].y, acc[4 * j + 1], bhi(xr[2 * j])));
    xr[2 * j + 1] = pack_rn(fmaf(ga[j].x, acc[4 * j + 2], blo(xr[2 * j + 1])), fmaf(ga[j].y, acc[4 * j + 3], bhi(xr[2 * j + 1])));
    o[j * 512] = xr[2 * j]; o[j * 512 + 32] = xr[2 * j + 1];
    s0 += blo(xr[2 * j]) + bhi(xr[2 * j]); s1 += blo(xr[2 * j + 1]) + bhi(xr[2 * j + 1]);
  }
  const float m0 = qsum(s0) * (1.f / 64), m1 = qsum(s1) * (1.f / 64);
  float v0 = 0, v1 = 0;
#pragma unroll
  for (int j = 0; j < 8; j++) {
    float d;
    d = blo(xr[2 * j]) - m0; v0 += d * d; d = bhi(xr[2 * j]) - m0; v0 += d * d;
    d = blo(xr[2 * j + 1]) - m1; v1 += d * d; d = bhi(xr[2 * j + 1]) - m1; v1 += d * d;
  }
  v0 = qsum(v0); v1 = qsum(v1);
  if (t == 0) g_st[(rb * 128 + lrow) * 8 + ct] = make_float2(m0, v0);
  if (t == 1) g_st[(rb * 128 + lrow + 8) * 8 + ct] = make_float2(m1, v1);
  TS(3, 4);
}

constexpr int W2_SMEM = 6 * 32768 + 32768 + 256;
__global__ void __cluster_dims__(2, 1, 1) __launch_bounds__(288, 1) k_w2(const __grid_constant__ CUtensorMap mW, bf16* __restrict__ out) {
  extern __shared__ __align__(1024) uint8_t smem[];
  const uint32_t sR = smem_u32(smem), sX = sR + 6 * 32768, bF = sX + 32768, bE = bF + 48;
  const int tid = threadIdx.x, warp = tid >> 5, lane = tid & 31, g = lane >> 2, t = lane & 3;
  const int kh = blockIdx.x & 1, ct = (blockIdx.x >> 1) & 3, rb = blockIdx.x >> 3;
  TS(5, 0);
  pdl_launch();
  if (tid == 256) {
    for (int i = 0; i < 6; i++) { mbar_init(bF + 8 * i, 1); mbar_init(bE + 8 * i, 8); }
    fence_init();
  }
  __syncthreads();
  asm volatile("barrier.cluster.arrive.relaxed.aligned;" ::: "memory");
  if (warp == 8) {
    if (lane == 0) {
      auto abytes = [&](int s) { return (kh == 1 && s == 10) ? 8192 : 16384; };
      auto loadB = [&](int s) {
        const int st = s % 6;
        mbar_expect(bF + 8 * st, 16384 + abytes(s));
        for (int j = 0; j < 2; j++) tma2d(sR + st * 32768 + 16384 + j * 8192, &mW, ct * 128 + j * 64, kh * 704 + s * 64, bF + 8 * st);
      };
      auto loadA = [&](int s) { bulk_load(sR + (s % 6) * 32768, g_h + (rb * 172 + kh * 88 + s * 8) * 1024, abytes(s), bF + 8 * (s % 6)); };
      for (int s = 0; s < 6; s++) loadB(s);
      pdl_wait();
      for (int s = 0; s < 6; s++) loadA(s);
      for (int s = 6; s < 11; s++) { mbar_wait(bE + 8 * (s - 6), 0); loadB(s); loadA(s); }
    }
    __syncwarp();
    asm volatile("barrier.cluster.wait.aligned;" ::: "memory");
    asm volatile("barrier.cluster.arrive.release.aligned;" ::: "memory");
    asm volatile("barrier.cluster.wait.acquire.aligned;" ::: "memory");
    return;
  }
  pdl_wait();
  TS(5, 1);
  const int lrow = warp * 16 + g;
  uint32_t xr[16];
  float2 gb[8];
  const uint32_t* xp = (const uint32_t*)g_x1 + ((rb * 64 + ct * 16 + kh * 8) * 128 + lrow) * 4 + t;
#pragma unroll
  for (int j = 0; j < 8; j++) {
    xr[2 * j] = xp[j * 512]; xr[2 * j + 1] = xp[j * 512 + 32];
    gb[j] = *(const float2*)(g_mod + 2560 + ct * 128 + kh * 64 + j * 8 + t * 2);
  }
  float acc[64];
#pragma unroll 1
  for (int s = 0; s < 11; s++) {
    const int st = s % 6;
    mbar_wait(bF + 8 * st, s >= 6);
    const uint64_t da = mk_desc(sR + st * 32768 + (warp >> 2) * 1024, 2048, 128, 0), db = mk_desc(sR + st * 32768 + 16384, 8192, 1024, 1);
    if (s == 0) TS(5, 2);
    wg_fence();
    wgmma_ss_n128_t1(acc, da, db, s);
    wgmma_ss_n128_t1(acc, da + 256, db + 128, 1);
    wgmma_ss_n128_t1(acc, da + 512, db + 256, 1);
    wgmma_ss_n128_t1(acc, da + 768, db + 384, 1);
    wg_commit();
    wg_wait<1>();
    if (s > 0 && s < 6 && lane == 0) mbar_arrive(bE + 8 * (s - 1));
  }
  wg_wait<0>();
  reg_fence(acc);
  TS(5, 3);
  asm volatile("barrier.cluster.wait.aligned;" ::: "memory");
  uint32_t rem;
  asm("mapa.shared::cluster.u32 %0,%1,%2;" : "=r"(rem) : "r"(sX + tid * 16), "r"(kh ^ 1));
#pragma unroll
  for (int j = 0; j < 8; j++) {
    float v[4];
#pragma unroll
    for (int i = 0; i < 4; i++) { v[i] = kh ? acc[4 * j + i] : acc[32 + 4 * j + i]; acc[4 * j + i] = kh ? acc[32 + 4 * j + i] : acc[4 * j + i]; }
    asm volatile("st.shared::cluster.v4.f32 [%0],{%1,%2,%3,%4};" ::"r"(rem + j * 4096), "f"(v[0]), "f"(v[1]), "f"(v[2]), "f"(v[3]) : "memory");
  }
  asm volatile("barrier.cluster.arrive.release.aligned;" ::: "memory");
  asm volatile("barrier.cluster.wait.acquire.aligned;" ::: "memory");
  TS(5, 5);
  const uint32_t sw = sR + warp * 2048;
#pragma unroll
  for (int j = 0; j < 8; j++) {
    const float4 p = *(const float4*)(smem + 6 * 32768 + j * 4096 + tid * 16);
    xr[2 * j] = pack_rn(fmaf(gb[j].x, acc[4 * j] + p.x, blo(xr[2 * j])), fmaf(gb[j].y, acc[4 * j + 1] + p.y, bhi(xr[2 * j])));
    xr[2 * j + 1] = pack_rn(fmaf(gb[j].x, acc[4 * j + 2] + p.z, blo(xr[2 * j + 1])), fmaf(gb[j].y, acc[4 * j + 3] + p.w, bhi(xr[2 * j + 1])));
    if (j & 1) asm volatile("stmatrix.sync.aligned.m8n8.x4.shared.b16 [%0],{%1,%2,%3,%4};" ::"r"(sw + (lane & 15) * 128 + (((j - 1 + (lane >> 4)) ^ (lane & 7)) << 4)),
                            "r"(xr[2 * j - 2]), "r"(xr[2 * j - 1]), "r"(xr[2 * j]), "r"(xr[2 * j + 1]) : "memory");
  }
  __syncwarp();
#pragma unroll
  for (int i = 0; i < 4; i++) {
    const int r = i * 4 + (lane >> 3);
    *(uint4*)(out + (rb * 128 + warp * 16 + r) * 512 + ct * 128 + kh * 64 + (lane & 7) * 8) = *(const uint4*)(smem + warp * 2048 + r * 128 + (((lane ^ r) & 7) << 4));
  }
  TS(5, 4);
}

typedef CUresult (*EncFn)(CUtensorMap*, CUtensorMapDataType, cuuint32_t, void*, const cuuint64_t*, const cuuint64_t*, const cuuint32_t*,
                          const cuuint32_t*, CUtensorMapInterleave, CUtensorMapSwizzle, CUtensorMapL2promotion, CUtensorMapFloatOOBfill);
static void mk_map(EncFn f, CUtensorMap* m, const void* p, int rows, int cols, int box_rows) {
  cuuint64_t dim[2] = {(cuuint64_t)cols, (cuuint64_t)rows}, str[1] = {(cuuint64_t)cols * 2};
  cuuint32_t box[2] = {64, (cuuint32_t)box_rows}, es[2] = {1, 1};
  f(m, CU_TENSOR_MAP_DATA_TYPE_BFLOAT16, 2, (void*)p, dim, str, box, es, CU_TENSOR_MAP_INTERLEAVE_NONE, CU_TENSOR_MAP_SWIZZLE_128B,
    CU_TENSOR_MAP_L2_PROMOTION_L2_128B, CU_TENSOR_MAP_FLOAT_OOB_FILL_NONE);
}
template <typename... KA, typename... A>
static void launch(void (*k)(KA...), int grid, int block, int smem, bool pdl, A... args) {
  cudaLaunchConfig_t cfg = {};
  cfg.gridDim = dim3(grid); cfg.blockDim = dim3(block); cfg.dynamicSmemBytes = smem; cfg.stream = cudaStreamPerThread;
  cudaLaunchAttribute at[1];
  at[0].id = cudaLaunchAttributeProgrammaticStreamSerialization; at[0].val.programmaticStreamSerializationAllowed = 1;
  cfg.attrs = at; cfg.numAttrs = pdl ? 1 : 0;
  cudaLaunchKernelEx(&cfg, k, args...);
}
extern "C" void kernel_launch(void* const* d_in, const int* in_sizes, int n_in, void* d_out, int out_size) {
  const bf16 *x = (const bf16*)d_in[0], *wqkv = (const bf16*)d_in[1], *wo = (const bf16*)d_in[2], *w1 = (const bf16*)d_in[4],
             *w3 = (const bf16*)d_in[5], *w2 = (const bf16*)d_in[6], *c = (const bf16*)d_in[7], *wmod = (const bf16*)d_in[8];
  void* fp = nullptr;
  cudaDriverEntryPointQueryResult qr;
  cudaGetDriverEntryPoint("cuTensorMapEncodeTiled", &fp, cudaEnableDefault, &qr);
  EncFn f = (EncFn)fp;
  CUtensorMap mX, mQ, mO, m1, m3, m2;
  mk_map(f, &mX, x, S_, D_, 128); mk_map(f, &mQ, wqkv, D_, 3 * D_, 64); mk_map(f, &mO, wo, D_, D_, 64);
  mk_map(f, &m1, w1, D_, F_, 32); mk_map(f, &m3, w3, D_, F_, 32); mk_map(f, &m2, w2, F_, D_, 64);
  cudaFuncSetAttribute(k_lngemm<false>, cudaFuncAttributeMaxDynamicSharedMemorySize, LN_SMEM);
  cudaFuncSetAttribute(k_lngemm<true>, cudaFuncAttributeMaxDynamicSharedMemorySize, LN_SMEM);
  cudaFuncSetAttribute(k_attn, cudaFuncAttributeMaxDynamicSharedMemorySize, AT_SMEM);
  cudaFuncSetAttribute(k_wo, cudaFuncAttributeMaxDynamicSharedMemorySize, WO_SMEM);
  cudaFuncSetAttribute(k_w2, cudaFuncAttributeMaxDynamicSharedMemorySize, W2_SMEM);
  launch(k_lngemm<false>, 128, 384, LN_SMEM, false, mX, mQ, mQ, c, wmod, x);
  launch(k_attn, 132, 512, AT_SMEM, true, wo, w1, w3, w2, c, wmod, 0u);
  launch(k_wo, 128, 256, WO_SMEM, true, mO, x);
  launch(k_lngemm<true>, 128, 384, LN_SMEM, true, mX, m1, m3, c, wmod, x);
  launch(k_w2, 128, 288, W2_SMEM, true, m2, (bf16*)d_out);
}
```

```cpp
#include <cuda_runtime.h>
#include <cuda_bf16.h>
#include <cuda.h>
#include <stdint.h>
typedef __nv_bfloat16 bf16;
constexpr int S_ = 2048, D_ = 512, F_ = 1376;
__device__ __align__(1024) float g_mod[3072];
__device__ __align__(1024) uint32_t g_modv[1024 + 4096];
__device__ __align__(1024) bf16 g_qkv[192 * 2048 * 8];
__device__ __align__(1024) float g_kmax[32 * 128];
__device__ __align__(1024) bf16 g_o[16 * 64 * 128 * 8];
__device__ __align__(1024) bf16 g_x1[16 * 64 * 128 * 8];
__device__ __align__(1024) float2 g_st[2048 * 8];
__device__ __align__(1024) bf16 g_h[16 * 172 * 128 * 8];

__device__ __forceinline__ uint32_t smem_u32(const void* p) { return (uint32_t)__cvta_generic_to_shared(p); }
__device__ __forceinline__ void mbar_init(uint32_t b, int n) { asm volatile("mbarrier.init.shared::cta.b64 [%0],%1;" ::"r"(b), "r"(n) : "memory"); }
__device__ __forceinline__ void mbar_expect(uint32_t b, int bytes) { asm volatile("mbarrier.arrive.expect_tx.shared::cta.b64 _,[%0],%1;" ::"r"(b), "r"(bytes) : "memory"); }
__device__ __forceinline__ void mbar_arrive(uint32_t b) { asm volatile("mbarrier.arrive.shared::cta.b64 _,[%0];" ::"r"(b) : "memory"); }
__device__ __forceinline__ void mbar_wait(uint32_t b, int parity) {
  asm volatile("{\n.reg .pred p;\n.reg .u32 n;\nmov.u32 n,0;\nLW:\nmbarrier.try_wait.parity.shared::cta.b64 p,[%0],%1;\n@p bra LD;\n"
               "add.u32 n,n,1;\nsetp.lt.u32 p,n,4194304;\n@p bra LW;\nLD:\n}\n" ::"r"(b), "r"(parity) : "memory");
}
__device__ __forceinline__ void fence_init() { asm volatile("fence.mbarrier_init.release.cluster;" ::: "memory"); }
__device__ __forceinline__ void fence_async() { asm volatile("fence.proxy.async.shared::cta;" ::: "memory"); }
__device__ __forceinline__ void bulk_load(uint32_t dst, const void* src, int bytes, uint32_t bar) {
  asm volatile("cp.async.bulk.shared::cluster.global.mbarrier::complete_tx::bytes [%0],[%1],%2,[%3];" ::"r"(dst), "l"(src), "r"(bytes), "r"(bar) : "memory");
}
__device__ __forceinline__ void tma2d(uint32_t dst, const CUtensorMap* m, int c0, int c1, uint32_t bar) {
  asm volatile("cp.async.bulk.tensor.2d.shared::cluster.global.mbarrier::complete_tx::bytes [%0],[%1,{%3,%4}],[%2];" ::"r"(dst), "l"(m), "r"(bar), "r"(c0), "r"(c1) : "memory");
}
__device__ __forceinline__ void bulk_load_mc(uint32_t dst, const void* src, int bytes, uint32_t bar) {
  asm volatile("cp.async.bulk.shared::cluster.global.mbarrier::complete_tx::bytes.multicast::cluster [%0],[%1],%2,[%3],%4;" ::"r"(dst), "l"(src), "r"(bytes), "r"(bar), "h"((uint16_t)3) : "memory");
}
__device__ __forceinline__ void tma2d_mc(uint32_t dst, const CUtensorMap* m, int c0, int c1, uint32_t bar) {
  asm volatile("cp.async.bulk.tensor.2d.shared::cluster.global.mbarrier::complete_tx::bytes.multicast::cluster [%0],[%1,{%3,%4}],[%2],%5;" ::"r"(dst), "l"(m), "r"(bar), "r"(c0), "r"(c1), "h"((uint16_t)3) : "memory");
}
__device__ __forceinline__ void cluster_arrive() { asm volatile("barrier.cluster.arrive.relaxed.aligned;" ::: "memory"); }
__device__ __forceinline__ void cluster_wait() { asm volatile("barrier.cluster.wait.aligned;" ::: "memory"); }
__device__ __forceinline__ void cluster_sync() { asm volatile("barrier.cluster.arrive.release.aligned;\nbarrier.cluster.wait.acquire.aligned;" ::: "memory"); }
__device__ __forceinline__ void l2_prefetch(const void* p, int bytes) { asm volatile("cp.async.bulk.prefetch.L2.global [%0],%1;" ::"l"(p), "r"(bytes) : "memory"); }
__device__ __forceinline__ void pdl_launch() { asm volatile("griddepcontrol.launch_dependents;" ::: "memory"); }
__device__ __forceinline__ void pdl_wait() { asm volatile("griddepcontrol.wait;" ::: "memory"); }
__device__ __forceinline__ void wg_fence() { asm volatile("wgmma.fence.sync.aligned;" ::: "memory"); }
__device__ __forceinline__ void wg_commit() { asm volatile("wgmma.commit_group.sync.aligned;" ::: "memory"); }
template <int N> __device__ __forceinline__ void wg_wait() { asm volatile("wgmma.wait_group.sync.aligned %0;" ::"n"(N) : "memory"); }
template <int N> __device__ __forceinline__ void reg_fence(float (&d)[N]) {
#pragma unroll
  for (int i = 0; i < N; i++) asm volatile("" : "+f"(d[i])::"memory");
}
template <int N> __device__ __forceinline__ void zero(float (&d)[N]) {
#pragma unroll
  for (int i = 0; i < N; i++) d[i] = 0.f;
  reg_fence(d);
}
__device__ __forceinline__ uint64_t mk_desc(uint32_t addr, uint32_t lbo, uint32_t sbo, uint32_t mode) {
  return (uint64_t)((addr >> 4) & 0x3FFF) | ((uint64_t)(lbo >> 4) << 16) | ((uint64_t)(sbo >> 4) << 32) | ((uint64_t)mode << 62);
}
__device__ __forceinline__ void ldsm4(uint32_t a, uint32_t (&r)[4]) {
  asm volatile("ldmatrix.sync.aligned.m8n8.x4.shared.b16 {%0,%1,%2,%3},[%4];" : "=r"(r[0]), "=r"(r[1]), "=r"(r[2]), "=r"(r[3]) : "r"(a) : "memory");
}
__device__ __forceinline__ uint32_t pack_rn(float lo, float hi) { uint32_t r; asm("cvt.rn.bf16x2.f32 %0,%1,%2;" : "=r"(r) : "f"(hi), "f"(lo)); return r; }
__device__ __forceinline__ uint32_t pack_rz(float lo, float hi) { uint32_t r; asm("cvt.rz.bf16x2.f32 %0,%1,%2;" : "=r"(r) : "f"(hi), "f"(lo)); return r; }
__device__ __forceinline__ float blo(uint32_t u) { return __uint_as_float(u << 16); }
__device__ __forceinline__ float bhi(uint32_t u) { return __uint_as_float(u & 0xFFFF0000u); }
__device__ __forceinline__ float rbf(float x) { return __bfloat162float(__float2bfloat16_rn(x)); }
__device__ __forceinline__ float qsum(float v) { v += __shfl_xor_sync(~0u, v, 1); return v + __shfl_xor_sync(~0u, v, 2); }
__device__ __forceinline__ float ex2(float x) { float r; asm("ex2.approx.ftz.f32 %0,%1;" : "=f"(r) : "f"(x)); return r; }
#define TS(k, i)
__device__ __forceinline__ void wgmma_rs_n176_t1(float (&d)[88],uint32_t a0,uint32_t a1,uint32_t a2,uint32_t a3,uint64_t db,int sc){
  asm volatile("{\n.reg .pred p;\nsetp.ne.b32 p,%93,0;\n"
    "wgmma.mma_async.sync.aligned.m64n176k16.f32.bf16.bf16 {%0,%1,%2,%3,%4,%5,%6,%7,%8,%9,%10,%11,%12,%13,%14,%15,%16,%17,%18,%19,%20,%21,%22,%23,%24,%25,%26,%27,%28,%29,%30,%31,%32,%33,%34,%35,%36,%37,%38,%39,%40,%41,%42,%43,%44,%45,%46,%47,%48,%49,%50,%51,%52,%53,%54,%55,%56,%57,%58,%59,%60,%61,%62,%63,%64,%65,%66,%67,%68,%69,%70,%71,%72,%73,%74,%75,%76,%77,%78,%79,%80,%81,%82,%83,%84,%85,%86,%87},{%88,%89,%90,%91},%92,p,1,1,1;\n}\n"
    :"+f"(d[0]),"+f"(d[1]),"+f"(d[2]),"+f"(d[3]),"+f"(d[4]),"+f"(d[5]),"+f"(d[6]),"+f"(d[7]),"+f"(d[8]),"+f"(d[9]),"+f"(d[10]),"+f"(d[11]),"+f"(d[12]),"+f"(d[13]),"+f"(d[14]),"+f"(d[15]),"+f"(d[16]),"+f"(d[17]),"+f"(d[18]),"+f"(d[19]),"+f"(d[20]),"+f"(d[21]),"+f"(d[22]),"+f"(d[23]),"+f"(d[24]),"+f"(d[25]),"+f"(d[26]),"+f"(d[27]),"+f"(d[28]),"+f"(d[29]),"+f"(d[30]),"+f"(d[31]),"+f"(d[32]),"+f"(d[33]),"+f"(d[34]),"+f"(d[35]),"+f"(d[36]),"+f"(d[37]),"+f"(d[38]),"+f"(d[39]),"+f"(d[40]),"+f"(d[41]),"+f"(d[42]),"+f"(d[43]),"+f"(d[44]),"+f"(d[45]),"+f"(d[46]),"+f"(d[47]),"+f"(d[48]),"+f"(d[49]),"+f"(d[50]),"+f"(d[51]),"+f"(d[52]),"+f"(d[53]),"+f"(d[54]),"+f"(d[55]),"+f"(d[56]),"+f"(d[57]),"+f"(d[58]),"+f"(d[59]),"+f"(d[60]),"+f"(d[61]),"+f"(d[62]),"+f"(d[63]),"+f"(d[64]),"+f"(d[65]),"+f"(d[66]),"+f"(d[67]),"+f"(d[68]),"+f"(d[69]),"+f"(d[70]),"+f"(d[71]),"+f"(d[72]),"+f"(d[73]),"+f"(d[74]),"+f"(d[75]),"+f"(d[76]),"+f"(d[77]),"+f"(d[78]),"+f"(d[79]),"+f"(d[80]),"+f"(d[81]),"+f"(d[82]),"+f"(d[83]),"+f"(d[84]),"+f"(d[85]),"+f"(d[86]),"+f"(d[87])
    :"r"(a0),"r"(a1),"r"(a2),"r"(a3),"l"(db),"r"(sc));
}
__device__ __forceinline__ void wgmma_rs_n192_t1(float (&d)[96],uint32_t a0,uint32_t a1,uint32_t a2,uint32_t a3,uint64_t db,int sc){
  asm volatile("{\n.reg .pred p;\nsetp.ne.b32 p,%101,0;\n"
    "wgmma.mma_async.sync.aligned.m64n192k16.f32.bf16.bf16 {%0,%1,%2,%3,%4,%5,%6,%7,%8,%9,%10,%11,%12,%13,%14,%15,%16,%17,%18,%19,%20,%21,%22,%23,%24,%25,%26,%27,%28,%29,%30,%31,%32,%33,%34,%35,%36,%37,%38,%39,%40,%41,%42,%43,%44,%45,%46,%47,%48,%49,%50,%51,%52,%53,%54,%55,%56,%57,%58,%59,%60,%61,%62,%63,%64,%65,%66,%67,%68,%69,%70,%71,%72,%73,%74,%75,%76,%77,%78,%79,%80,%81,%82,%83,%84,%85,%86,%87,%88,%89,%90,%91,%92,%93,%94,%95},{%96,%97,%98,%99},%100,p,1,1,1;\n}\n"
    :"+f"(d[0]),"+f"(d[1]),"+f"(d[2]),"+f"(d[3]),"+f"(d[4]),"+f"(d[5]),"+f"(d[6]),"+f"(d[7]),"+f"(d[8]),"+f"(d[9]),"+f"(d[10]),"+f"(d[11]),"+f"(d[12]),"+f"(d[13]),"+f"(d[14]),"+f"(d[15]),"+f"(d[16]),"+f"(d[17]),"+f"(d[18]),"+f"(d[19]),"+f"(d[20]),"+f"(d[21]),"+f"(d[22]),"+f"(d[23]),"+f"(d[24]),"+f"(d[25]),"+f"(d[26]),"+f"(d[27]),"+f"(d[28]),"+f"(d[29]),"+f"(d[30]),"+f"(d[31]),"+f"(d[32]),"+f"(d[33]),"+f"(d[34]),"+f"(d[35]),"+f"(d[36]),"+f"(d[37]),"+f"(d[38]),"+f"(d[39]),"+f"(d[40]),"+f"(d[41]),"+f"(d[42]),"+f"(d[43]),"+f"(d[44]),"+f"(d[45]),"+f"(d[46]),"+f"(d[47]),"+f"(d[48]),"+f"(d[49]),"+f"(d[50]),"+f"(d[51]),"+f"(d[52]),"+f"(d[53]),"+f"(d[54]),"+f"(d[55]),"+f"(d[56]),"+f"(d[57]),"+f"(d[58]),"+f"(d[59]),"+f"(d[60]),"+f"(d[61]),"+f"(d[62]),"+f"(d[63]),"+f"(d[64]),"+f"(d[65]),"+f"(d[66]),"+f"(d[67]),"+f"(d[68]),"+f"(d[69]),"+f"(d[70]),"+f"(d[71]),"+f"(d[72]),"+f"(d[73]),"+f"(d[74]),"+f"(d[75]),"+f"(d[76]),"+f"(d[77]),"+f"(d[78]),"+f"(d[79]),"+f"(d[80]),"+f"(d[81]),"+f"(d[82]),"+f"(d[83]),"+f"(d[84]),"+f"(d[85]),"+f"(d[86]),"+f"(d[87]),"+f"(d[88]),"+f"(d[89]),"+f"(d[90]),"+f"(d[91]),"+f"(d[92]),"+f"(d[93]),"+f"(d[94]),"+f"(d[95])
    :"r"(a0),"r"(a1),"r"(a2),"r"(a3),"l"(db),"r"(sc));
}
__device__ __forceinline__ void wgmma_rs_n24_t1(float (&d)[12],uint32_t a0,uint32_t a1,uint32_t a2,uint32_t a3,uint64_t db,int sc){
  asm volatile("{\n.reg .pred p;\nsetp.ne.b32 p,%17,0;\n"
    "wgmma.mma_async.sync.aligned.m64n24k16.f32.bf16.bf16 {%0,%1,%2,%3,%4,%5,%6,%7,%8,%9,%10,%11},{%12,%13,%14,%15},%16,p,1,1,1;\n}\n"
    :"+f"(d[0]),"+f"(d[1]),"+f"(d[2]),"+f"(d[3]),"+f"(d[4]),"+f"(d[5]),"+f"(d[6]),"+f"(d[7]),"+f"(d[8]),"+f"(d[9]),"+f"(d[10]),"+f"(d[11])
    :"r"(a0),"r"(a1),"r"(a2),"r"(a3),"l"(db),"r"(sc));
}
__device__ __forceinline__ void wgmma_rs_n64_t0(float (&d)[32],uint32_t a0,uint32_t a1,uint32_t a2,uint32_t a3,uint64_t db,int sc){
  asm volatile("{\n.reg .pred p;\nsetp.ne.b32 p,%37,0;\n"
    "wgmma.mma_async.sync.aligned.m64n64k16.f32.bf16.bf16 {%0,%1,%2,%3,%4,%5,%6,%7,%8,%9,%10,%11,%12,%13,%14,%15,%16,%17,%18,%19,%20,%21,%22,%23,%24,%25,%26,%27,%28,%29,%30,%31},{%32,%33,%34,%35},%36,p,1,1,0;\n}\n"
    :"+f"(d[0]),"+f"(d[1]),"+f"(d[2]),"+f"(d[3]),"+f"(d[4]),"+f"(d[5]),"+f"(d[6]),"+f"(d[7]),"+f"(d[8]),"+f"(d[9]),"+f"(d[10]),"+f"(d[11]),"+f"(d[12]),"+f"(d[13]),"+f"(d[14]),"+f"(d[15]),"+f"(d[16]),"+f"(d[17]),"+f"(d[18]),"+f"(d[19]),"+f"(d[20]),"+f"(d[21]),"+f"(d[22]),"+f"(d[23]),"+f"(d[24]),"+f"(d[25]),"+f"(d[26]),"+f"(d[27]),"+f"(d[28]),"+f"(d[29]),"+f"(d[30]),"+f"(d[31])
    :"r"(a0),"r"(a1),"r"(a2),"r"(a3),"l"(db),"r"(sc));
}
__device__ __forceinline__ void wgmma_ss_n128_t1(float (&d)[64],uint64_t da,uint64_t db,int sc){
  asm volatile("{\n.reg .pred p;\nsetp.ne.b32 p,%66,0;\n"
    "wgmma.mma_async.sync.aligned.m64n128k16.f32.bf16.bf16 {%0,%1,%2,%3,%4,%5,%6,%7,%8,%9,%10,%11,%12,%13,%14,%15,%16,%17,%18,%19,%20,%21,%22,%23,%24,%25,%26,%27,%28,%29,%30,%31,%32,%33,%34,%35,%36,%37,%38,%39,%40,%41,%42,%43,%44,%45,%46,%47,%48,%49,%50,%51,%52,%53,%54,%55,%56,%57,%58,%59,%60,%61,%62,%63},%64,%65,p,1,1,0,1;\n}\n"
    :"+f"(d[0]),"+f"(d[1]),"+f"(d[2]),"+f"(d[3]),"+f"(d[4]),"+f"(d[5]),"+f"(d[6]),"+f"(d[7]),"+f"(d[8]),"+f"(d[9]),"+f"(d[10]),"+f"(d[11]),"+f"(d[12]),"+f"(d[13]),"+f"(d[14]),"+f"(d[15]),"+f"(d[16]),"+f"(d[17]),"+f"(d[18]),"+f"(d[19]),"+f"(d[20]),"+f"(d[21]),"+f"(d[22]),"+f"(d[23]),"+f"(d[24]),"+f"(d[25]),"+f"(d[26]),"+f"(d[27]),"+f"(d[28]),"+f"(d[29]),"+f"(d[30]),"+f"(d[31]),"+f"(d[32]),"+f"(d[33]),"+f"(d[34]),"+f"(d[35]),"+f"(d[36]),"+f"(d[37]),"+f"(d[38]),"+f"(d[39]),"+f"(d[40]),"+f"(d[41]),"+f"(d[42]),"+f"(d[43]),"+f"(d[44]),"+f"(d[45]),"+f"(d[46]),"+f"(d[47]),"+f"(d[48]),"+f"(d[49]),"+f"(d[50]),"+f"(d[51]),"+f"(d[52]),"+f"(d[53]),"+f"(d[54]),"+f"(d[55]),"+f"(d[56]),"+f"(d[57]),"+f"(d[58]),"+f"(d[59]),"+f"(d[60]),"+f"(d[61]),"+f"(d[62]),"+f"(d[63])
    :"l"(da),"l"(db),"r"(sc));
}
__device__ __forceinline__ void wgmma_ss_n64_t1(float (&d)[32],uint64_t da,uint64_t db,int sc){
  asm volatile("{\n.reg .pred p;\nsetp.ne.b32 p,%34,0;\n"
    "wgmma.mma_async.sync.aligned.m64n64k16.f32.bf16.bf16 {%0,%1,%2,%3,%4,%5,%6,%7,%8,%9,%10,%11,%12,%13,%14,%15,%16,%17,%18,%19,%20,%21,%22,%23,%24,%25,%26,%27,%28,%29,%30,%31},%32,%33,p,1,1,0,1;\n}\n"
    :"+f"(d[0]),"+f"(d[1]),"+f"(d[2]),"+f"(d[3]),"+f"(d[4]),"+f"(d[5]),"+f"(d[6]),"+f"(d[7]),"+f"(d[8]),"+f"(d[9]),"+f"(d[10]),"+f"(d[11]),"+f"(d[12]),"+f"(d[13]),"+f"(d[14]),"+f"(d[15]),"+f"(d[16]),"+f"(d[17]),"+f"(d[18]),"+f"(d[19]),"+f"(d[20]),"+f"(d[21]),"+f"(d[22]),"+f"(d[23]),"+f"(d[24]),"+f"(d[25]),"+f"(d[26]),"+f"(d[27]),"+f"(d[28]),"+f"(d[29]),"+f"(d[30]),"+f"(d[31])
    :"l"(da),"l"(db),"r"(sc));
}

__device__ __forceinline__ float silu_bf(bf16 c) { const float x = __bfloat162float(c); return rbf(x / (1.f + __expf(-x))); }
__device__ __forceinline__ void fma8(float (&a)[8], float s, const uint4& v) {
  a[0] += s * blo(v.x); a[1] += s * bhi(v.x); a[2] += s * blo(v.y); a[3] += s * bhi(v.y);
  a[4] += s * blo(v.z); a[5] += s * bhi(v.z); a[6] += s * blo(v.w); a[7] += s * bhi(v.w);
}
__device__ __forceinline__ float red8(float (&a)[8], int lane) {
#pragma unroll
  for (int w = 4; w >= 1; w >>= 1) {
    const bool up = lane & (w * 4);
#pragma unroll
    for (int j = 0; j < w; j++) a[j] = (up ? a[j + w] : a[j]) + __shfl_xor_sync(~0u, up ? a[j] : a[j + w], w * 4);
  }
  return a[0];
}
__device__ __forceinline__ float mod_fin(float s, int n) { s = rbf(s); return ((n >> 9) == 1 || (n >> 9) == 4) ? rbf(1.f + s) : s; }
__device__ __forceinline__ void poll4(uint2& a, uint2& b, uint2& c, uint2& d, const uint32_t* p, const uint32_t* q) {
  asm volatile("{\n.reg .pred p;\n.reg .u32 n,t;\nmov.u32 n,0;\nLW:\nld.relaxed.gpu.global.v2.u32 {%0,%1},[%8];\nld.relaxed.gpu.global.v2.u32 {%2,%3},[%8+64];\n"
               "ld.relaxed.gpu.global.v2.u32 {%4,%5},[%9];\nld.relaxed.gpu.global.v2.u32 {%6,%7},[%9+2048];\n"
               "lop3.b32 t,%0,%1,%2,0x80;\nlop3.b32 t,t,%3,%4,0x80;\nlop3.b32 t,t,%5,%6,0x80;\nlop3.b32 t,t,%7,1,0x80;\n"
               "setp.ne.u32 p,t,0;\n@p bra LD;\nadd.u32 n,n,1;\nsetp.lt.u32 p,n,1048576;\n@p bra LW;\nLD:\n}\n"
               : "=&r"(a.x), "=&r"(a.y), "=&r"(b.x), "=&r"(b.y), "=&r"(c.x), "=&r"(c.y), "=&r"(d.x), "=&r"(d.y) : "l"(p), "l"(q) : "memory");
}

constexpr int LN_SMEM = 131072 + 4 * 24576 + 2048 + 256 + 512;
template <bool FFN>
__global__ void __cluster_dims__(2, 1, 1) __launch_bounds__(384, 1) k_lngemm(const __grid_constant__ CUtensorMap mX, const __grid_constant__ CUtensorMap mB0,
                                                   const __grid_constant__ CUtensorMap mB1, const bf16* __restrict__ cv, const bf16* __restrict__ wm, const bf16* __restrict__ xg) {
  extern __shared__ __align__(1024) uint8_t smem[];
  const uint32_t sA = smem_u32(smem), sB = sA + 131072, sM = sB + 4 * 24576, bars = sM + 2048;
  const uint32_t bA = bars, bF = bars + 64, bE = bars + 96;
  const int tid = threadIdx.x, warp = tid >> 5, lane = tid & 31;
  const int pr = blockIdx.x & 1, rb = FFN ? (blockIdx.x >> 4) * 2 + pr : blockIdx.x >> 3, ct = FFN ? (blockIdx.x >> 1) & 7 : blockIdx.x & 7;
  constexpr int NST = FFN ? 16 : 8, KS = FFN ? 2 : 4, BOX = FFN ? 4096 : 8192;
  TS(FFN ? 4 : 1, 0);
  pdl_launch();
  float* red = (float*)(smem + (bars - sA) + 256);
  if (tid == 256) {
    for (int i = 0; i < 8; i++) mbar_init(bA + 8 * i, 1);
    for (int i = 0; i < 4; i++) { mbar_init(bF + 8 * i, 1); mbar_init(bE + 8 * i, FFN ? 16 : 8); }
    fence_init();
  }
  __syncwarp();
  cluster_arrive();
  uint4 wv0, wv1, xv[4];
  bf16 cv0, cv1;
  if (!FFN && tid < 256) {
    wv0 = __ldg((const uint4*)(wm + tid * 3072 + blockIdx.x * 8)); wv1 = __ldg((const uint4*)(wm + (tid + 256) * 3072 + blockIdx.x * 8));
    cv0 = cv[tid]; cv1 = cv[tid + 256];
#pragma unroll
    for (int i = 0; i < 4; i++) xv[i] = __ldg((const uint4*)(xg + (blockIdx.x * 16 + (tid >> 4)) * 512 + i * 128 + (tid & 15) * 8));
  }
  cluster_wait();
  if (!FFN) TS(0, 2);
  if (warp >= 8) {
    asm volatile("setmaxnreg.dec.sync.aligned.u32 40;");
    if (tid == 256) {
      auto loadB = [&](int s) {
        const uint32_t d = sB + (s & 3) * 24576, b = bF + (s & 3) * 8;
        mbar_expect(b, 24576);
        for (int j = 0; j < 3; j++) {
          if (FFN) tma2d_mc(d + (pr * 3 + j) * BOX, pr ? &mB1 : &mB0, ct * 176 + j * 64, s * 32, b);
          else tma2d(d + j * BOX, &mB0, ct * 192 + j * 64, s * 64, b);
        }
      };
      for (int i = 0; i < 8; i++) mbar_expect(bA + 8 * i, 16384);
      for (int s = 0; s < 4; s++) {
        const int i = s * 2 + (ct & 1);
        if (!FFN) tma2d_mc(sA + i * 16384, &mX, i * 64, rb * 128, bA + 8 * i);
        loadB(s);
      }
      if (FFN) {
        pdl_wait();
        for (int i = 0; i < 8; i++) bulk_load(sA + i * 16384, g_x1 + (rb * 64 + i * 8) * 1024, 16384, bA + 8 * i);
      }
      for (int s = 4; s < NST; s++) { mbar_wait(bE + (s & 3) * 8, ((s >> 2) - 1) & 1); loadB(s); }
    }
  } else {
  asm volatile("setmaxnreg.inc.sync.aligned.u32 232;");
  const int g = lane >> 2, t = lane & 3;
  const int lr = warp * 16 + (lane & 7) + ((lane >> 3) & 1) * 8;
  auto aaddr = [&](int ks) -> uint32_t {
    if (FFN) return sA + (ks * 2 + (lane >> 4)) * 2048 + lr * 16;
    return sA + (ks >> 2) * 16384 + lr * 128 + ((((ks & 3) * 2 + (lane >> 4)) ^ (lr & 7)) << 4);
  };
  const int row0 = rb * 128 + warp * 16 + g;
  float2 msh, msc;
  uint2 sh, sc;
  float rs0, rs1, nm0, nm1;
  if (!FFN) {
    {
      float a[8] = {0, 0, 0, 0, 0, 0, 0, 0};
      fma8(a, silu_bf(cv0), wv0); fma8(a, silu_bf(cv1), wv1);
      if (a[0] != 123.f) TS(0, 3);
      const float s = qsum(red8(a, lane));
      if (t == 0) red[warp * 8 + g] = s;
      asm volatile("bar.sync 1,256;" ::: "memory");
      if (tid < 8) {
        float r = 0;
#pragma unroll
        for (int i = 0; i < 8; i++) r += red[i * 8 + tid];
        const int n = blockIdx.x * 8 + tid;
        asm volatile("st.relaxed.gpu.global.u32 [%0],%1;" ::"l"(g_modv + n), "r"(__float_as_uint(mod_fin(r, n)) | 1u) : "memory");
      }
      TS(0, 1);
    }
    {
      float v[32], s = 0, q = 0;
#pragma unroll
      for (int i = 0; i < 16; i++) { const uint32_t u = ((const uint32_t*)xv)[i]; v[2 * i] = blo(u); v[2 * i + 1] = bhi(u); s += v[2 * i] + v[2 * i + 1]; }
      s = qsum(s); s += __shfl_xor_sync(~0u, s, 4); s += __shfl_xor_sync(~0u, s, 8);
      const float m = s * (1.f / 512);
#pragma unroll
      for (int i = 0; i < 32; i++) q += (v[i] - m) * (v[i] - m);
      q = qsum(q); q += __shfl_xor_sync(~0u, q, 4); q += __shfl_xor_sync(~0u, q, 8);
      const float rs = rsqrtf(q * (1.f / 512) + 1e-5f);
      if ((tid & 15) == 0)
        asm volatile("st.relaxed.gpu.global.v2.u32 [%0],{%1,%2};" ::"l"(g_modv + 1024 + (blockIdx.x * 16 + (tid >> 4)) * 2), "r"(__float_as_uint(rs) | 1u), "r"(__float_as_uint(-m * rs) | 1u) : "memory");
    }
    TS(0, 4);
    uint2 p0, p1;
    poll4(p0, p1, sh, sc, g_modv + 1024 + row0 * 2, g_modv + tid * 2);
    rs0 = __uint_as_float(p0.x); nm0 = __uint_as_float(p0.y); rs1 = __uint_as_float(p1.x); nm1 = __uint_as_float(p1.y);
    TS(1, 1);
  } else {
    pdl_wait();
    TS(4, 1);
    msh = *(const float2*)(g_mod + 1536 + tid * 2); msc = *(const float2*)(g_mod + 2048 + tid * 2);
    const float4 p0 = *(const float4*)(g_st + row0 * 8 + t * 2), p1 = *(const float4*)(g_st + (row0 + 8) * 8 + t * 2);
    const float m0 = qsum(p0.x + p0.z) * 0.125f, m1 = qsum(p1.x + p1.z) * 0.125f;
    const float v0 = qsum(p0.y + p0.w + 64.f * ((p0.x - m0) * (p0.x - m0) + (p0.z - m0) * (p0.z - m0)));
    const float v1 = qsum(p1.y + p1.w + 64.f * ((p1.x - m1) * (p1.x - m1) + (p1.z - m1) * (p1.z - m1)));
    rs0 = rsqrtf(v0 * (1.f / 512) + 1e-5f); rs1 = rsqrtf(v1 * (1.f / 512) + 1e-5f);
    nm0 = -m0 * rs0; nm1 = -m1 * rs1;
  }
  {
    uint32_t* m = (uint32_t*)(smem + (sM - sA)) + (tid >> 3) * 16 + (tid & 3) * 4 + ((tid >> 2) & 1);
    if (FFN) { m[0] = pack_rn(msc.x, msc.y); m[2] = pack_rn(msh.x, msh.y); }
    else { m[0] = __byte_perm(sc.x, sc.y, 0x7632); m[2] = __byte_perm(sh.x, sh.y, 0x7632); }
    asm volatile("bar.sync 1,256;" ::: "memory");
  }
  constexpr int NA = FFN ? 88 : 96;
  float acc0[NA], acc1[FFN ? 88 : 1];
  uint32_t a[2][KS][4];
  auto prep = [&](int ks, uint32_t(&o)[4]) {
    if ((ks & 3) == 0) mbar_wait(bA + 2 * ks, 0);
    uint32_t r[4]; ldsm4(aaddr(ks), r);
    const uint4 m = *(const uint4*)(smem + (sM - sA) + ks * 64 + t * 16);
#pragma unroll
    for (int i = 0; i < 4; i++) {
      const float rs = (i & 1) ? rs1 : rs0, nm = (i & 1) ? nm1 : nm0;
      const uint32_t n = pack_rn(fmaf(blo(r[i]), rs, nm), fmaf(bhi(r[i]), rs, nm));
      asm("fma.rn.bf16x2 %0,%1,%2,%3;" : "=r"(o[i]) : "r"(n), "r"(i < 2 ? m.x : m.y), "r"(i < 2 ? m.z : m.w));
    }
  };
  auto stage = [&](int s, uint32_t(&c)[KS][4], uint32_t(&n)[KS][4]) {
    mbar_wait(bF + (s & 3) * 8, (s >> 2) & 1);
    const uint64_t db = mk_desc(sB + (s & 3) * 24576, BOX, 1024, 1);
    wg_fence();
#pragma unroll
    for (int k = 0; k < KS; k++) {
      if constexpr (FFN) {
        wgmma_rs_n176_t1(acc0, c[k][0], c[k][1], c[k][2], c[k][3], db + k * 128, s + k);
        wgmma_rs_n176_t1(acc1, c[k][0], c[k][1], c[k][2], c[k][3], db + k * 128 + 3 * BOX / 16, s + k);
      } else {
        wgmma_rs_n192_t1(acc0, c[k][0], c[k][1], c[k][2], c[k][3], db + k * 128, s + k);
      }
    }
    wg_commit();
    wg_wait<1>();
    if (s > 0 && s <= NST - 4) {
      if (!FFN) { if (lane == 0) mbar_arrive(bE + ((s - 1) & 3) * 8); }
      else if (lane < 2) asm volatile("{\n.reg .b32 r;\nmapa.shared::cluster.u32 r,%0,%1;\nmbarrier.arrive.relaxed.cluster.shared::cluster.b64 _,[r];\n}" ::"r"(bE + ((s - 1) & 3) * 8), "r"(lane) : "memory");
    }
    if (s < NST - 1) {
#pragma unroll
      for (int k = 0; k < KS; k++) prep((s + 1) * KS + k, n[k]);
    }
  };
#pragma unroll
  for (int k = 0; k < KS; k++) prep(k, a[0][k]);
  TS(FFN ? 4 : 1, 2);
#pragma unroll 1
  for (int s = 0; s < NST; s += 2) { stage(s, a[0], a[1]); stage(s + 1, a[1], a[0]); }
  wg_wait<0>();
  reg_fence(acc0);
  TS(FFN ? 4 : 1, 3);
  if constexpr (FFN) {
    reg_fence(acc1);
    uint32_t* o = (uint32_t*)g_h + ((rb * 172 + ct * 22) * 128 + warp * 16 + g) * 4 + t;
#pragma unroll
    for (int j = 0; j < 22; j++) {
      if (ct * 22 + j < 172) {
        float h[4];
#pragma unroll
        for (int i = 0; i < 4; i++) { const float x = acc0[4 * j + i]; h[i] = __fdividef(x, 1.f + ex2(-1.4426950408889634f * x)) * acc1[4 * j + i]; }
        o[j * 512] = pack_rn(h[0], h[1]);
        o[j * 512 + 32] = pack_rn(h[2], h[3]);
      }
    }
  } else {
    uint32_t* o = (uint32_t*)g_qkv + (ct * 24 * 2048 + row0) * 4 + t;
#pragma unroll
    for (int j = 0; j < 24; j += 2) {
      const int G = ct * 24 + j;
      const float sc = G < 64 ? 0.25f * 1.4426950408889634f : 1.f;
      uint32_t p[4];
#pragma unroll
      for (int i = 0; i < 4; i++) p[i] = pack_rn(acc0[4 * j + 2 * i] * sc, acc0[4 * j + 2 * i + 1] * sc);
      o[j * 8192] = p[0]; o[j * 8192 + 32] = p[1]; o[(j + 1) * 8192] = p[2]; o[(j + 1) * 8192 + 32] = p[3];
      if (G >= 64 && G < 128) {
        float n0 = blo(p[0]) * blo(p[0]) + bhi(p[0]) * bhi(p[0]) + blo(p[2]) * blo(p[2]) + bhi(p[2]) * bhi(p[2]);
        float n1 = blo(p[1]) * blo(p[1]) + bhi(p[1]) * bhi(p[1]) + blo(p[3]) * blo(p[3]) + bhi(p[3]) * bhi(p[3]);
        n0 = qsum(n0); n1 = qsum(n1);
        const uint32_t mx = __reduce_max_sync(~0u, max(__float_as_uint(n0), __float_as_uint(n1)));
        if (lane == 0) g_kmax[((G - 64) >> 1) * 128 + rb * 8 + warp] = __uint_as_float(mx);
      }
    }
  }
  TS(FFN ? 4 : 1, 4);
}
}

#define SMASK 0xAAu
#define BRK 0
#define PACK 1
#define PP 1
constexpr int AT_SMEM = 5 * 32768 + 256;
__device__ __forceinline__ uint32_t exp2_pair_fma(float s0, float s1, float c, uint32_t ka, uint32_t kz) {
  uint32_t r;
  asm volatile("{\n.reg .b32 y0,y1,e,u,t;\n"
      "fma.rn.sat.f32 y0,%1,0f00000080,%3;\nfma.rn.sat.f32 y1,%2,0f00000080,%3;\n"
      "mad.lo.u32 e,y1,65536,y0;\n"
      "and.b32 u,e,0x007F007F;\n"
      "fma.rn.f16x2 u,u,%4,%5;\nfma.rn.f16x2 t,u,u,%6;\nfma.rn.f16x2 t,t,u,%7;\n"
      "lop3.b32 %0,t,0x007F007F,e,0xE2;\n}\n"
      : "=r"(r) : "f"(s0), "f"(s1), "f"(c), "r"(ka), "r"(0x36B236B2u), "r"(0x3C733C73u), "r"(0x47764776u), "r"(kz));
  return r;
}
__device__ __forceinline__ void attn_pass(float (&oa)[12], float (&ob)[12], const uint32_t (&q)[4], float m0, float m1, uint32_t sK, uint32_t bars, bool first, uint32_t kz) {
  const uint64_t dk = mk_desc(sK, 32768, 128, 0), dv = mk_desc(sK + 65536, 128, 32768, 0);
  const float c0 = (127.f - m0) * __uint_as_float(0x80u), c1 = (127.f - m1) * __uint_as_float(0x80u);
  const uint32_t ka = 0x7ACE7ACEu + kz;
  constexpr int NK = 64, NS = 32, NP = 16, NI = 32;
  auto qk = [&](float (&s)[NS], int i) { wgmma_rs_n64_t0(s, q[0], q[1], q[2], q[3], dk + i * NK, 0); };
  auto softmax = [&](float (&s)[NS], uint32_t (&p)[NP], uint32_t mask) {
    reg_fence(s);
    float e0, e1;
    int pend = -1;
#pragma unroll
    for (int t = 0; t < NP; t++) {
      const int j = (t & 3) * 4 + (t >> 2);
      if ((mask >> (t & 3)) & 1) {
        p[j] = exp2_pair_fma(s[2 * j], s[2 * j + 1], (j & 1) ? c1 : c0, ka, kz);
      } else {
        float f0, f1;
        asm volatile("ex2.approx.ftz.f32 %0,%2;\nex2.approx.ftz.f32 %1,%3;" : "=&f"(f0), "=f"(f1) : "f"(s[2 * j]), "f"(s[2 * j + 1]));
        if (pend >= 0) asm volatile("cvt.rn.bf16x2.f32 %0,%1,%2;" : "=r"(p[pend]) : "f"(e1), "f"(e0));
        e0 = f0; e1 = f1; pend = j;
      }
    }
    if (pend >= 0) asm volatile("cvt.rn.bf16x2.f32 %0,%1,%2;" : "=r"(p[pend]) : "f"(e1), "f"(e0));
#pragma unroll
    for (int j = 0; j < NP; j++) asm volatile("" : "+r"(p[j])::"memory");
  };
  auto pv = [&](uint32_t (&p)[NP], int i, uint32_t mask) {
#pragma unroll
    for (int k = 0; k < 4; k++) wgmma_rs_n24_t1(((mask >> k) & 1) ? ob : oa, p[4 * k], p[4 * k + 1], p[4 * k + 2], p[4 * k + 3], dv + i * NK + k * 16, 1);
  };
  auto ld = [&](int i) { if (first && (i & 3) == 0) mbar_wait(bars + i * 2, 0); };
  constexpr uint32_t M0 = SMASK & 15, M1 = SMASK >> 4;
  zero(oa); zero(ob);
  ld(0);
  if (first) TS(2, 2);
  float s[NS];
  zero(s);
  uint32_t p0[NP], p1[NP];
  wg_fence(); qk(s, 0); wg_commit(); wg_wait<0>(); softmax(s, p0, M0);
#pragma unroll 1
  for (int i = 0; i < NI - 2; i += 2) {
    wg_fence(); qk(s, i + 1); wg_commit(); pv(p0, i, M0); wg_commit(); wg_wait<1>(); softmax(s, p1, M1); wg_wait<0>();
    ld(i + 2);
    wg_fence(); qk(s, i + 2); wg_commit(); pv(p1, i + 1, M1); wg_commit(); wg_wait<1>(); softmax(s, p0, M0); wg_wait<0>();
  }
  wg_fence(); qk(s, NI - 1); wg_commit(); pv(p0, NI - 2, M0); wg_commit(); wg_wait<1>(); softmax(s, p1, M1); wg_wait<0>();
  wg_fence(); pv(p1, NI - 1, M1); wg_commit();
  wg_wait<0>();
  reg_fence(oa); reg_fence(ob);
}
__device__ __forceinline__ void mma16816(float (&d)[4], const uint32_t (&a)[4], uint32_t b0, uint32_t b1) {
  asm("mma.sync.aligned.m16n8k16.row.col.f32.bf16.bf16.f32 {%0,%1,%2,%3},{%4,%5,%6,%7},{%8,%9},{%0,%1,%2,%3};"
      : "+f"(d[0]), "+f"(d[1]), "+f"(d[2]), "+f"(d[3]) : "r"(a[0]), "r"(a[1]), "r"(a[2]), "r"(a[3]), "r"(b0), "r"(b1));
}
__device__ __forceinline__ void attn_safe(float (&o)[12], const uint32_t (&q)[4], uint32_t sK) {
  const int lane = threadIdx.x & 31;
  const uint32_t ka = sK + (lane >> 4) * 32768 + (lane & 15) * 16;
  float m0 = -INFINITY, m1 = -INFINITY;
#pragma unroll 2
  for (int i = 0; i < 128; i++) {
    uint32_t k[4]; ldsm4(ka + i * 256, k);
    float s0[4] = {0, 0, 0, 0}, s1[4] = {0, 0, 0, 0};
    mma16816(s0, q, k[0], k[2]); mma16816(s1, q, k[1], k[3]);
    m0 = fmaxf(fmaxf(m0, fmaxf(s0[0], s0[1])), fmaxf(s1[0], s1[1])); m1 = fmaxf(fmaxf(m1, fmaxf(s0[2], s0[3])), fmaxf(s1[2], s1[3]));
  }
  m0 = fmaxf(m0, __shfl_xor_sync(~0u, m0, 1)); m0 = fmaxf(m0, __shfl_xor_sync(~0u, m0, 2));
  m1 = fmaxf(m1, __shfl_xor_sync(~0u, m1, 1)); m1 = fmaxf(m1, __shfl_xor_sync(~0u, m1, 2));
  float o0[4] = {0, 0, 0, 0}, o1[4] = {0, 0, 0, 0}, o2[4] = {0, 0, 0, 0};
#pragma unroll 2
  for (int i = 0; i < 128; i++) {
    uint32_t k[4], v[4]; ldsm4(ka + i * 256, k);
    asm volatile("ldmatrix.sync.aligned.m8n8.x4.trans.shared.b16 {%0,%1,%2,%3},[%4];" : "=r"(v[0]), "=r"(v[1]), "=r"(v[2]), "=r"(v[3]) : "r"(ka + 65536 + i * 256) : "memory");
    float s0[4] = {0, 0, 0, 0}, s1[4] = {0, 0, 0, 0};
    mma16816(s0, q, k[0], k[2]); mma16816(s1, q, k[1], k[3]);
    const uint32_t p[4] = {pack_rn(ex2(s0[0] - m0), ex2(s0[1] - m0)), pack_rn(ex2(s0[2] - m1), ex2(s0[3] - m1)),
                           pack_rn(ex2(s1[0] - m0), ex2(s1[1] - m0)), pack_rn(ex2(s1[2] - m1), ex2(s1[3] - m1))};
    mma16816(o0, p, v[0], v[1]); mma16816(o1, p, v[2], v[3]); mma16816(o2, p, 0x3F803F80u, 0x3F803F80u);
  }
#pragma unroll
  for (int i = 0; i < 4; i++) { o[i] = o0[i]; o[4 + i] = o1[i]; o[8 + i] = o2[i]; }
}
__global__ void __cluster_dims__(2, 1, 1) __launch_bounds__(512, 1) k_attn(const bf16* wo, const bf16* w1, const bf16* w3, const bf16* w2, const bf16* __restrict__ cv, const bf16* __restrict__ wm, uint32_t kz) {
  extern __shared__ __align__(1024) uint8_t smem[];
  const uint32_t sK = smem_u32(smem), bars = sK + 5 * 32768;
  const int tid = threadIdx.x, warp = tid >> 5, lane = tid & 31, g = lane >> 2, t = lane & 3;
  pdl_launch();
  if (blockIdx.x < 4) {
    float* cs = (float*)smem;
    cs[tid] = silu_bf(cv[tid]);
    __syncthreads();
    const int n0 = 1024 + blockIdx.x * 512, r0 = (tid >> 6) * 64;
    float a[8] = {0, 0, 0, 0, 0, 0, 0, 0};
#pragma unroll 16
    for (int r = r0; r < r0 + 64; r++) fma8(a, cs[r], __ldg((const uint4*)(wm + r * 3072 + n0 + (tid & 63) * 8)));
    float4* rp = (float4*)(cs + 512 + tid * 8);
    rp[0] = make_float4(a[0], a[1], a[2], a[3]); rp[1] = make_float4(a[4], a[5], a[6], a[7]);
    __syncthreads();
    float s = 0;
#pragma unroll
    for (int i = 0; i < 8; i++) s += cs[512 + i * 512 + tid];
    g_mod[n0 + tid] = mod_fin(s, n0 + tid);
    return;
  }
  const int bid = blockIdx.x - 4, h = bid >> 2, qb = bid & 3;
  TS(2, 0);
  if (tid == 0) { for (int i = 0; i < 8; i++) { mbar_init(bars + 8 * i, 1); mbar_expect(bars + 8 * i, 16384); } fence_init(); }
#pragma unroll
  for (int i = 0; i < 4; i++) *(uint4*)(smem + 131072 + i * 8192 + tid * 16) = make_uint4(0x3F803F80u, 0x3F803F80u, 0x3F803F80u, 0x3F803F80u);
  fence_async();
  cluster_sync();
  pdl_wait();
  TS(2, 1);
  if (tid >= 472) g_modv[bid * 40 + tid - 472] = 0;
  const uint4 km4 = *(const uint4*)(g_kmax + h * 128 + lane * 4);
  const uint32_t* qp = (const uint32_t*)g_qkv + (h * 2 * 2048 + qb * 512 + warp * 16 + g) * 4 + t;
  uint32_t q[4] = {qp[0], qp[32], qp[8192], qp[8192 + 32]};
  if (lane == 0) {
    const int c = warp >> 1, pl = (qb & 1) + (warp & 1) * 2;
    bulk_load_mc(sK + pl * 32768 + c * 4096, g_qkv + ((64 + (pl >> 1) * 64 + h * 2 + (pl & 1)) * 2048 + c * 256) * 8, 4096, bars + 8 * c);
  }
  const uint32_t qn[4] = {qp[1024], qp[1024 + 32], qp[1024 + 8192], qp[1024 + 8192 + 32]};
  const float kmax = __uint_as_float(__reduce_max_sync(~0u, max(max(km4.x, km4.y), max(km4.z, km4.w))));
#pragma unroll 1
  for (int tile = 0; tile < 2; tile++) {
    const int row = qb * 512 + tile * 256 + warp * 16 + g;
    const float n0 = qsum(blo(q[0]) * blo(q[0]) + bhi(q[0]) * bhi(q[0]) + blo(q[2]) * blo(q[2]) + bhi(q[2]) * bhi(q[2]));
    const float n1 = qsum(blo(q[1]) * blo(q[1]) + bhi(q[1]) * bhi(q[1]) + blo(q[3]) * blo(q[3]) + bhi(q[3]) * bhi(q[3]));
    const float b0 = sqrtf(n0 * kmax) * 1.001f, b1 = sqrtf(n1 * kmax) * 1.001f;
    const float m0 = fmaxf(ceilf(b0 - 100.f), 0.f), m1 = fmaxf(ceilf(b1 - 100.f), 0.f);
    float o[12], ob[12];
    attn_pass(o, ob, q, m0, m1, sK, bars, tile == 0, kz);
    const float f0 = ex2(-m0), f1 = ex2(-m1);
#pragma unroll
    for (int i = 0; i < 12; i++) o[i] = fmaf(o[i], (i & 2) ? f1 : f0, ob[i]);
    bool ok = b0 < 220.f && b1 < 220.f && o[8] >= 0x1p-90f && o[10] >= 0x1p-90f;
#pragma unroll
    for (int i = 0; i < 12; i++) ok = ok && fabsf(o[i]) < INFINITY;
    if (!__all_sync(~0u, ok)) attn_safe(o, q, sK);
    const float r0 = 1.f / o[8], r1 = 1.f / o[10];
    uint32_t* op = (uint32_t*)g_o + (((row >> 7) * 64 + h * 2) * 128 + (row & 127)) * 4 + t;
    op[0] = pack_rn(o[0] * r0, o[1] * r0); op[32] = pack_rn(o[2] * r1, o[3] * r1);
    op[512] = pack_rn(o[4] * r0, o[5] * r0); op[512 + 32] = pack_rn(o[6] * r1, o[7] * r1);
    if (tile == 0 && tid == 32) {
      l2_prefetch((const char*)wo + bid * 4096, 4096);
      l2_prefetch((const char*)w1 + bid * 11008, 11008);
      l2_prefetch((const char*)w3 + bid * 11008, 11008);
      l2_prefetch((const char*)w2 + bid * 11008, 11008);
    }
#pragma unroll
    for (int i = 0; i < 4; i++) q[i] = qn[i];
    TS(2, 3 + tile);
  }
}

constexpr int WO_SMEM = 131072 + 65536 + 256;
__global__ void __cluster_dims__(2, 1, 1) __launch_bounds__(256, 1) k_wo(const __grid_constant__ CUtensorMap mW, const bf16* __restrict__ x) {
  extern __shared__ __align__(1024) uint8_t smem[];
  const uint32_t sA = smem_u32(smem), sB = sA + 131072, bars = sB + 65536;
  const int tid = threadIdx.x, warp = tid >> 5, lane = tid & 31, g = lane >> 2, t = lane & 3;
  const int rb = blockIdx.x >> 3, ct = blockIdx.x & 7;
  TS(3, 0);
  pdl_launch();
  if (tid == 0) {
    for (int i = 0; i < 8; i++) mbar_init(bars + 8 * i, 1);
    fence_init();
    for (int i = 0; i < 8; i++) { mbar_expect(bars + 8 * i, 24576); tma2d(sB + i * 8192, &mW, ct * 64, i * 64, bars + 8 * i); }
  }
  __syncwarp();
  cluster_arrive();
  const int lrow = warp * 16 + g;
  uint32_t xr[16];
  const uint32_t* xp = (const uint32_t*)(x + (rb * 128 + lrow) * 512 + ct * 64) + t;
#pragma unroll
  for (int j = 0; j < 8; j++) { xr[2 * j] = __ldg(xp + j * 4); xr[2 * j + 1] = __ldg(xp + j * 4 + 8 * 256); }
  cluster_wait();
  pdl_wait();
  TS(3, 1);
  if (tid == 0) for (int i = ct & 1; i < 8; i += 2) bulk_load_mc(sA + i * 16384, g_o + (rb * 64 + i * 8) * 1024, 16384, bars + 8 * i);
  float2 ga[8];
#pragma unroll
  for (int j = 0; j < 8; j++) ga[j] = *(const float2*)(g_mod + 1024 + ct * 64 + j * 8 + t * 2);
  float acc[32];
  const uint64_t da = mk_desc(sA + (warp >> 2) * 1024, 2048, 128, 0), db = mk_desc(sB, 8192, 1024, 1);
#pragma unroll
  for (int c = 0; c < 8; c++) {
    mbar_wait(bars + 8 * c, 0);
    if (c == 0) TS(3, 2);
    wg_fence();
#pragma unroll
    for (int k = 0; k < 4; k++) wgmma_ss_n64_t1(acc, da + (c * 4 + k) * 256, db + (c * 4 + k) * 128, c + k);
    wg_commit();
  }
  wg_wait<0>();
  reg_fence(acc);
  TS(3, 3);
  uint32_t* o = (uint32_t*)g_x1 + ((rb * 64 + ct * 8) * 128 + lrow) * 4 + t;
  float s0 = 0, s1 = 0;
#pragma unroll
  for (int j = 0; j < 8; j++) {
    xr[2 * j] = pack_rn(fmaf(ga[j].x, acc[4 * j], blo(xr[2 * j])), fmaf(ga[j].y, acc[4 * j + 1], bhi(xr[2 * j])));
    xr[2 * j + 1] = pack_rn(fmaf(ga[j].x, acc[4 * j + 2], blo(xr[2 * j + 1])), fmaf(ga[j].y, acc[4 * j + 3], bhi(xr[2 * j + 1])));
    o[j * 512] = xr[2 * j]; o[j * 512 + 32] = xr[2 * j + 1];
    s0 += blo(xr[2 * j]) + bhi(xr[2 * j]); s1 += blo(xr[2 * j + 1]) + bhi(xr[2 * j + 1]);
  }
  const float m0 = qsum(s0) * (1.f / 64), m1 = qsum(s1) * (1.f / 64);
  float v0 = 0, v1 = 0;
#pragma unroll
  for (int j = 0; j < 8; j++) {
    float d;
    d = blo(xr[2 * j]) - m0; v0 += d * d; d = bhi(xr[2 * j]) - m0; v0 += d * d;
    d = blo(xr[2 * j + 1]) - m1; v1 += d * d; d = bhi(xr[2 * j + 1]) - m1; v1 += d * d;
  }
  v0 = qsum(v0); v1 = qsum(v1);
  if (t == 0) g_st[(rb * 128 + lrow) * 8 + ct] = make_float2(m0, v0);
  if (t == 1) g_st[(rb * 128 + lrow + 8) * 8 + ct] = make_float2(m1, v1);
  TS(3, 4);
}

constexpr int W2_SMEM = 6 * 32768 + 32768 + 256;
__global__ void __cluster_dims__(2, 1, 1) __launch_bounds__(288, 1) k_w2(const __grid_constant__ CUtensorMap mW, bf16* __restrict__ out) {
  extern __shared__ __align__(1024) uint8_t smem[];
  const uint32_t sR = smem_u32(smem), sX = sR + 6 * 32768, bF = sX + 32768, bE = bF + 48, bX = bF + 96;
  const int tid = threadIdx.x, warp = tid >> 5, lane = tid & 31, g = lane >> 2, t = lane & 3;
  const int kh = blockIdx.x & 1, ct = (blockIdx.x >> 1) & 3, rb = blockIdx.x >> 3;
  TS(5, 0);
  pdl_launch();
  if (tid == 256) {
    for (int i = 0; i < 6; i++) { mbar_init(bF + 8 * i, 1); mbar_init(bE + 8 * i, 8); }
    for (int i = 0; i < 8; i++) { mbar_init(bX + 8 * i, 1); mbar_expect(bX + 8 * i, 4096); }
    fence_init();
  }
  __syncthreads();
  asm volatile("barrier.cluster.arrive.relaxed.aligned;" ::: "memory");
  if (warp == 8) {
    if (lane == 0) {
      auto abytes = [&](int s) { return (kh == 1 && s == 10) ? 8192 : 16384; };
      auto loadB = [&](int s) {
        const int st = s % 6;
        mbar_expect(bF + 8 * st, 16384 + abytes(s));
        for (int j = 0; j < 2; j++) tma2d(sR + st * 32768 + 16384 + j * 8192, &mW, ct * 128 + j * 64, kh * 704 + s * 64, bF + 8 * st);
      };
      auto loadA = [&](int s) { bulk_load(sR + (s % 6) * 32768, g_h + (rb * 172 + kh * 88 + s * 8) * 1024, abytes(s), bF + 8 * (s % 6)); };
      for (int s = 0; s < 6; s++) loadB(s);
      pdl_wait();
      for (int s = 0; s < 6; s++) loadA(s);
      for (int s = 6; s < 11; s++) { mbar_wait(bE + 8 * (s - 6), 0); loadB(s); loadA(s); }
    }
    __syncwarp();
    cluster_wait();
    return;
  }
  pdl_wait();
  TS(5, 1);
  const int lrow = warp * 16 + g;
  uint32_t xr[16];
  float2 gb[8];
  const uint32_t* xp = (const uint32_t*)g_x1 + ((rb * 64 + ct * 16 + kh * 8) * 128 + lrow) * 4 + t;
#pragma unroll
  for (int j = 0; j < 8; j++) {
    xr[2 * j] = xp[j * 512]; xr[2 * j + 1] = xp[j * 512 + 32];
    gb[j] = *(const float2*)(g_mod + 2560 + ct * 128 + kh * 64 + j * 8 + t * 2);
  }
  float acc[64];
#pragma unroll 1
  for (int s = 0; s < 11; s++) {
    const int st = s % 6;
    mbar_wait(bF + 8 * st, s >= 6);
    const uint64_t da = mk_desc(sR + st * 32768 + (warp >> 2) * 1024, 2048, 128, 0), db = mk_desc(sR + st * 32768 + 16384, 8192, 1024, 1);
    if (s == 0) TS(5, 2);
    wg_fence();
    wgmma_ss_n128_t1(acc, da, db, s);
    wgmma_ss_n128_t1(acc, da + 256, db + 128, 1);
    wgmma_ss_n128_t1(acc, da + 512, db + 256, 1);
    wgmma_ss_n128_t1(acc, da + 768, db + 384, 1);
    wg_commit();
    wg_wait<1>();
    if (s > 0 && s < 6 && lane == 0) mbar_arrive(bE + 8 * (s - 1));
  }
  wg_wait<0>();
  reg_fence(acc);
  TS(5, 3);
  asm volatile("barrier.cluster.wait.aligned;" ::: "memory");
  uint32_t rem, rbar;
  asm("mapa.shared::cluster.u32 %0,%1,%2;" : "=r"(rbar) : "r"(bX + warp * 8), "r"(kh ^ 1));
  asm("mapa.shared::cluster.u32 %0,%1,%2;" : "=r"(rem) : "r"(sX + warp * 4096 + lane * 16), "r"(kh ^ 1));
#pragma unroll
  for (int j = 0; j < 8; j++) {
    float v[4];
#pragma unroll
    for (int i = 0; i < 4; i++) { v[i] = kh ? acc[4 * j + i] : acc[32 + 4 * j + i]; acc[4 * j + i] = kh ? acc[32 + 4 * j + i] : acc[4 * j + i]; }
    asm volatile("st.async.weak.shared::cluster.mbarrier::complete_tx::bytes.v4.f32 [%0],{%1,%2,%3,%4},[%5];" ::"r"(rem + j * 512), "f"(v[0]), "f"(v[1]), "f"(v[2]), "f"(v[3]), "r"(rbar) : "memory");
  }
  mbar_wait(bX + warp * 8, 0);
  TS(5, 5);
  const uint32_t sw = sX + warp * 4096;
#pragma unroll
  for (int j = 0; j < 8; j++) {
    const float4 p = *(const float4*)(smem + 6 * 32768 + warp * 4096 + j * 512 + lane * 16);
    xr[2 * j] = pack_rn(fmaf(gb[j].x, acc[4 * j] + p.x, blo(xr[2 * j])), fmaf(gb[j].y, acc[4 * j + 1] + p.y, bhi(xr[2 * j])));
    xr[2 * j + 1] = pack_rn(fmaf(gb[j].x, acc[4 * j + 2] + p.z, blo(xr[2 * j + 1])), fmaf(gb[j].y, acc[4 * j + 3] + p.w, bhi(xr[2 * j + 1])));
  }
  __syncwarp();
#pragma unroll
  for (int j = 1; j < 8; j += 2) {
    asm volatile("stmatrix.sync.aligned.m8n8.x4.shared.b16 [%0],{%1,%2,%3,%4};" ::"r"(sw + (lane & 15) * 128 + (((j - 1 + (lane >> 4)) ^ (lane & 7)) << 4)),
                            "r"(xr[2 * j - 2]), "r"(xr[2 * j - 1]), "r"(xr[2 * j]), "r"(xr[2 * j + 1]) : "memory");
  }
  __syncwarp();
#pragma unroll
  for (int i = 0; i < 4; i++) {
    const int r = i * 4 + (lane >> 3);
    *(uint4*)(out + (rb * 128 + warp * 16 + r) * 512 + ct * 128 + kh * 64 + (lane & 7) * 8) = *(const uint4*)(smem + 6 * 32768 + warp * 4096 + r * 128 + (((lane ^ r) & 7) << 4));
  }
  TS(5, 4);
}

typedef CUresult (*EncFn)(CUtensorMap*, CUtensorMapDataType, cuuint32_t, void*, const cuuint64_t*, const cuuint64_t*, const cuuint32_t*,
                          const cuuint32_t*, CUtensorMapInterleave, CUtensorMapSwizzle, CUtensorMapL2promotion, CUtensorMapFloatOOBfill);
static void mk_map(EncFn f, CUtensorMap* m, const void* p, int rows, int cols, int box_rows) {
  cuuint64_t dim[2] = {(cuuint64_t)cols, (cuuint64_t)rows}, str[1] = {(cuuint64_t)cols * 2};
  cuuint32_t box[2] = {64, (cuuint32_t)box_rows}, es[2] = {1, 1};
  f(m, CU_TENSOR_MAP_DATA_TYPE_BFLOAT16, 2, (void*)p, dim, str, box, es, CU_TENSOR_MAP_INTERLEAVE_NONE, CU_TENSOR_MAP_SWIZZLE_128B,
    CU_TENSOR_MAP_L2_PROMOTION_L2_128B, CU_TENSOR_MAP_FLOAT_OOB_FILL_NONE);
}
template <typename... KA, typename... A>
static void launch(void (*k)(KA...), int grid, int block, int smem, bool pdl, A... args) {
  cudaLaunchConfig_t cfg = {};
  cfg.gridDim = dim3(grid); cfg.blockDim = dim3(block); cfg.dynamicSmemBytes = smem; cfg.stream = cudaStreamPerThread;
  cudaLaunchAttribute at[1];
  at[0].id = cudaLaunchAttributeProgrammaticStreamSerialization; at[0].val.programmaticStreamSerializationAllowed = 1;
  cfg.attrs = at; cfg.numAttrs = pdl ? 1 : 0;
  cudaLaunchKernelEx(&cfg, k, args...);
}
extern "C" void kernel_launch(void* const* d_in, const int* in_sizes, int n_in, void* d_out, int out_size) {
  const bf16 *x = (const bf16*)d_in[0], *wqkv = (const bf16*)d_in[1], *wo = (const bf16*)d_in[2], *w1 = (const bf16*)d_in[4],
             *w3 = (const bf16*)d_in[5], *w2 = (const bf16*)d_in[6], *c = (const bf16*)d_in[7], *wmod = (const bf16*)d_in[8];
  void* fp = nullptr;
  cudaDriverEntryPointQueryResult qr;
  cudaGetDriverEntryPoint("cuTensorMapEncodeTiled", &fp, cudaEnableDefault, &qr);
  EncFn f = (EncFn)fp;
  CUtensorMap mX, mQ, mO, m1, m3, m2;
  mk_map(f, &mX, x, S_, D_, 128); mk_map(f, &mQ, wqkv, D_, 3 * D_, 64); mk_map(f, &mO, wo, D_, D_, 64);
  mk_map(f, &m1, w1, D_, F_, 32); mk_map(f, &m3, w3, D_, F_, 32); mk_map(f, &m2, w2, F_, D_, 64);
  cudaFuncSetAttribute(k_lngemm<false>, cudaFuncAttributeMaxDynamicSharedMemorySize, LN_SMEM);
  cudaFuncSetAttribute(k_lngemm<true>, cudaFuncAttributeMaxDynamicSharedMemorySize, LN_SMEM);
  cudaFuncSetAttribute(k_attn, cudaFuncAttributeMaxDynamicSharedMemorySize, AT_SMEM);
  cudaFuncSetAttribute(k_wo, cudaFuncAttributeMaxDynamicSharedMemorySize, WO_SMEM);
  cudaFuncSetAttribute(k_w2, cudaFuncAttributeMaxDynamicSharedMemorySize, W2_SMEM);
  launch(k_lngemm<false>, 128, 384, LN_SMEM, false, mX, mQ, mQ, c, wmod, x);
  launch(k_attn, 132, 512, AT_SMEM, true, wo, w1, w3, w2, c, wmod, 0u);
  launch(k_wo, 128, 256, WO_SMEM, true, mO, x);
  launch(k_lngemm<true>, 128, 384, LN_SMEM, true, mX, m1, m3, c, wmod, x);
  launch(k_w2, 128, 288, W2_SMEM, true, m2, (bf16*)d_out);
}
```

```cpp
#include <cuda_runtime.h>
#include <cuda_bf16.h>
#include <cuda.h>
#include <stdint.h>
typedef __nv_bfloat16 bf16;
constexpr int S_ = 2048, D_ = 512, F_ = 1376;
__device__ __align__(1024) float g_mod[3072];
__device__ __align__(1024) uint32_t g_modv[1024 + 4096];
__device__ __align__(1024) uint32_t g_cnt[48 * 32];
__device__ __align__(1024) bf16 g_qkv[192 * 2048 * 8];
__device__ __align__(1024) float g_kmax[32 * 128];
__device__ __align__(1024) bf16 g_o[16 * 64 * 128 * 8];
__device__ __align__(1024) bf16 g_x1[16 * 64 * 128 * 8];
__device__ __align__(1024) float2 g_st[2048 * 8];
__device__ __align__(1024) bf16 g_h[16 * 172 * 128 * 8];

__device__ __forceinline__ uint32_t smem_u32(const void* p) { return (uint32_t)__cvta_generic_to_shared(p); }
__device__ __forceinline__ void mbar_init(uint32_t b, int n) { asm volatile("mbarrier.init.shared::cta.b64 [%0],%1;" ::"r"(b), "r"(n) : "memory"); }
__device__ __forceinline__ void mbar_expect(uint32_t b, int bytes) { asm volatile("mbarrier.arrive.expect_tx.shared::cta.b64 _,[%0],%1;" ::"r"(b), "r"(bytes) : "memory"); }
__device__ __forceinline__ void mbar_arrive(uint32_t b) { asm volatile("mbarrier.arrive.shared::cta.b64 _,[%0];" ::"r"(b) : "memory"); }
__device__ __forceinline__ void mbar_wait(uint32_t b, int parity) {
  asm volatile("{\n.reg .pred p;\n.reg .u32 n;\nmov.u32 n,0;\nLW:\nmbarrier.try_wait.parity.shared::cta.b64 p,[%0],%1;\n@p bra LD;\n"
               "add.u32 n,n,1;\nsetp.lt.u32 p,n,4194304;\n@p bra LW;\nLD:\n}\n" ::"r"(b), "r"(parity) : "memory");
}
__device__ __forceinline__ void fence_init() { asm volatile("fence.mbarrier_init.release.cluster;" ::: "memory"); }
__device__ __forceinline__ void fence_async() { asm volatile("fence.proxy.async.shared::cta;" ::: "memory"); }
__device__ __forceinline__ void bulk_load(uint32_t dst, const void* src, int bytes, uint32_t bar) {
  asm volatile("cp.async.bulk.shared::cluster.global.mbarrier::complete_tx::bytes [%0],[%1],%2,[%3];" ::"r"(dst), "l"(src), "r"(bytes), "r"(bar) : "memory");
}
__device__ __forceinline__ void tma2d(uint32_t dst, const CUtensorMap* m, int c0, int c1, uint32_t bar) {
  asm volatile("cp.async.bulk.tensor.2d.shared::cluster.global.mbarrier::complete_tx::bytes [%0],[%1,{%3,%4}],[%2];" ::"r"(dst), "l"(m), "r"(bar), "r"(c0), "r"(c1) : "memory");
}
__device__ __forceinline__ void bulk_load_mc(uint32_t dst, const void* src, int bytes, uint32_t bar) {
  asm volatile("cp.async.bulk.shared::cluster.global.mbarrier::complete_tx::bytes.multicast::cluster [%0],[%1],%2,[%3],%4;" ::"r"(dst), "l"(src), "r"(bytes), "r"(bar), "h"((uint16_t)3) : "memory");
}
__device__ __forceinline__ void tma2d_mc(uint32_t dst, const CUtensorMap* m, int c0, int c1, uint32_t bar) {
  asm volatile("cp.async.bulk.tensor.2d.shared::cluster.global.mbarrier::complete_tx::bytes.multicast::cluster [%0],[%1,{%3,%4}],[%2],%5;" ::"r"(dst), "l"(m), "r"(bar), "r"(c0), "r"(c1), "h"((uint16_t)3) : "memory");
}
__device__ __forceinline__ void flag_add(int i) { asm volatile("red.release.gpu.global.add.u32 [%0],1;" ::"l"(g_cnt + i * 32) : "memory"); }
__device__ __forceinline__ void flag_wait(int i, uint32_t n) {
  asm volatile("{\n.reg .pred p;\n.reg .u32 n,t;\nmov.u32 n,0;\nLW:\nld.acquire.gpu.global.u32 t,[%0];\nsetp.ge.u32 p,t,%1;\n@p bra LD;\n"
               "add.u32 n,n,1;\nsetp.lt.u32 p,n,1048576;\n@p bra LW;\nLD:\nfence.proxy.async.global;\n}\n" ::"l"(g_cnt + i * 32), "r"(n) : "memory");
}
__device__ __forceinline__ void cluster_arrive() { asm volatile("barrier.cluster.arrive.relaxed.aligned;" ::: "memory"); }
__device__ __forceinline__ void cluster_wait() { asm volatile("barrier.cluster.wait.aligned;" ::: "memory"); }
__device__ __forceinline__ void cluster_sync() { asm volatile("barrier.cluster.arrive.release.aligned;\nbarrier.cluster.wait.acquire.aligned;" ::: "memory"); }
__device__ __forceinline__ void l2_prefetch(const void* p, int bytes) { asm volatile("cp.async.bulk.prefetch.L2.global [%0],%1;" ::"l"(p), "r"(bytes) : "memory"); }
__device__ __forceinline__ void pdl_launch() { asm volatile("griddepcontrol.launch_dependents;" ::: "memory"); }
__device__ __forceinline__ void pdl_wait() { asm volatile("griddepcontrol.wait;" ::: "memory"); }
__device__ __forceinline__ void wg_fence() { asm volatile("wgmma.fence.sync.aligned;" ::: "memory"); }
__device__ __forceinline__ void wg_commit() { asm volatile("wgmma.commit_group.sync.aligned;" ::: "memory"); }
template <int N> __device__ __forceinline__ void wg_wait() { asm volatile("wgmma.wait_group.sync.aligned %0;" ::"n"(N) : "memory"); }
template <int N> __device__ __forceinline__ void reg_fence(float (&d)[N]) {
#pragma unroll
  for (int i = 0; i < N; i++) asm volatile("" : "+f"(d[i])::"memory");
}
template <int N> __device__ __forceinline__ void zero(float (&d)[N]) {
#pragma unroll
  for (int i = 0; i < N; i++) d[i] = 0.f;
  reg_fence(d);
}
__device__ __forceinline__ uint64_t mk_desc(uint32_t addr, uint32_t lbo, uint32_t sbo, uint32_t mode) {
  return (uint64_t)((addr >> 4) & 0x3FFF) | ((uint64_t)(lbo >> 4) << 16) | ((uint64_t)(sbo >> 4) << 32) | ((uint64_t)mode << 62);
}
__device__ __forceinline__ void ldsm4(uint32_t a, uint32_t (&r)[4]) {
  asm volatile("ldmatrix.sync.aligned.m8n8.x4.shared.b16 {%0,%1,%2,%3},[%4];" : "=r"(r[0]), "=r"(r[1]), "=r"(r[2]), "=r"(r[3]) : "r"(a) : "memory");
}
__device__ __forceinline__ uint32_t pack_rn(float lo, float hi) { uint32_t r; asm("cvt.rn.bf16x2.f32 %0,%1,%2;" : "=r"(r) : "f"(hi), "f"(lo)); return r; }
__device__ __forceinline__ uint32_t pack_rz(float lo, float hi) { uint32_t r; asm("cvt.rz.bf16x2.f32 %0,%1,%2;" : "=r"(r) : "f"(hi), "f"(lo)); return r; }
__device__ __forceinline__ float blo(uint32_t u) { return __uint_as_float(u << 16); }
__device__ __forceinline__ float bhi(uint32_t u) { return __uint_as_float(u & 0xFFFF0000u); }
__device__ __forceinline__ float rbf(float x) { return __bfloat162float(__float2bfloat16_rn(x)); }
__device__ __forceinline__ float qsum(float v) { v += __shfl_xor_sync(~0u, v, 1); return v + __shfl_xor_sync(~0u, v, 2); }
__device__ __forceinline__ float ex2(float x) { float r; asm("ex2.approx.ftz.f32 %0,%1;" : "=f"(r) : "f"(x)); return r; }
#define TS(k, i)
__device__ __forceinline__ void wgmma_rs_n176_t1(float (&d)[88],uint32_t a0,uint32_t a1,uint32_t a2,uint32_t a3,uint64_t db,int sc){
  asm volatile("{\n.reg .pred p;\nsetp.ne.b32 p,%93,0;\n"
    "wgmma.mma_async.sync.aligned.m64n176k16.f32.bf16.bf16 {%0,%1,%2,%3,%4,%5,%6,%7,%8,%9,%10,%11,%12,%13,%14,%15,%16,%17,%18,%19,%20,%21,%22,%23,%24,%25,%26,%27,%28,%29,%30,%31,%32,%33,%34,%35,%36,%37,%38,%39,%40,%41,%42,%43,%44,%45,%46,%47,%48,%49,%50,%51,%52,%53,%54,%55,%56,%57,%58,%59,%60,%61,%62,%63,%64,%65,%66,%67,%68,%69,%70,%71,%72,%73,%74,%75,%76,%77,%78,%79,%80,%81,%82,%83,%84,%85,%86,%87},{%88,%89,%90,%91},%92,p,1,1,1;\n}\n"
    :"+f"(d[0]),"+f"(d[1]),"+f"(d[2]),"+f"(d[3]),"+f"(d[4]),"+f"(d[5]),"+f"(d[6]),"+f"(d[7]),"+f"(d[8]),"+f"(d[9]),"+f"(d[10]),"+f"(d[11]),"+f"(d[12]),"+f"(d[13]),"+f"(d[14]),"+f"(d[15]),"+f"(d[16]),"+f"(d[17]),"+f"(d[18]),"+f"(d[19]),"+f"(d[20]),"+f"(d[21]),"+f"(d[22]),"+f"(d[23]),"+f"(d[24]),"+f"(d[25]),"+f"(d[26]),"+f"(d[27]),"+f"(d[28]),"+f"(d[29]),"+f"(d[30]),"+f"(d[31]),"+f"(d[32]),"+f"(d[33]),"+f"(d[34]),"+f"(d[35]),"+f"(d[36]),"+f"(d[37]),"+f"(d[38]),"+f"(d[39]),"+f"(d[40]),"+f"(d[41]),"+f"(d[42]),"+f"(d[43]),"+f"(d[44]),"+f"(d[45]),"+f"(d[46]),"+f"(d[47]),"+f"(d[48]),"+f"(d[49]),"+f"(d[50]),"+f"(d[51]),"+f"(d[52]),"+f"(d[53]),"+f"(d[54]),"+f"(d[55]),"+f"(d[56]),"+f"(d[57]),"+f"(d[58]),"+f"(d[59]),"+f"(d[60]),"+f"(d[61]),"+f"(d[62]),"+f"(d[63]),"+f"(d[64]),"+f"(d[65]),"+f"(d[66]),"+f"(d[67]),"+f"(d[68]),"+f"(d[69]),"+f"(d[70]),"+f"(d[71]),"+f"(d[72]),"+f"(d[73]),"+f"(d[74]),"+f"(d[75]),"+f"(d[76]),"+f"(d[77]),"+f"(d[78]),"+f"(d[79]),"+f"(d[80]),"+f"(d[81]),"+f"(d[82]),"+f"(d[83]),"+f"(d[84]),"+f"(d[85]),"+f"(d[86]),"+f"(d[87])
    :"r"(a0),"r"(a1),"r"(a2),"r"(a3),"l"(db),"r"(sc));
}
__device__ __forceinline__ void wgmma_rs_n192_t1(float (&d)[96],uint32_t a0,uint32_t a1,uint32_t a2,uint32_t a3,uint64_t db,int sc){
  asm volatile("{\n.reg .pred p;\nsetp.ne.b32 p,%101,0;\n"
    "wgmma.mma_async.sync.aligned.m64n192k16.f32.bf16.bf16 {%0,%1,%2,%3,%4,%5,%6,%7,%8,%9,%10,%11,%12,%13,%14,%15,%16,%17,%18,%19,%20,%21,%22,%23,%24,%25,%26,%27,%28,%29,%30,%31,%32,%33,%34,%35,%36,%37,%38,%39,%40,%41,%42,%43,%44,%45,%46,%47,%48,%49,%50,%51,%52,%53,%54,%55,%56,%57,%58,%59,%60,%61,%62,%63,%64,%65,%66,%67,%68,%69,%70,%71,%72,%73,%74,%75,%76,%77,%78,%79,%80,%81,%82,%83,%84,%85,%86,%87,%88,%89,%90,%91,%92,%93,%94,%95},{%96,%97,%98,%99},%100,p,1,1,1;\n}\n"
    :"+f"(d[0]),"+f"(d[1]),"+f"(d[2]),"+f"(d[3]),"+f"(d[4]),"+f"(d[5]),"+f"(d[6]),"+f"(d[7]),"+f"(d[8]),"+f"(d[9]),"+f"(d[10]),"+f"(d[11]),"+f"(d[12]),"+f"(d[13]),"+f"(d[14]),"+f"(d[15]),"+f"(d[16]),"+f"(d[17]),"+f"(d[18]),"+f"(d[19]),"+f"(d[20]),"+f"(d[21]),"+f"(d[22]),"+f"(d[23]),"+f"(d[24]),"+f"(d[25]),"+f"(d[26]),"+f"(d[27]),"+f"(d[28]),"+f"(d[29]),"+f"(d[30]),"+f"(d[31]),"+f"(d[32]),"+f"(d[33]),"+f"(d[34]),"+f"(d[35]),"+f"(d[36]),"+f"(d[37]),"+f"(d[38]),"+f"(d[39]),"+f"(d[40]),"+f"(d[41]),"+f"(d[42]),"+f"(d[43]),"+f"(d[44]),"+f"(d[45]),"+f"(d[46]),"+f"(d[47]),"+f"(d[48]),"+f"(d[49]),"+f"(d[50]),"+f"(d[51]),"+f"(d[52]),"+f"(d[53]),"+f"(d[54]),"+f"(d[55]),"+f"(d[56]),"+f"(d[57]),"+f"(d[58]),"+f"(d[59]),"+f"(d[60]),"+f"(d[61]),"+f"(d[62]),"+f"(d[63]),"+f"(d[64]),"+f"(d[65]),"+f"(d[66]),"+f"(d[67]),"+f"(d[68]),"+f"(d[69]),"+f"(d[70]),"+f"(d[71]),"+f"(d[72]),"+f"(d[73]),"+f"(d[74]),"+f"(d[75]),"+f"(d[76]),"+f"(d[77]),"+f"(d[78]),"+f"(d[79]),"+f"(d[80]),"+f"(d[81]),"+f"(d[82]),"+f"(d[83]),"+f"(d[84]),"+f"(d[85]),"+f"(d[86]),"+f"(d[87]),"+f"(d[88]),"+f"(d[89]),"+f"(d[90]),"+f"(d[91]),"+f"(d[92]),"+f"(d[93]),"+f"(d[94]),"+f"(d[95])
    :"r"(a0),"r"(a1),"r"(a2),"r"(a3),"l"(db),"r"(sc));
}
__device__ __forceinline__ void wgmma_rs_n24_t1(float (&d)[12],uint32_t a0,uint32_t a1,uint32_t a2,uint32_t a3,uint64_t db,int sc){
  asm volatile("{\n.reg .pred p;\nsetp.ne.b32 p,%17,0;\n"
    "wgmma.mma_async.sync.aligned.m64n24k16.f32.bf16.bf16 {%0,%1,%2,%3,%4,%5,%6,%7,%8,%9,%10,%11},{%12,%13,%14,%15},%16,p,1,1,1;\n}\n"
    :"+f"(d[0]),"+f"(d[1]),"+f"(d[2]),"+f"(d[3]),"+f"(d[4]),"+f"(d[5]),"+f"(d[6]),"+f"(d[7]),"+f"(d[8]),"+f"(d[9]),"+f"(d[10]),"+f"(d[11])
    :"r"(a0),"r"(a1),"r"(a2),"r"(a3),"l"(db),"r"(sc));
}
__device__ __forceinline__ void wgmma_rs_n64_t0(float (&d)[32],uint32_t a0,uint32_t a1,uint32_t a2,uint32_t a3,uint64_t db,int sc){
  asm volatile("{\n.reg .pred p;\nsetp.ne.b32 p,%37,0;\n"
    "wgmma.mma_async.sync.aligned.m64n64k16.f32.bf16.bf16 {%0,%1,%2,%3,%4,%5,%6,%7,%8,%9,%10,%11,%12,%13,%14,%15,%16,%17,%18,%19,%20,%21,%22,%23,%24,%25,%26,%27,%28,%29,%30,%31},{%32,%33,%34,%35},%36,p,1,1,0;\n}\n"
    :"+f"(d[0]),"+f"(d[1]),"+f"(d[2]),"+f"(d[3]),"+f"(d[4]),"+f"(d[5]),"+f"(d[6]),"+f"(d[7]),"+f"(d[8]),"+f"(d[9]),"+f"(d[10]),"+f"(d[11]),"+f"(d[12]),"+f"(d[13]),"+f"(d[14]),"+f"(d[15]),"+f"(d[16]),"+f"(d[17]),"+f"(d[18]),"+f"(d[19]),"+f"(d[20]),"+f"(d[21]),"+f"(d[22]),"+f"(d[23]),"+f"(d[24]),"+f"(d[25]),"+f"(d[26]),"+f"(d[27]),"+f"(d[28]),"+f"(d[29]),"+f"(d[30]),"+f"(d[31])
    :"r"(a0),"r"(a1),"r"(a2),"r"(a3),"l"(db),"r"(sc));
}
__device__ __forceinline__ void wgmma_ss_n128_t1(float (&d)[64],uint64_t da,uint64_t db,int sc){
  asm volatile("{\n.reg .pred p;\nsetp.ne.b32 p,%66,0;\n"
    "wgmma.mma_async.sync.aligned.m64n128k16.f32.bf16.bf16 {%0,%1,%2,%3,%4,%5,%6,%7,%8,%9,%10,%11,%12,%13,%14,%15,%16,%17,%18,%19,%20,%21,%22,%23,%24,%25,%26,%27,%28,%29,%30,%31,%32,%33,%34,%35,%36,%37,%38,%39,%40,%41,%42,%43,%44,%45,%46,%47,%48,%49,%50,%51,%52,%53,%54,%55,%56,%57,%58,%59,%60,%61,%62,%63},%64,%65,p,1,1,0,1;\n}\n"
    :"+f"(d[0]),"+f"(d[1]),"+f"(d[2]),"+f"(d[3]),"+f"(d[4]),"+f"(d[5]),"+f"(d[6]),"+f"(d[7]),"+f"(d[8]),"+f"(d[9]),"+f"(d[10]),"+f"(d[11]),"+f"(d[12]),"+f"(d[13]),"+f"(d[14]),"+f"(d[15]),"+f"(d[16]),"+f"(d[17]),"+f"(d[18]),"+f"(d[19]),"+f"(d[20]),"+f"(d[21]),"+f"(d[22]),"+f"(d[23]),"+f"(d[24]),"+f"(d[25]),"+f"(d[26]),"+f"(d[27]),"+f"(d[28]),"+f"(d[29]),"+f"(d[30]),"+f"(d[31]),"+f"(d[32]),"+f"(d[33]),"+f"(d[34]),"+f"(d[35]),"+f"(d[36]),"+f"(d[37]),"+f"(d[38]),"+f"(d[39]),"+f"(d[40]),"+f"(d[41]),"+f"(d[42]),"+f"(d[43]),"+f"(d[44]),"+f"(d[45]),"+f"(d[46]),"+f"(d[47]),"+f"(d[48]),"+f"(d[49]),"+f"(d[50]),"+f"(d[51]),"+f"(d[52]),"+f"(d[53]),"+f"(d[54]),"+f"(d[55]),"+f"(d[56]),"+f"(d[57]),"+f"(d[58]),"+f"(d[59]),"+f"(d[60]),"+f"(d[61]),"+f"(d[62]),"+f"(d[63])
    :"l"(da),"l"(db),"r"(sc));
}
__device__ __forceinline__ void wgmma_ss_n64_t1(float (&d)[32],uint64_t da,uint64_t db,int sc){
  asm volatile("{\n.reg .pred p;\nsetp.ne.b32 p,%34,0;\n"
    "wgmma.mma_async.sync.aligned.m64n64k16.f32.bf16.bf16 {%0,%1,%2,%3,%4,%5,%6,%7,%8,%9,%10,%11,%12,%13,%14,%15,%16,%17,%18,%19,%20,%21,%22,%23,%24,%25,%26,%27,%28,%29,%30,%31},%32,%33,p,1,1,0,1;\n}\n"
    :"+f"(d[0]),"+f"(d[1]),"+f"(d[2]),"+f"(d[3]),"+f"(d[4]),"+f"(d[5]),"+f"(d[6]),"+f"(d[7]),"+f"(d[8]),"+f"(d[9]),"+f"(d[10]),"+f"(d[11]),"+f"(d[12]),"+f"(d[13]),"+f"(d[14]),"+f"(d[15]),"+f"(d[16]),"+f"(d[17]),"+f"(d[18]),"+f"(d[19]),"+f"(d[20]),"+f"(d[21]),"+f"(d[22]),"+f"(d[23]),"+f"(d[24]),"+f"(d[25]),"+f"(d[26]),"+f"(d[27]),"+f"(d[28]),"+f"(d[29]),"+f"(d[30]),"+f"(d[31])
    :"l"(da),"l"(db),"r"(sc));
}

__device__ __forceinline__ float silu_bf(bf16 c) { const float x = __bfloat162float(c); return rbf(x / (1.f + __expf(-x))); }
__device__ __forceinline__ void fma8(float (&a)[8], float s, const uint4& v) {
  a[0] += s * blo(v.x); a[1] += s * bhi(v.x); a[2] += s * blo(v.y); a[3] += s * bhi(v.y);
  a[4] += s * blo(v.z); a[5] += s * bhi(v.z); a[6] += s * blo(v.w); a[7] += s * bhi(v.w);
}
__device__ __forceinline__ float red8(float (&a)[8], int lane) {
#pragma unroll
  for (int w = 4; w >= 1; w >>= 1) {
    const bool up = lane & (w * 4);
#pragma unroll
    for (int j = 0; j < w; j++) a[j] = (up ? a[j + w] : a[j]) + __shfl_xor_sync(~0u, up ? a[j] : a[j + w], w * 4);
  }
  return a[0];
}
__device__ __forceinline__ float mod_fin(float s, int n) { s = rbf(s); return ((n >> 9) == 1 || (n >> 9) == 4) ? rbf(1.f + s) : s; }
__device__ __forceinline__ void poll4(uint2& a, uint2& b, uint2& c, uint2& d, const uint32_t* p, const uint32_t* q) {
  asm volatile("{\n.reg .pred p;\n.reg .u32 n,t;\nmov.u32 n,0;\nLW:\nld.relaxed.gpu.global.v2.u32 {%0,%1},[%8];\nld.relaxed.gpu.global.v2.u32 {%2,%3},[%8+64];\n"
               "ld.relaxed.gpu.global.v2.u32 {%4,%5},[%9];\nld.relaxed.gpu.global.v2.u32 {%6,%7},[%9+2048];\n"
               "lop3.b32 t,%0,%1,%2,0x80;\nlop3.b32 t,t,%3,%4,0x80;\nlop3.b32 t,t,%5,%6,0x80;\nlop3.b32 t,t,%7,1,0x80;\n"
               "setp.ne.u32 p,t,0;\n@p bra LD;\nadd.u32 n,n,1;\nsetp.lt.u32 p,n,1048576;\n@p bra LW;\nLD:\n}\n"
               : "=&r"(a.x), "=&r"(a.y), "=&r"(b.x), "=&r"(b.y), "=&r"(c.x), "=&r"(c.y), "=&r"(d.x), "=&r"(d.y) : "l"(p), "l"(q) : "memory");
}

constexpr int LN_SMEM = 131072 + 4 * 24576 + 2048 + 256 + 512;
template <bool FFN>
__global__ void __cluster_dims__(2, 1, 1) __launch_bounds__(384, 1) k_lngemm(const __grid_constant__ CUtensorMap mX, const __grid_constant__ CUtensorMap mB0,
                                                   const __grid_constant__ CUtensorMap mB1, const bf16* __restrict__ cv, const bf16* __restrict__ wm, const bf16* __restrict__ xg) {
  extern __shared__ __align__(1024) uint8_t smem[];
  const uint32_t sA = smem_u32(smem), sB = sA + 131072, sM = sB + 4 * 24576, bars = sM + 2048;
  const uint32_t bA = bars, bF = bars + 64, bE = bars + 96, bG = bars + 128;
  const int tid = threadIdx.x, warp = tid >> 5, lane = tid & 31;
  const int pr = blockIdx.x & 1, rb = FFN ? (blockIdx.x >> 4) * 2 + pr : blockIdx.x >> 3, ct = FFN ? (blockIdx.x >> 1) & 7 : blockIdx.x & 7;
  constexpr int NST = FFN ? 16 : 8, KS = FFN ? 2 : 4, BOX = FFN ? 4096 : 8192;
  TS(FFN ? 4 : 1, 0);
  if (!FFN && blockIdx.x == 0 && tid >= 320 && tid < 368) { g_cnt[(tid - 320) * 32] = 0; __threadfence(); }
  pdl_launch();
  float* red = (float*)(smem + (bars - sA) + 256);
  if (tid == 256) {
    for (int i = 0; i < 8; i++) mbar_init(bA + 8 * i, 1);
    for (int i = 0; i < 4; i++) { mbar_init(bF + 8 * i, 1); mbar_init(bE + 8 * i, FFN ? 16 : 8); }
    mbar_init(bG, 1);
    fence_init();
  }
  __syncwarp();
  cluster_arrive();
  uint4 wv0, wv1, xv[4];
  bf16 cv0, cv1;
  if (!FFN && tid < 256) {
    wv0 = __ldg((const uint4*)(wm + tid * 3072 + blockIdx.x * 8)); wv1 = __ldg((const uint4*)(wm + (tid + 256) * 3072 + blockIdx.x * 8));
    cv0 = cv[tid]; cv1 = cv[tid + 256];
#pragma unroll
    for (int i = 0; i < 4; i++) xv[i] = __ldg((const uint4*)(xg + (blockIdx.x * 16 + (tid >> 4)) * 512 + i * 128 + (tid & 15) * 8));
  }
  cluster_wait();
  if (!FFN) TS(0, 2);
  if (warp >= 8) {
    asm volatile("setmaxnreg.dec.sync.aligned.u32 40;");
    if (tid == 256) {
      auto loadB = [&](int s) {
        const uint32_t d = sB + (s & 3) * 24576, b = bF + (s & 3) * 8;
        mbar_expect(b, 24576);
        for (int j = 0; j < 3; j++) {
          if (FFN) tma2d_mc(d + (pr * 3 + j) * BOX, pr ? &mB1 : &mB0, ct * 176 + j * 64, s * 32, b);
          else tma2d(d + j * BOX, &mB0, ct * 192 + j * 64, s * 64, b);
        }
      };
      for (int i = 0; i < 8; i++) mbar_expect(bA + 8 * i, 16384);
      for (int s = 0; s < 4; s++) {
        const int i = s * 2 + (ct & 1);
        if (!FFN) tma2d_mc(sA + i * 16384, &mX, i * 64, rb * 128, bA + 8 * i);
        loadB(s);
      }
      if (FFN) {
        flag_wait(16 + rb, 8);
        mbar_arrive(bG);
        for (int i = 0; i < 8; i++) bulk_load(sA + i * 16384, g_x1 + (rb * 64 + i * 8) * 1024, 16384, bA + 8 * i);
      }
      for (int s = 4; s < NST; s++) { mbar_wait(bE + (s & 3) * 8, ((s >> 2) - 1) & 1); loadB(s); }
    }
  } else {
  asm volatile("setmaxnreg.inc.sync.aligned.u32 232;");
  const int g = lane >> 2, t = lane & 3;
  const int lr = warp * 16 + (lane & 7) + ((lane >> 3) & 1) * 8;
  auto aaddr = [&](int ks) -> uint32_t {
    if (FFN) return sA + (ks * 2 + (lane >> 4)) * 2048 + lr * 16;
    return sA + (ks >> 2) * 16384 + lr * 128 + ((((ks & 3) * 2 + (lane >> 4)) ^ (lr & 7)) << 4);
  };
  const int row0 = rb * 128 + warp * 16 + g;
  float2 msh, msc;
  uint2 sh, sc;
  float rs0, rs1, nm0, nm1;
  if (!FFN) {
    {
      float a[8] = {0, 0, 0, 0, 0, 0, 0, 0};
      fma8(a, silu_bf(cv0), wv0); fma8(a, silu_bf(cv1), wv1);
      if (a[0] != 123.f) TS(0, 3);
      const float s = qsum(red8(a, lane));
      if (t == 0) red[warp * 8 + g] = s;
      asm volatile("bar.sync 1,256;" ::: "memory");
      if (tid < 8) {
        float r = 0;
#pragma unroll
        for (int i = 0; i < 8; i++) r += red[i * 8 + tid];
        const int n = blockIdx.x * 8 + tid;
        asm volatile("st.relaxed.gpu.global.u32 [%0],%1;" ::"l"(g_modv + n), "r"(__float_as_uint(mod_fin(r, n)) | 1u) : "memory");
      }
      TS(0, 1);
    }
    {
      float v[32], s = 0, q = 0;
#pragma unroll
      for (int i = 0; i < 16; i++) { const uint32_t u = ((const uint32_t*)xv)[i]; v[2 * i] = blo(u); v[2 * i + 1] = bhi(u); s += v[2 * i] + v[2 * i + 1]; }
      s = qsum(s); s += __shfl_xor_sync(~0u, s, 4); s += __shfl_xor_sync(~0u, s, 8);
      const float m = s * (1.f / 512);
#pragma unroll
      for (int i = 0; i < 32; i++) q += (v[i] - m) * (v[i] - m);
      q = qsum(q); q += __shfl_xor_sync(~0u, q, 4); q += __shfl_xor_sync(~0u, q, 8);
      const float rs = rsqrtf(q * (1.f / 512) + 1e-5f);
      if ((tid & 15) == 0)
        asm volatile("st.relaxed.gpu.global.v2.u32 [%0],{%1,%2};" ::"l"(g_modv + 1024 + (blockIdx.x * 16 + (tid >> 4)) * 2), "r"(__float_as_uint(rs) | 1u), "r"(__float_as_uint(-m * rs) | 1u) : "memory");
    }
    TS(0, 4);
    uint2 p0, p1;
    poll4(p0, p1, sh, sc, g_modv + 1024 + row0 * 2, g_modv + tid * 2);
    rs0 = __uint_as_float(p0.x); nm0 = __uint_as_float(p0.y); rs1 = __uint_as_float(p1.x); nm1 = __uint_as_float(p1.y);
    TS(1, 1);
  } else {
    mbar_wait(bG, 0);
    TS(4, 1);
    msh = *(const float2*)(g_mod + 1536 + tid * 2); msc = *(const float2*)(g_mod + 2048 + tid * 2);
    const float4 p0 = *(const float4*)(g_st + row0 * 8 + t * 2), p1 = *(const float4*)(g_st + (row0 + 8) * 8 + t * 2);
    const float m0 = qsum(p0.x + p0.z) * 0.125f, m1 = qsum(p1.x + p1.z) * 0.125f;
    const float v0 = qsum(p0.y + p0.w + 64.f * ((p0.x - m0) * (p0.x - m0) + (p0.z - m0) * (p0.z - m0)));
    const float v1 = qsum(p1.y + p1.w + 64.f * ((p1.x - m1) * (p1.x - m1) + (p1.z - m1) * (p1.z - m1)));
    rs0 = rsqrtf(v0 * (1.f / 512) + 1e-5f); rs1 = rsqrtf(v1 * (1.f / 512) + 1e-5f);
    nm0 = -m0 * rs0; nm1 = -m1 * rs1;
  }
  {
    uint32_t* m = (uint32_t*)(smem + (sM - sA)) + (tid >> 3) * 16 + (tid & 3) * 4 + ((tid >> 2) & 1);
    if (FFN) { m[0] = pack_rn(msc.x, msc.y); m[2] = pack_rn(msh.x, msh.y); }
    else { m[0] = __byte_perm(sc.x, sc.y, 0x7632); m[2] = __byte_perm(sh.x, sh.y, 0x7632); }
    asm volatile("bar.sync 1,256;" ::: "memory");
  }
  constexpr int NA = FFN ? 88 : 96;
  float acc0[NA], acc1[FFN ? 88 : 1];
  uint32_t a[2][KS][4];
  auto prep = [&](int ks, uint32_t(&o)[4]) {
    if ((ks & 3) == 0) mbar_wait(bA + 2 * ks, 0);
    uint32_t r[4]; ldsm4(aaddr(ks), r);
    const uint4 m = *(const uint4*)(smem + (sM - sA) + ks * 64 + t * 16);
#pragma unroll
    for (int i = 0; i < 4; i++) {
      const float rs = (i & 1) ? rs1 : rs0, nm = (i & 1) ? nm1 : nm0;
      const uint32_t n = pack_rn(fmaf(blo(r[i]), rs, nm), fmaf(bhi(r[i]), rs, nm));
      asm("fma.rn.bf16x2 %0,%1,%2,%3;" : "=r"(o[i]) : "r"(n), "r"(i < 2 ? m.x : m.y), "r"(i < 2 ? m.z : m.w));
    }
  };
  auto stage = [&](int s, uint32_t(&c)[KS][4], uint32_t(&n)[KS][4]) {
    mbar_wait(bF + (s & 3) * 8, (s >> 2) & 1);
    const uint64_t db = mk_desc(sB + (s & 3) * 24576, BOX, 1024, 1);
    wg_fence();
#pragma unroll
    for (int k = 0; k < KS; k++) {
      if constexpr (FFN) {
        wgmma_rs_n176_t1(acc0, c[k][0], c[k][1], c[k][2], c[k][3], db + k * 128, s + k);
        wgmma_rs_n176_t1(acc1, c[k][0], c[k][1], c[k][2], c[k][3], db + k * 128 + 3 * BOX / 16, s + k);
      } else {
        wgmma_rs_n192_t1(acc0, c[k][0], c[k][1], c[k][2], c[k][3], db + k * 128, s + k);
      }
    }
    wg_commit();
    wg_wait<1>();
    if (s > 0 && s <= NST - 4) {
      if (!FFN) { if (lane == 0) mbar_arrive(bE + ((s - 1) & 3) * 8); }
      else if (lane < 2) asm volatile("{\n.reg .b32 r;\nmapa.shared::cluster.u32 r,%0,%1;\nmbarrier.arrive.relaxed.cluster.shared::cluster.b64 _,[r];\n}" ::"r"(bE + ((s - 1) & 3) * 8), "r"(lane) : "memory");
    }
    if (s < NST - 1) {
#pragma unroll
      for (int k = 0; k < KS; k++) prep((s + 1) * KS + k, n[k]);
    }
  };
#pragma unroll
  for (int k = 0; k < KS; k++) prep(k, a[0][k]);
  TS(FFN ? 4 : 1, 2);
#pragma unroll 1
  for (int s = 0; s < NST; s += 2) { stage(s, a[0], a[1]); stage(s + 1, a[1], a[0]); }
  wg_wait<0>();
  reg_fence(acc0);
  TS(FFN ? 4 : 1, 3);
  if constexpr (FFN) {
    reg_fence(acc1);
    uint32_t* o = (uint32_t*)g_h + ((rb * 172 + ct * 22) * 128 + warp * 16 + g) * 4 + t;
#pragma unroll
    for (int j = 0; j < 22; j++) {
      if (ct * 22 + j < 172) {
        float h[4];
#pragma unroll
        for (int i = 0; i < 4; i++) { const float x = acc0[4 * j + i]; h[i] = __fdividef(x, 1.f + ex2(-1.4426950408889634f * x)) * acc1[4 * j + i]; }
        o[j * 512] = pack_rn(h[0], h[1]);
        o[j * 512 + 32] = pack_rn(h[2], h[3]);
      }
    }
    asm volatile("bar.sync 1,256;" ::: "memory");
    if (tid == 0) flag_add(32 + rb);
  } else {
    uint32_t* o = (uint32_t*)g_qkv + (ct * 24 * 2048 + row0) * 4 + t;
#pragma unroll
    for (int j = 0; j < 24; j += 2) {
      const int G = ct * 24 + j;
      const float sc = G < 64 ? 0.25f * 1.4426950408889634f : 1.f;
      uint32_t p[4];
#pragma unroll
      for (int i = 0; i < 4; i++) p[i] = pack_rn(acc0[4 * j + 2 * i] * sc, acc0[4 * j + 2 * i + 1] * sc);
      o[j * 8192] = p[0]; o[j * 8192 + 32] = p[1]; o[(j + 1) * 8192] = p[2]; o[(j + 1) * 8192 + 32] = p[3];
      if (G >= 64 && G < 128) {
        float n0 = blo(p[0]) * blo(p[0]) + bhi(p[0]) * bhi(p[0]) + blo(p[2]) * blo(p[2]) + bhi(p[2]) * bhi(p[2]);
        float n1 = blo(p[1]) * blo(p[1]) + bhi(p[1]) * bhi(p[1]) + blo(p[3]) * blo(p[3]) + bhi(p[3]) * bhi(p[3]);
        n0 = qsum(n0); n1 = qsum(n1);
        const uint32_t mx = __reduce_max_sync(~0u, max(__float_as_uint(n0), __float_as_uint(n1)));
        if (lane == 0) g_kmax[((G - 64) >> 1) * 128 + rb * 8 + warp] = __uint_as_float(mx);
      }
    }
  }
  TS(FFN ? 4 : 1, 4);
}
}

#define SMASK 0xAAu
#define BRK 0
#define PACK 1
#define PP 1
constexpr int AT_SMEM = 5 * 32768 + 256;
__device__ __forceinline__ uint32_t exp2_pair_fma(float s0, float s1, float c, uint32_t ka, uint32_t kz) {
  uint32_t r;
  asm volatile("{\n.reg .b32 y0,y1,e,u,t;\n"
      "fma.rn.sat.f32 y0,%1,0f00000080,%3;\nfma.rn.sat.f32 y1,%2,0f00000080,%3;\n"
      "mad.lo.u32 e,y1,65536,y0;\n"
      "and.b32 u,e,0x007F007F;\n"
      "fma.rn.f16x2 u,u,%4,%5;\nfma.rn.f16x2 t,u,u,%6;\nfma.rn.f16x2 t,t,u,%7;\n"
      "lop3.b32 %0,t,0x007F007F,e,0xE2;\n}\n"
      : "=r"(r) : "f"(s0), "f"(s1), "f"(c), "r"(ka), "r"(0x36B236B2u), "r"(0x3C733C73u), "r"(0x47764776u), "r"(kz));
  return r;
}
__device__ __forceinline__ void attn_pass(float (&oa)[12], float (&ob)[12], const uint32_t (&q)[4], float m0, float m1, uint32_t sK, uint32_t bars, bool first, uint32_t kz) {
  const uint64_t dk = mk_desc(sK, 32768, 128, 0), dv = mk_desc(sK + 65536, 128, 32768, 0);
  const float c0 = (127.f - m0) * __uint_as_float(0x80u), c1 = (127.f - m1) * __uint_as_float(0x80u);
  const uint32_t ka = 0x7ACE7ACEu + kz;
  constexpr int NK = 64, NS = 32, NP = 16, NI = 32;
  auto qk = [&](float (&s)[NS], int i) { wgmma_rs_n64_t0(s, q[0], q[1], q[2], q[3], dk + i * NK, 0); };
  auto softmax = [&](float (&s)[NS], uint32_t (&p)[NP], uint32_t mask) {
    reg_fence(s);
    float e0, e1;
    int pend = -1;
#pragma unroll
    for (int t = 0; t < NP; t++) {
      const int j = (t & 3) * 4 + (t >> 2);
      if ((mask >> (t & 3)) & 1) {
        p[j] = exp2_pair_fma(s[2 * j], s[2 * j + 1], (j & 1) ? c1 : c0, ka, kz);
      } else {
        float f0, f1;
        asm volatile("ex2.approx.ftz.f32 %0,%2;\nex2.approx.ftz.f32 %1,%3;" : "=&f"(f0), "=f"(f1) : "f"(s[2 * j]), "f"(s[2 * j + 1]));
        if (pend >= 0) asm volatile("cvt.rn.bf16x2.f32 %0,%1,%2;" : "=r"(p[pend]) : "f"(e1), "f"(e0));
        e0 = f0; e1 = f1; pend = j;
      }
    }
    if (pend >= 0) asm volatile("cvt.rn.bf16x2.f32 %0,%1,%2;" : "=r"(p[pend]) : "f"(e1), "f"(e0));
#pragma unroll
    for (int j = 0; j < NP; j++) asm volatile("" : "+r"(p[j])::"memory");
  };
  auto pv = [&](uint32_t (&p)[NP], int i, uint32_t mask) {
#pragma unroll
    for (int k = 0; k < 4; k++) wgmma_rs_n24_t1(((mask >> k) & 1) ? ob : oa, p[4 * k], p[4 * k + 1], p[4 * k + 2], p[4 * k + 3], dv + i * NK + k * 16, 1);
  };
  auto ld = [&](int i) { if (first && (i & 3) == 0) mbar_wait(bars + i * 2, 0); };
  constexpr uint32_t M0 = SMASK & 15, M1 = SMASK >> 4;
  zero(oa); zero(ob);
  ld(0);
  if (first) TS(2, 2);
  float s[NS];
  zero(s);
  uint32_t p0[NP], p1[NP];
  wg_fence(); qk(s, 0); wg_commit(); wg_wait<0>(); softmax(s, p0, M0);
#pragma unroll 1
  for (int i = 0; i < NI - 2; i += 2) {
    wg_fence(); qk(s, i + 1); wg_commit(); pv(p0, i, M0); wg_commit(); wg_wait<1>(); softmax(s, p1, M1); wg_wait<0>();
    ld(i + 2);
    wg_fence(); qk(s, i + 2); wg_commit(); pv(p1, i + 1, M1); wg_commit(); wg_wait<1>(); softmax(s, p0, M0); wg_wait<0>();
  }
  wg_fence(); qk(s, NI - 1); wg_commit(); pv(p0, NI - 2, M0); wg_commit(); wg_wait<1>(); softmax(s, p1, M1); wg_wait<0>();
  wg_fence(); pv(p1, NI - 1, M1); wg_commit();
  wg_wait<0>();
  reg_fence(oa); reg_fence(ob);
}
__device__ __forceinline__ void mma16816(float (&d)[4], const uint32_t (&a)[4], uint32_t b0, uint32_t b1) {
  asm("mma.sync.aligned.m16n8k16.row.col.f32.bf16.bf16.f32 {%0,%1,%2,%3},{%4,%5,%6,%7},{%8,%9},{%0,%1,%2,%3};"
      : "+f"(d[0]), "+f"(d[1]), "+f"(d[2]), "+f"(d[3]) : "r"(a[0]), "r"(a[1]), "r"(a[2]), "r"(a[3]), "r"(b0), "r"(b1));
}
__device__ __forceinline__ void attn_safe(float (&o)[12], const uint32_t (&q)[4], uint32_t sK) {
  const int lane = threadIdx.x & 31;
  const uint32_t ka = sK + (lane >> 4) * 32768 + (lane & 15) * 16;
  float m0 = -INFINITY, m1 = -INFINITY;
#pragma unroll 2
  for (int i = 0; i < 128; i++) {
    uint32_t k[4]; ldsm4(ka + i * 256, k);
    float s0[4] = {0, 0, 0, 0}, s1[4] = {0, 0, 0, 0};
    mma16816(s0, q, k[0], k[2]); mma16816(s1, q, k[1], k[3]);
    m0 = fmaxf(fmaxf(m0, fmaxf(s0[0], s0[1])), fmaxf(s1[0], s1[1])); m1 = fmaxf(fmaxf(m1, fmaxf(s0[2], s0[3])), fmaxf(s1[2], s1[3]));
  }
  m0 = fmaxf(m0, __shfl_xor_sync(~0u, m0, 1)); m0 = fmaxf(m0, __shfl_xor_sync(~0u, m0, 2));
  m1 = fmaxf(m1, __shfl_xor_sync(~0u, m1, 1)); m1 = fmaxf(m1, __shfl_xor_sync(~0u, m1, 2));
  float o0[4] = {0, 0, 0, 0}, o1[4] = {0, 0, 0, 0}, o2[4] = {0, 0, 0, 0};
#pragma unroll 2
  for (int i = 0; i < 128; i++) {
    uint32_t k[4], v[4]; ldsm4(ka + i * 256, k);
    asm volatile("ldmatrix.sync.aligned.m8n8.x4.trans.shared.b16 {%0,%1,%2,%3},[%4];" : "=r"(v[0]), "=r"(v[1]), "=r"(v[2]), "=r"(v[3]) : "r"(ka + 65536 + i * 256) : "memory");
    float s0[4] = {0, 0, 0, 0}, s1[4] = {0, 0, 0, 0};
    mma16816(s0, q, k[0], k[2]); mma16816(s1, q, k[1], k[3]);
    const uint32_t p[4] = {pack_rn(ex2(s0[0] - m0), ex2(s0[1] - m0)), pack_rn(ex2(s0[2] - m1), ex2(s0[3] - m1)),
                           pack_rn(ex2(s1[0] - m0), ex2(s1[1] - m0)), pack_rn(ex2(s1[2] - m1), ex2(s1[3] - m1))};
    mma16816(o0, p, v[0], v[1]); mma16816(o1, p, v[2], v[3]); mma16816(o2, p, 0x3F803F80u, 0x3F803F80u);
  }
#pragma unroll
  for (int i = 0; i < 4; i++) { o[i] = o0[i]; o[4 + i] = o1[i]; o[8 + i] = o2[i]; }
}
__global__ void __cluster_dims__(2, 1, 1) __launch_bounds__(512, 1) k_attn(const bf16* wo, const bf16* w1, const bf16* w3, const bf16* w2, const bf16* __restrict__ cv, const bf16* __restrict__ wm, uint32_t kz) {
  extern __shared__ __align__(1024) uint8_t smem[];
  const uint32_t sK = smem_u32(smem), bars = sK + 5 * 32768;
  const int tid = threadIdx.x, warp = tid >> 5, lane = tid & 31, g = lane >> 2, t = lane & 3;
  pdl_launch();
  if (blockIdx.x < 4) {
    float* cs = (float*)smem;
    cs[tid] = silu_bf(cv[tid]);
    __syncthreads();
    const int n0 = 1024 + blockIdx.x * 512, r0 = (tid >> 6) * 64;
    float a[8] = {0, 0, 0, 0, 0, 0, 0, 0};
#pragma unroll 16
    for (int r = r0; r < r0 + 64; r++) fma8(a, cs[r], __ldg((const uint4*)(wm + r * 3072 + n0 + (tid & 63) * 8)));
    float4* rp = (float4*)(cs + 512 + tid * 8);
    rp[0] = make_float4(a[0], a[1], a[2], a[3]); rp[1] = make_float4(a[4], a[5], a[6], a[7]);
    __syncthreads();
    float s = 0;
#pragma unroll
    for (int i = 0; i < 8; i++) s += cs[512 + i * 512 + tid];
    g_mod[n0 + tid] = mod_fin(s, n0 + tid);
    __syncthreads();
    if (tid < 16) flag_add(tid);
    return;
  }
  const int bid = blockIdx.x - 4, h = bid >> 2, qb = bid & 3;
  TS(2, 0);
  if (tid == 0) { for (int i = 0; i < 8; i++) { mbar_init(bars + 8 * i, 1); mbar_expect(bars + 8 * i, 16384); } fence_init(); }
#pragma unroll
  for (int i = 0; i < 4; i++) *(uint4*)(smem + 131072 + i * 8192 + tid * 16) = make_uint4(0x3F803F80u, 0x3F803F80u, 0x3F803F80u, 0x3F803F80u);
  fence_async();
  cluster_sync();
  pdl_wait();
  TS(2, 1);
  if (tid >= 472) g_modv[bid * 40 + tid - 472] = 0;
  const uint4 km4 = *(const uint4*)(g_kmax + h * 128 + lane * 4);
  const uint32_t* qp = (const uint32_t*)g_qkv + (h * 2 * 2048 + qb * 512 + warp * 16 + g) * 4 + t;
  uint32_t q[4] = {qp[0], qp[32], qp[8192], qp[8192 + 32]};
  auto ldkv = [&]() {
    const int c = warp >> 1, pl = (qb & 1) + (warp & 1) * 2;
    bulk_load_mc(sK + pl * 32768 + c * 4096, g_qkv + ((64 + (pl >> 1) * 64 + h * 2 + (pl & 1)) * 2048 + c * 256) * 8, 4096, bars + 8 * c);
  };
  if (lane == 0 && warp < 4) ldkv();
  const uint32_t qn[4] = {qp[1024], qp[1024 + 32], qp[1024 + 8192], qp[1024 + 8192 + 32]};
  const float kmax = __uint_as_float(__reduce_max_sync(~0u, max(max(km4.x, km4.y), max(km4.z, km4.w))));
  if (lane == 0 && warp >= 4 && kmax != -1.f) ldkv();
#pragma unroll 1
  for (int tile = 0; tile < 2; tile++) {
    const int row = qb * 512 + tile * 256 + warp * 16 + g;
    const float n0 = qsum(blo(q[0]) * blo(q[0]) + bhi(q[0]) * bhi(q[0]) + blo(q[2]) * blo(q[2]) + bhi(q[2]) * bhi(q[2]));
    const float n1 = qsum(blo(q[1]) * blo(q[1]) + bhi(q[1]) * bhi(q[1]) + blo(q[3]) * blo(q[3]) + bhi(q[3]) * bhi(q[3]));
    const float b0 = sqrtf(n0 * kmax) * 1.001f, b1 = sqrtf(n1 * kmax) * 1.001f;
    const float m0 = fmaxf(ceilf(b0 - 100.f), 0.f), m1 = fmaxf(ceilf(b1 - 100.f), 0.f);
    float o[12], ob[12];
    attn_pass(o, ob, q, m0, m1, sK, bars, tile == 0, kz);
    const float f0 = ex2(-m0), f1 = ex2(-m1);
#pragma unroll
    for (int i = 0; i < 12; i++) o[i] = fmaf(o[i], (i & 2) ? f1 : f0, ob[i]);
    bool ok = b0 < 220.f && b1 < 220.f && o[8] >= 0x1p-90f && o[10] >= 0x1p-90f;
#pragma unroll
    for (int i = 0; i < 12; i++) ok = ok && fabsf(o[i]) < INFINITY;
    if (!__all_sync(~0u, ok)) attn_safe(o, q, sK);
    const float r0 = 1.f / o[8], r1 = 1.f / o[10];
    uint32_t* op = (uint32_t*)g_o + (((row >> 7) * 64 + h * 2) * 128 + (row & 127)) * 4 + t;
    op[0] = pack_rn(o[0] * r0, o[1] * r0); op[32] = pack_rn(o[2] * r1, o[3] * r1);
    op[512] = pack_rn(o[4] * r0, o[5] * r0); op[512 + 32] = pack_rn(o[6] * r1, o[7] * r1);
    asm volatile("bar.sync %0,128;" ::"r"(1 + (warp >> 2)) : "memory");
    if ((tid & 127) == 0) flag_add(row >> 7);
    if (tile == 0 && tid == 32) {
      l2_prefetch((const char*)wo + bid * 4096, 4096);
      l2_prefetch((const char*)w1 + bid * 11008, 11008);
      l2_prefetch((const char*)w3 + bid * 11008, 11008);
      l2_prefetch((const char*)w2 + bid * 11008, 11008);
    }
#pragma unroll
    for (int i = 0; i < 4; i++) q[i] = qn[i];
    TS(2, 3 + tile);
  }
}

constexpr int WO_SMEM = 131072 + 65536 + 256;
__global__ void __cluster_dims__(2, 1, 1) __launch_bounds__(256, 1) k_wo(const __grid_constant__ CUtensorMap mW, const bf16* __restrict__ x) {
  extern __shared__ __align__(1024) uint8_t smem[];
  const uint32_t sA = smem_u32(smem), sB = sA + 131072, bars = sB + 65536;
  const int tid = threadIdx.x, warp = tid >> 5, lane = tid & 31, g = lane >> 2, t = lane & 3;
  const int rb = blockIdx.x >> 3, ct = blockIdx.x & 7;
  TS(3, 0);
  pdl_launch();
  if (tid == 0) {
    for (int i = 0; i < 8; i++) mbar_init(bars + 8 * i, 1);
    fence_init();
    for (int i = 0; i < 8; i++) { mbar_expect(bars + 8 * i, 24576); tma2d(sB + i * 8192, &mW, ct * 64, i * 64, bars + 8 * i); }
  }
  __syncwarp();
  cluster_arrive();
  const int lrow = warp * 16 + g;
  uint32_t xr[16];
  const uint32_t* xp = (const uint32_t*)(x + (rb * 128 + lrow) * 512 + ct * 64) + t;
#pragma unroll
  for (int j = 0; j < 8; j++) { xr[2 * j] = __ldg(xp + j * 4); xr[2 * j + 1] = __ldg(xp + j * 4 + 8 * 256); }
  cluster_wait();
  if (tid == 0) {
    flag_wait(rb, 68);
    for (int i = ct & 1; i < 8; i += 2) bulk_load_mc(sA + i * 16384, g_o + (rb * 64 + i * 8) * 1024, 16384, bars + 8 * i);
  }
  __syncthreads();
  TS(3, 1);
  float2 ga[8];
#pragma unroll
  for (int j = 0; j < 8; j++) ga[j] = *(const float2*)(g_mod + 1024 + ct * 64 + j * 8 + t * 2);
  float acc[32];
  const uint64_t da = mk_desc(sA + (warp >> 2) * 1024, 2048, 128, 0), db = mk_desc(sB, 8192, 1024, 1);
#pragma unroll
  for (int c = 0; c < 8; c++) {
    mbar_wait(bars + 8 * c, 0);
    if (c == 0) TS(3, 2);
    wg_fence();
#pragma unroll
    for (int k = 0; k < 4; k++) wgmma_ss_n64_t1(acc, da + (c * 4 + k) * 256, db + (c * 4 + k) * 128, c + k);
    wg_commit();
  }
  wg_wait<0>();
  reg_fence(acc);
  TS(3, 3);
  uint32_t* o = (uint32_t*)g_x1 + ((rb * 64 + ct * 8) * 128 + lrow) * 4 + t;
  float s0 = 0, s1 = 0;
#pragma unroll
  for (int j = 0; j < 8; j++) {
    xr[2 * j] = pack_rn(fmaf(ga[j].x, acc[4 * j], blo(xr[2 * j])), fmaf(ga[j].y, acc[4 * j + 1], bhi(xr[2 * j])));
    xr[2 * j + 1] = pack_rn(fmaf(ga[j].x, acc[4 * j + 2], blo(xr[2 * j + 1])), fmaf(ga[j].y, acc[4 * j + 3], bhi(xr[2 * j + 1])));
    o[j * 512] = xr[2 * j]; o[j * 512 + 32] = xr[2 * j + 1];
    s0 += blo(xr[2 * j]) + bhi(xr[2 * j]); s1 += blo(xr[2 * j + 1]) + bhi(xr[2 * j + 1]);
  }
  const float m0 = qsum(s0) * (1.f / 64), m1 = qsum(s1) * (1.f / 64);
  float v0 = 0, v1 = 0;
#pragma unroll
  for (int j = 0; j < 8; j++) {
    float d;
    d = blo(xr[2 * j]) - m0; v0 += d * d; d = bhi(xr[2 * j]) - m0; v0 += d * d;
    d = blo(xr[2 * j + 1]) - m1; v1 += d * d; d = bhi(xr[2 * j + 1]) - m1; v1 += d * d;
  }
  v0 = qsum(v0); v1 = qsum(v1);
  if (t == 0) g_st[(rb * 128 + lrow) * 8 + ct] = make_float2(m0, v0);
  if (t == 1) g_st[(rb * 128 + lrow + 8) * 8 + ct] = make_float2(m1, v1);
  __syncthreads();
  if (tid == 0) flag_add(16 + rb);
  TS(3, 4);
}

constexpr int W2_SMEM = 6 * 32768 + 32768 + 256;
__global__ void __cluster_dims__(2, 1, 1) __launch_bounds__(288, 1) k_w2(const __grid_constant__ CUtensorMap mW, bf16* __restrict__ out) {
  extern __shared__ __align__(1024) uint8_t smem[];
  const uint32_t sR = smem_u32(smem), sX = sR + 6 * 32768, bF = sX + 32768, bE = bF + 48, bX = bF + 96, bG = bF + 160;
  const int tid = threadIdx.x, warp = tid >> 5, lane = tid & 31, g = lane >> 2, t = lane & 3;
  const int kh = blockIdx.x & 1, ct = (blockIdx.x >> 1) & 3, rb = blockIdx.x >> 3;
  TS(5, 0);
  pdl_launch();
  if (tid == 256) {
    for (int i = 0; i < 6; i++) { mbar_init(bF + 8 * i, 1); mbar_init(bE + 8 * i, 8); }
    for (int i = 0; i < 8; i++) { mbar_init(bX + 8 * i, 1); mbar_expect(bX + 8 * i, 4096); }
    mbar_init(bG, 1);
    fence_init();
  }
  __syncthreads();
  asm volatile("barrier.cluster.arrive.relaxed.aligned;" ::: "memory");
  if (warp == 8) {
    if (lane == 0) {
      auto abytes = [&](int s) { return (kh == 1 && s == 10) ? 8192 : 16384; };
      auto loadB = [&](int s) {
        const int st = s % 6;
        mbar_expect(bF + 8 * st, 16384 + abytes(s));
        for (int j = 0; j < 2; j++) tma2d(sR + st * 32768 + 16384 + j * 8192, &mW, ct * 128 + j * 64, kh * 704 + s * 64, bF + 8 * st);
      };
      auto loadA = [&](int s) { bulk_load(sR + (s % 6) * 32768, g_h + (rb * 172 + kh * 88 + s * 8) * 1024, abytes(s), bF + 8 * (s % 6)); };
      for (int s = 0; s < 6; s++) loadB(s);
      flag_wait(32 + rb, 8);
      for (int s = 0; s < 6; s++) loadA(s);
      mbar_arrive(bG);
      for (int s = 6; s < 11; s++) { mbar_wait(bE + 8 * (s - 6), 0); loadB(s); loadA(s); }
    }
    __syncwarp();
    cluster_wait();
    return;
  }
  mbar_wait(bG, 0);
  TS(5, 1);
  const int lrow = warp * 16 + g;
  uint32_t xr[16];
  float2 gb[8];
  const uint32_t* xp = (const uint32_t*)g_x1 + ((rb * 64 + ct * 16 + kh * 8) * 128 + lrow) * 4 + t;
#pragma unroll
  for (int j = 0; j < 8; j++) {
    xr[2 * j] = xp[j * 512]; xr[2 * j + 1] = xp[j * 512 + 32];
    gb[j] = *(const float2*)(g_mod + 2560 + ct * 128 + kh * 64 + j * 8 + t * 2);
  }
  float acc[64];
#pragma unroll 1
  for (int s = 0; s < 11; s++) {
    const int st = s % 6;
    mbar_wait(bF + 8 * st, s >= 6);
    const uint64_t da = mk_desc(sR + st * 32768 + (warp >> 2) * 1024, 2048, 128, 0), db = mk_desc(sR + st * 32768 + 16384, 8192, 1024, 1);
    if (s == 0) TS(5, 2);
    wg_fence();
    wgmma_ss_n128_t1(acc, da, db, s);
    wgmma_ss_n128_t1(acc, da + 256, db + 128, 1);
    wgmma_ss_n128_t1(acc, da + 512, db + 256, 1);
    wgmma_ss_n128_t1(acc, da + 768, db + 384, 1);
    wg_commit();
    wg_wait<1>();
    if (s > 0 && s < 6 && lane == 0) mbar_arrive(bE + 8 * (s - 1));
  }
  wg_wait<0>();
  reg_fence(acc);
  TS(5, 3);
  asm volatile("barrier.cluster.wait.aligned;" ::: "memory");
  uint32_t rem, rbar;
  asm("mapa.shared::cluster.u32 %0,%1,%2;" : "=r"(rbar) : "r"(bX + warp * 8), "r"(kh ^ 1));
  asm("mapa.shared::cluster.u32 %0,%1,%2;" : "=r"(rem) : "r"(sX + warp * 4096 + lane * 16), "r"(kh ^ 1));
#pragma unroll
  for (int j = 0; j < 8; j++) {
    float v[4];
#pragma unroll
    for (int i = 0; i < 4; i++) { v[i] = kh ? acc[4 * j + i] : acc[32 + 4 * j + i]; acc[4 * j + i] = kh ? acc[32 + 4 * j + i] : acc[4 * j + i]; }
    asm volatile("st.async.weak.shared::cluster.mbarrier::complete_tx::bytes.v4.f32 [%0],{%1,%2,%3,%4},[%5];" ::"r"(rem + j * 512), "f"(v[0]), "f"(v[1]), "f"(v[2]), "f"(v[3]), "r"(rbar) : "memory");
  }
  mbar_wait(bX + warp * 8, 0);
  TS(5, 5);
  const uint32_t sw = sX + warp * 4096;
#pragma unroll
  for (int j = 0; j < 8; j++) {
    const float4 p = *(const float4*)(smem + 6 * 32768 + warp * 4096 + j * 512 + lane * 16);
    xr[2 * j] = pack_rn(fmaf(gb[j].x, acc[4 * j] + p.x, blo(xr[2 * j])), fmaf(gb[j].y, acc[4 * j + 1] + p.y, bhi(xr[2 * j])));
    xr[2 * j + 1] = pack_rn(fmaf(gb[j].x, acc[4 * j + 2] + p.z, blo(xr[2 * j + 1])), fmaf(gb[j].y, acc[4 * j + 3] + p.w, bhi(xr[2 * j + 1])));
  }
  __syncwarp();
#pragma unroll
  for (int j = 1; j < 8; j += 2) {
    asm volatile("stmatrix.sync.aligned.m8n8.x4.shared.b16 [%0],{%1,%2,%3,%4};" ::"r"(sw + (lane & 15) * 128 + (((j - 1 + (lane >> 4)) ^ (lane & 7)) << 4)),
                            "r"(xr[2 * j - 2]), "r"(xr[2 * j - 1]), "r"(xr[2 * j]), "r"(xr[2 * j + 1]) : "memory");
  }
  __syncwarp();
#pragma unroll
  for (int i = 0; i < 4; i++) {
    const int r = i * 4 + (lane >> 3);
    *(uint4*)(out + (rb * 128 + warp * 16 + r) * 512 + ct * 128 + kh * 64 + (lane & 7) * 8) = *(const uint4*)(smem + 6 * 32768 + warp * 4096 + r * 128 + (((lane ^ r) & 7) << 4));
  }
  TS(5, 4);
}

typedef CUresult (*EncFn)(CUtensorMap*, CUtensorMapDataType, cuuint32_t, void*, const cuuint64_t*, const cuuint64_t*, const cuuint32_t*,
                          const cuuint32_t*, CUtensorMapInterleave, CUtensorMapSwizzle, CUtensorMapL2promotion, CUtensorMapFloatOOBfill);
static void mk_map(EncFn f, CUtensorMap* m, const void* p, int rows, int cols, int box_rows) {
  cuuint64_t dim[2] = {(cuuint64_t)cols, (cuuint64_t)rows}, str[1] = {(cuuint64_t)cols * 2};
  cuuint32_t box[2] = {64, (cuuint32_t)box_rows}, es[2] = {1, 1};
  f(m, CU_TENSOR_MAP_DATA_TYPE_BFLOAT16, 2, (void*)p, dim, str, box, es, CU_TENSOR_MAP_INTERLEAVE_NONE, CU_TENSOR_MAP_SWIZZLE_128B,
    CU_TENSOR_MAP_L2_PROMOTION_L2_128B, CU_TENSOR_MAP_FLOAT_OOB_FILL_NONE);
}
template <typename... KA, typename... A>
static void launch(void (*k)(KA...), int grid, int block, int smem, bool pdl, A... args) {
  cudaLaunchConfig_t cfg = {};
  cfg.gridDim = dim3(grid); cfg.blockDim = dim3(block); cfg.dynamicSmemBytes = smem; cfg.stream = cudaStreamPerThread;
  cudaLaunchAttribute at[1];
  at[0].id = cudaLaunchAttributeProgrammaticStreamSerialization; at[0].val.programmaticStreamSerializationAllowed = 1;
  cfg.attrs = at; cfg.numAttrs = pdl ? 1 : 0;
  cudaLaunchKernelEx(&cfg, k, args...);
}
extern "C" void kernel_launch(void* const* d_in, const int* in_sizes, int n_in, void* d_out, int out_size) {
  const bf16 *x = (const bf16*)d_in[0], *wqkv = (const bf16*)d_in[1], *wo = (const bf16*)d_in[2], *w1 = (const bf16*)d_in[4],
             *w3 = (const bf16*)d_in[5], *w2 = (const bf16*)d_in[6], *c = (const bf16*)d_in[7], *wmod = (const bf16*)d_in[8];
  void* fp = nullptr;
  cudaDriverEntryPointQueryResult qr;
  cudaGetDriverEntryPoint("cuTensorMapEncodeTiled", &fp, cudaEnableDefault, &qr);
  EncFn f = (EncFn)fp;
  CUtensorMap mX, mQ, mO, m1, m3, m2;
  mk_map(f, &mX, x, S_, D_, 128); mk_map(f, &mQ, wqkv, D_, 3 * D_, 64); mk_map(f, &mO, wo, D_, D_, 64);
  mk_map(f, &m1, w1, D_, F_, 32); mk_map(f, &m3, w3, D_, F_, 32); mk_map(f, &m2, w2, F_, D_, 64);
  cudaFuncSetAttribute(k_lngemm<false>, cudaFuncAttributeMaxDynamicSharedMemorySize, LN_SMEM);
  cudaFuncSetAttribute(k_lngemm<true>, cudaFuncAttributeMaxDynamicSharedMemorySize, LN_SMEM);
  cudaFuncSetAttribute(k_attn, cudaFuncAttributeMaxDynamicSharedMemorySize, AT_SMEM);
  cudaFuncSetAttribute(k_wo, cudaFuncAttributeMaxDynamicSharedMemorySize, WO_SMEM);
  cudaFuncSetAttribute(k_w2, cudaFuncAttributeMaxDynamicSharedMemorySize, W2_SMEM);
  launch(k_lngemm<false>, 128, 384, LN_SMEM, false, mX, mQ, mQ, c, wmod, x);
  launch(k_attn, 132, 512, AT_SMEM, true, wo, w1, w3, w2, c, wmod, 0u);
  launch(k_wo, 128, 256, WO_SMEM, true, mO, x);
  launch(k_lngemm<true>, 128, 384, LN_SMEM, true, mX, m1, m3, c, wmod, x);
  launch(k_w2, 128, 288, W2_SMEM, true, m2, (bf16*)d_out);
}
```

```cpp
#include <cuda_runtime.h>
#include <cuda_bf16.h>
#include <cuda.h>
#include <stdint.h>
typedef __nv_bfloat16 bf16;
constexpr int S_ = 2048, D_ = 512, F_ = 1376;
__device__ __align__(1024) float g_mod[3072];
__device__ __align__(1024) uint32_t g_modv[1024 + 4096];
__device__ __align__(1024) bf16 g_qkv[192 * 2048 * 8];
__device__ __align__(1024) float g_kmax[32 * 128];
__device__ __align__(1024) bf16 g_o[16 * 64 * 128 * 8];
__device__ __align__(1024) bf16 g_x1[16 * 64 * 128 * 8];
__device__ __align__(1024) float2 g_st[2048 * 8];
__device__ __align__(1024) bf16 g_h[16 * 172 * 128 * 8];

__device__ __forceinline__ uint32_t smem_u32(const void* p) { return (uint32_t)__cvta_generic_to_shared(p); }
__device__ __forceinline__ void mbar_init(uint32_t b, int n) { asm volatile("mbarrier.init.shared::cta.b64 [%0],%1;" ::"r"(b), "r"(n) : "memory"); }
__device__ __forceinline__ void mbar_expect(uint32_t b, int bytes) { asm volatile("mbarrier.arrive.expect_tx.shared::cta.b64 _,[%0],%1;" ::"r"(b), "r"(bytes) : "memory"); }
__device__ __forceinline__ void mbar_arrive(uint32_t b) { asm volatile("mbarrier.arrive.shared::cta.b64 _,[%0];" ::"r"(b) : "memory"); }
__device__ __forceinline__ void mbar_wait(uint32_t b, int parity) {
  asm volatile("{\n.reg .pred p;\n.reg .u32 n;\nmov.u32 n,0;\nLW:\nmbarrier.try_wait.parity.shared::cta.b64 p,[%0],%1;\n@p bra LD;\n"
               "add.u32 n,n,1;\nsetp.lt.u32 p,n,4194304;\n@p bra LW;\nLD:\n}\n" ::"r"(b), "r"(parity) : "memory");
}
__device__ __forceinline__ void fence_init() { asm volatile("fence.mbarrier_init.release.cluster;" ::: "memory"); }
__device__ __forceinline__ void fence_async() { asm volatile("fence.proxy.async.shared::cta;" ::: "memory"); }
__device__ __forceinline__ void bulk_load(uint32_t dst, const void* src, int bytes, uint32_t bar) {
  asm volatile("cp.async.bulk.shared::cluster.global.mbarrier::complete_tx::bytes [%0],[%1],%2,[%3];" ::"r"(dst), "l"(src), "r"(bytes), "r"(bar) : "memory");
}
__device__ __forceinline__ void tma2d(uint32_t dst, const CUtensorMap* m, int c0, int c1, uint32_t bar) {
  asm volatile("cp.async.bulk.tensor.2d.shared::cluster.global.mbarrier::complete_tx::bytes [%0],[%1,{%3,%4}],[%2];" ::"r"(dst), "l"(m), "r"(bar), "r"(c0), "r"(c1) : "memory");
}
__device__ __forceinline__ void bulk_load_mc(uint32_t dst, const void* src, int bytes, uint32_t bar) {
  asm volatile("cp.async.bulk.shared::cluster.global.mbarrier::complete_tx::bytes.multicast::cluster [%0],[%1],%2,[%3],%4;" ::"r"(dst), "l"(src), "r"(bytes), "r"(bar), "h"((uint16_t)3) : "memory");
}
__device__ __forceinline__ void tma2d_mc(uint32_t dst, const CUtensorMap* m, int c0, int c1, uint32_t bar) {
  asm volatile("cp.async.bulk.tensor.2d.shared::cluster.global.mbarrier::complete_tx::bytes.multicast::cluster [%0],[%1,{%3,%4}],[%2],%5;" ::"r"(dst), "l"(m), "r"(bar), "r"(c0), "r"(c1), "h"((uint16_t)3) : "memory");
}
__device__ __forceinline__ void cluster_arrive() { asm volatile("barrier.cluster.arrive.relaxed.aligned;" ::: "memory"); }
__device__ __forceinline__ void cluster_wait() { asm volatile("barrier.cluster.wait.aligned;" ::: "memory"); }
__device__ __forceinline__ void cluster_sync() { asm volatile("barrier.cluster.arrive.release.aligned;\nbarrier.cluster.wait.acquire.aligned;" ::: "memory"); }
__device__ __forceinline__ void l2_prefetch(const void* p, int bytes) { asm volatile("cp.async.bulk.prefetch.L2.global [%0],%1;" ::"l"(p), "r"(bytes) : "memory"); }
__device__ __forceinline__ void pdl_launch() { asm volatile("griddepcontrol.launch_dependents;" ::: "memory"); }
__device__ __forceinline__ void pdl_wait() { asm volatile("griddepcontrol.wait;" ::: "memory"); }
__device__ __forceinline__ void wg_fence() { asm volatile("wgmma.fence.sync.aligned;" ::: "memory"); }
__device__ __forceinline__ void wg_commit() { asm volatile("wgmma.commit_group.sync.aligned;" ::: "memory"); }
template <int N> __device__ __forceinline__ void wg_wait() { asm volatile("wgmma.wait_group.sync.aligned %0;" ::"n"(N) : "memory"); }
template <int N> __device__ __forceinline__ void reg_fence(float (&d)[N]) {
#pragma unroll
  for (int i = 0; i < N; i++) asm volatile("" : "+f"(d[i])::"memory");
}
template <int N> __device__ __forceinline__ void zero(float (&d)[N]) {
#pragma unroll
  for (int i = 0; i < N; i++) d[i] = 0.f;
  reg_fence(d);
}
__device__ __forceinline__ uint64_t mk_desc(uint32_t addr, uint32_t lbo, uint32_t sbo, uint32_t mode) {
  return (uint64_t)((addr >> 4) & 0x3FFF) | ((uint64_t)(lbo >> 4) << 16) | ((uint64_t)(sbo >> 4) << 32) | ((uint64_t)mode << 62);
}
__device__ __forceinline__ void ldsm4(uint32_t a, uint32_t (&r)[4]) {
  asm volatile("ldmatrix.sync.aligned.m8n8.x4.shared.b16 {%0,%1,%2,%3},[%4];" : "=r"(r[0]), "=r"(r[1]), "=r"(r[2]), "=r"(r[3]) : "r"(a) : "memory");
}
__device__ __forceinline__ uint32_t pack_rn(float lo, float hi) { uint32_t r; asm("cvt.rn.bf16x2.f32 %0,%1,%2;" : "=r"(r) : "f"(hi), "f"(lo)); return r; }
__device__ __forceinline__ uint32_t pack_rz(float lo, float hi) { uint32_t r; asm("cvt.rz.bf16x2.f32 %0,%1,%2;" : "=r"(r) : "f"(hi), "f"(lo)); return r; }
__device__ __forceinline__ float blo(uint32_t u) { return __uint_as_float(u << 16); }
__device__ __forceinline__ float bhi(uint32_t u) { return __uint_as_float(u & 0xFFFF0000u); }
__device__ __forceinline__ float rbf(float x) { return __bfloat162float(__float2bfloat16_rn(x)); }
__device__ __forceinline__ float qsum(float v) { v += __shfl_xor_sync(~0u, v, 1); return v + __shfl_xor_sync(~0u, v, 2); }
__device__ __forceinline__ float ex2(float x) { float r; asm("ex2.approx.ftz.f32 %0,%1;" : "=f"(r) : "f"(x)); return r; }
#define TS(k, i)
__device__ __forceinline__ void wgmma_rs_n176_t1(float (&d)[88],uint32_t a0,uint32_t a1,uint32_t a2,uint32_t a3,uint64_t db,int sc){
  asm volatile("{\n.reg .pred p;\nsetp.ne.b32 p,%93,0;\n"
    "wgmma.mma_async.sync.aligned.m64n176k16.f32.bf16.bf16 {%0,%1,%2,%3,%4,%5,%6,%7,%8,%9,%10,%11,%12,%13,%14,%15,%16,%17,%18,%19,%20,%21,%22,%23,%24,%25,%26,%27,%28,%29,%30,%31,%32,%33,%34,%35,%36,%37,%38,%39,%40,%41,%42,%43,%44,%45,%46,%47,%48,%49,%50,%51,%52,%53,%54,%55,%56,%57,%58,%59,%60,%61,%62,%63,%64,%65,%66,%67,%68,%69,%70,%71,%72,%73,%74,%75,%76,%77,%78,%79,%80,%81,%82,%83,%84,%85,%86,%87},{%88,%89,%90,%91},%92,p,1,1,1;\n}\n"
    :"+f"(d[0]),"+f"(d[1]),"+f"(d[2]),"+f"(d[3]),"+f"(d[4]),"+f"(d[5]),"+f"(d[6]),"+f"(d[7]),"+f"(d[8]),"+f"(d[9]),"+f"(d[10]),"+f"(d[11]),"+f"(d[12]),"+f"(d[13]),"+f"(d[14]),"+f"(d[15]),"+f"(d[16]),"+f"(d[17]),"+f"(d[18]),"+f"(d[19]),"+f"(d[20]),"+f"(d[21]),"+f"(d[22]),"+f"(d[23]),"+f"(d[24]),"+f"(d[25]),"+f"(d[26]),"+f"(d[27]),"+f"(d[28]),"+f"(d[29]),"+f"(d[30]),"+f"(d[31]),"+f"(d[32]),"+f"(d[33]),"+f"(d[34]),"+f"(d[35]),"+f"(d[36]),"+f"(d[37]),"+f"(d[38]),"+f"(d[39]),"+f"(d[40]),"+f"(d[41]),"+f"(d[42]),"+f"(d[43]),"+f"(d[44]),"+f"(d[45]),"+f"(d[46]),"+f"(d[47]),"+f"(d[48]),"+f"(d[49]),"+f"(d[50]),"+f"(d[51]),"+f"(d[52]),"+f"(d[53]),"+f"(d[54]),"+f"(d[55]),"+f"(d[56]),"+f"(d[57]),"+f"(d[58]),"+f"(d[59]),"+f"(d[60]),"+f"(d[61]),"+f"(d[62]),"+f"(d[63]),"+f"(d[64]),"+f"(d[65]),"+f"(d[66]),"+f"(d[67]),"+f"(d[68]),"+f"(d[69]),"+f"(d[70]),"+f"(d[71]),"+f"(d[72]),"+f"(d[73]),"+f"(d[74]),"+f"(d[75]),"+f"(d[76]),"+f"(d[77]),"+f"(d[78]),"+f"(d[79]),"+f"(d[80]),"+f"(d[81]),"+f"(d[82]),"+f"(d[83]),"+f"(d[84]),"+f"(d[85]),"+f"(d[86]),"+f"(d[87])
    :"r"(a0),"r"(a1),"r"(a2),"r"(a3),"l"(db),"r"(sc));
}
__device__ __forceinline__ void wgmma_rs_n192_t1(float (&d)[96],uint32_t a0,uint32_t a1,uint32_t a2,uint32_t a3,uint64_t db,int sc){
  asm volatile("{\n.reg .pred p;\nsetp.ne.b32 p,%101,0;\n"
    "wgmma.mma_async.sync.aligned.m64n192k16.f32.bf16.bf16 {%0,%1,%2,%3,%4,%5,%6,%7,%8,%9,%10,%11,%12,%13,%14,%15,%16,%17,%18,%19,%20,%21,%22,%23,%24,%25,%26,%27,%28,%29,%30,%31,%32,%33,%34,%35,%36,%37,%38,%39,%40,%41,%42,%43,%44,%45,%46,%47,%48,%49,%50,%51,%52,%53,%54,%55,%56,%57,%58,%59,%60,%61,%62,%63,%64,%65,%66,%67,%68,%69,%70,%71,%72,%73,%74,%75,%76,%77,%78,%79,%80,%81,%82,%83,%84,%85,%86,%87,%88,%89,%90,%91,%92,%93,%94,%95},{%96,%97,%98,%99},%100,p,1,1,1;\n}\n"
    :"+f"(d[0]),"+f"(d[1]),"+f"(d[2]),"+f"(d[3]),"+f"(d[4]),"+f"(d[5]),"+f"(d[6]),"+f"(d[7]),"+f"(d[8]),"+f"(d[9]),"+f"(d[10]),"+f"(d[11]),"+f"(d[12]),"+f"(d[13]),"+f"(d[14]),"+f"(d[15]),"+f"(d[16]),"+f"(d[17]),"+f"(d[18]),"+f"(d[19]),"+f"(d[20]),"+f"(d[21]),"+f"(d[22]),"+f"(d[23]),"+f"(d[24]),"+f"(d[25]),"+f"(d[26]),"+f"(d[27]),"+f"(d[28]),"+f"(d[29]),"+f"(d[30]),"+f"(d[31]),"+f"(d[32]),"+f"(d[33]),"+f"(d[34]),"+f"(d[35]),"+f"(d[36]),"+f"(d[37]),"+f"(d[38]),"+f"(d[39]),"+f"(d[40]),"+f"(d[41]),"+f"(d[42]),"+f"(d[43]),"+f"(d[44]),"+f"(d[45]),"+f"(d[46]),"+f"(d[47]),"+f"(d[48]),"+f"(d[49]),"+f"(d[50]),"+f"(d[51]),"+f"(d[52]),"+f"(d[53]),"+f"(d[54]),"+f"(d[55]),"+f"(d[56]),"+f"(d[57]),"+f"(d[58]),"+f"(d[59]),"+f"(d[60]),"+f"(d[61]),"+f"(d[62]),"+f"(d[63]),"+f"(d[64]),"+f"(d[65]),"+f"(d[66]),"+f"(d[67]),"+f"(d[68]),"+f"(d[69]),"+f"(d[70]),"+f"(d[71]),"+f"(d[72]),"+f"(d[73]),"+f"(d[74]),"+f"(d[75]),"+f"(d[76]),"+f"(d[77]),"+f"(d[78]),"+f"(d[79]),"+f"(d[80]),"+f"(d[81]),"+f"(d[82]),"+f"(d[83]),"+f"(d[84]),"+f"(d[85]),"+f"(d[86]),"+f"(d[87]),"+f"(d[88]),"+f"(d[89]),"+f"(d[90]),"+f"(d[91]),"+f"(d[92]),"+f"(d[93]),"+f"(d[94]),"+f"(d[95])
    :"r"(a0),"r"(a1),"r"(a2),"r"(a3),"l"(db),"r"(sc));
}
__device__ __forceinline__ void wgmma_rs_n24_t1(float (&d)[12],uint32_t a0,uint32_t a1,uint32_t a2,uint32_t a3,uint64_t db,int sc){
  asm volatile("{\n.reg .pred p;\nsetp.ne.b32 p,%17,0;\n"
    "wgmma.mma_async.sync.aligned.m64n24k16.f32.bf16.bf16 {%0,%1,%2,%3,%4,%5,%6,%7,%8,%9,%10,%11},{%12,%13,%14,%15},%16,p,1,1,1;\n}\n"
    :"+f"(d[0]),"+f"(d[1]),"+f"(d[2]),"+f"(d[3]),"+f"(d[4]),"+f"(d[5]),"+f"(d[6]),"+f"(d[7]),"+f"(d[8]),"+f"(d[9]),"+f"(d[10]),"+f"(d[11])
    :"r"(a0),"r"(a1),"r"(a2),"r"(a3),"l"(db),"r"(sc));
}
__device__ __forceinline__ void wgmma_rs_n64_t0(float (&d)[32],uint32_t a0,uint32_t a1,uint32_t a2,uint32_t a3,uint64_t db,int sc){
  asm volatile("{\n.reg .pred p;\nsetp.ne.b32 p,%37,0;\n"
    "wgmma.mma_async.sync.aligned.m64n64k16.f32.bf16.bf16 {%0,%1,%2,%3,%4,%5,%6,%7,%8,%9,%10,%11,%12,%13,%14,%15,%16,%17,%18,%19,%20,%21,%22,%23,%24,%25,%26,%27,%28,%29,%30,%31},{%32,%33,%34,%35},%36,p,1,1,0;\n}\n"
    :"+f"(d[0]),"+f"(d[1]),"+f"(d[2]),"+f"(d[3]),"+f"(d[4]),"+f"(d[5]),"+f"(d[6]),"+f"(d[7]),"+f"(d[8]),"+f"(d[9]),"+f"(d[10]),"+f"(d[11]),"+f"(d[12]),"+f"(d[13]),"+f"(d[14]),"+f"(d[15]),"+f"(d[16]),"+f"(d[17]),"+f"(d[18]),"+f"(d[19]),"+f"(d[20]),"+f"(d[21]),"+f"(d[22]),"+f"(d[23]),"+f"(d[24]),"+f"(d[25]),"+f"(d[26]),"+f"(d[27]),"+f"(d[28]),"+f"(d[29]),"+f"(d[30]),"+f"(d[31])
    :"r"(a0),"r"(a1),"r"(a2),"r"(a3),"l"(db),"r"(sc));
}
__device__ __forceinline__ void wgmma_ss_n128_t1(float (&d)[64],uint64_t da,uint64_t db,int sc){
  asm volatile("{\n.reg .pred p;\nsetp.ne.b32 p,%66,0;\n"
    "wgmma.mma_async.sync.aligned.m64n128k16.f32.bf16.bf16 {%0,%1,%2,%3,%4,%5,%6,%7,%8,%9,%10,%11,%12,%13,%14,%15,%16,%17,%18,%19,%20,%21,%22,%23,%24,%25,%26,%27,%28,%29,%30,%31,%32,%33,%34,%35,%36,%37,%38,%39,%40,%41,%42,%43,%44,%45,%46,%47,%48,%49,%50,%51,%52,%53,%54,%55,%56,%57,%58,%59,%60,%61,%62,%63},%64,%65,p,1,1,0,1;\n}\n"
    :"+f"(d[0]),"+f"(d[1]),"+f"(d[2]),"+f"(d[3]),"+f"(d[4]),"+f"(d[5]),"+f"(d[6]),"+f"(d[7]),"+f"(d[8]),"+f"(d[9]),"+f"(d[10]),"+f"(d[11]),"+f"(d[12]),"+f"(d[13]),"+f"(d[14]),"+f"(d[15]),"+f"(d[16]),"+f"(d[17]),"+f"(d[18]),"+f"(d[19]),"+f"(d[20]),"+f"(d[21]),"+f"(d[22]),"+f"(d[23]),"+f"(d[24]),"+f"(d[25]),"+f"(d[26]),"+f"(d[27]),"+f"(d[28]),"+f"(d[29]),"+f"(d[30]),"+f"(d[31]),"+f"(d[32]),"+f"(d[33]),"+f"(d[34]),"+f"(d[35]),"+f"(d[36]),"+f"(d[37]),"+f"(d[38]),"+f"(d[39]),"+f"(d[40]),"+f"(d[41]),"+f"(d[42]),"+f"(d[43]),"+f"(d[44]),"+f"(d[45]),"+f"(d[46]),"+f"(d[47]),"+f"(d[48]),"+f"(d[49]),"+f"(d[50]),"+f"(d[51]),"+f"(d[52]),"+f"(d[53]),"+f"(d[54]),"+f"(d[55]),"+f"(d[56]),"+f"(d[57]),"+f"(d[58]),"+f"(d[59]),"+f"(d[60]),"+f"(d[61]),"+f"(d[62]),"+f"(d[63])
    :"l"(da),"l"(db),"r"(sc));
}
__device__ __forceinline__ void wgmma_ss_n64_t1(float (&d)[32],uint64_t da,uint64_t db,int sc){
  asm volatile("{\n.reg .pred p;\nsetp.ne.b32 p,%34,0;\n"
    "wgmma.mma_async.sync.aligned.m64n64k16.f32.bf16.bf16 {%0,%1,%2,%3,%4,%5,%6,%7,%8,%9,%10,%11,%12,%13,%14,%15,%16,%17,%18,%19,%20,%21,%22,%23,%24,%25,%26,%27,%28,%29,%30,%31},%32,%33,p,1,1,0,1;\n}\n"
    :"+f"(d[0]),"+f"(d[1]),"+f"(d[2]),"+f"(d[3]),"+f"(d[4]),"+f"(d[5]),"+f"(d[6]),"+f"(d[7]),"+f"(d[8]),"+f"(d[9]),"+f"(d[10]),"+f"(d[11]),"+f"(d[12]),"+f"(d[13]),"+f"(d[14]),"+f"(d[15]),"+f"(d[16]),"+f"(d[17]),"+f"(d[18]),"+f"(d[19]),"+f"(d[20]),"+f"(d[21]),"+f"(d[22]),"+f"(d[23]),"+f"(d[24]),"+f"(d[25]),"+f"(d[26]),"+f"(d[27]),"+f"(d[28]),"+f"(d[29]),"+f"(d[30]),"+f"(d[31])
    :"l"(da),"l"(db),"r"(sc));
}

__device__ __forceinline__ float silu_bf(bf16 c) { const float x = __bfloat162float(c); return rbf(x / (1.f + __expf(-x))); }
__device__ __forceinline__ void fma8(float (&a)[8], float s, const uint4& v) {
  a[0] += s * blo(v.x); a[1] += s * bhi(v.x); a[2] += s * blo(v.y); a[3] += s * bhi(v.y);
  a[4] += s * blo(v.z); a[5] += s * bhi(v.z); a[6] += s * blo(v.w); a[7] += s * bhi(v.w);
}
__device__ __forceinline__ float red8(float (&a)[8], int lane) {
#pragma unroll
  for (int w = 4; w >= 1; w >>= 1) {
    const bool up = lane & (w * 4);
#pragma unroll
    for (int j = 0; j < w; j++) a[j] = (up ? a[j + w] : a[j]) + __shfl_xor_sync(~0u, up ? a[j] : a[j + w], w * 4);
  }
  return a[0];
}
__device__ __forceinline__ float mod_fin(float s, int n) { s = rbf(s); return ((n >> 9) == 1 || (n >> 9) == 4) ? rbf(1.f + s) : s; }
__device__ __forceinline__ void poll4(uint2& a, uint2& b, uint2& c, uint2& d, const uint32_t* p, const uint32_t* q) {
  asm volatile("{\n.reg .pred p;\n.reg .u32 n,t;\nmov.u32 n,0;\nLW:\nld.relaxed.gpu.global.v2.u32 {%0,%1},[%8];\nld.relaxed.gpu.global.v2.u32 {%2,%3},[%8+64];\n"
               "ld.relaxed.gpu.global.v2.u32 {%4,%5},[%9];\nld.relaxed.gpu.global.v2.u32 {%6,%7},[%9+2048];\n"
               "lop3.b32 t,%0,%1,%2,0x80;\nlop3.b32 t,t,%3,%4,0x80;\nlop3.b32 t,t,%5,%6,0x80;\nlop3.b32 t,t,%7,1,0x80;\n"
               "setp.ne.u32 p,t,0;\n@p bra LD;\nadd.u32 n,n,1;\nsetp.lt.u32 p,n,1048576;\n@p bra LW;\nLD:\n}\n"
               : "=&r"(a.x), "=&r"(a.y), "=&r"(b.x), "=&r"(b.y), "=&r"(c.x), "=&r"(c.y), "=&r"(d.x), "=&r"(d.y) : "l"(p), "l"(q) : "memory");
}

constexpr int LN_SMEM = 131072 + 4 * 24576 + 2048 + 256 + 512;
template <bool FFN>
__global__ void __cluster_dims__(2, 1, 1) __launch_bounds__(384, 1) k_lngemm(const __grid_constant__ CUtensorMap mX, const __grid_constant__ CUtensorMap mB0,
                                                   const __grid_constant__ CUtensorMap mB1, const bf16* __restrict__ cv, const bf16* __restrict__ wm, const bf16* __restrict__ xg) {
  extern __shared__ __align__(1024) uint8_t smem[];
  const uint32_t sA = smem_u32(smem), sB = sA + 131072, sM = sB + 4 * 24576, bars = sM + 2048;
  const uint32_t bA = bars, bF = bars + 64, bE = bars + 96;
  const int tid = threadIdx.x, warp = tid >> 5, lane = tid & 31;
  const int pr = blockIdx.x & 1, rb = FFN ? (blockIdx.x >> 4) * 2 + pr : blockIdx.x >> 3, ct = FFN ? (blockIdx.x >> 1) & 7 : blockIdx.x & 7;
  constexpr int NST = FFN ? 16 : 8, KS = FFN ? 2 : 4, BOX = FFN ? 4096 : 8192;
  TS(FFN ? 4 : 1, 0);
  pdl_launch();
  float* red = (float*)(smem + (bars - sA) + 256);
  if (tid == 256) {
    for (int i = 0; i < 8; i++) mbar_init(bA + 8 * i, 1);
    for (int i = 0; i < 4; i++) { mbar_init(bF + 8 * i, 1); mbar_init(bE + 8 * i, FFN ? 16 : 8); }
    fence_init();
  }
  __syncwarp();
  cluster_arrive();
  uint4 wv0, wv1, xv[4];
  bf16 cv0, cv1;
  if (!FFN && tid < 256) {
    wv0 = __ldg((const uint4*)(wm + tid * 3072 + blockIdx.x * 8)); wv1 = __ldg((const uint4*)(wm + (tid + 256) * 3072 + blockIdx.x * 8));
    cv0 = cv[tid]; cv1 = cv[tid + 256];
#pragma unroll
    for (int i = 0; i < 4; i++) xv[i] = __ldg((const uint4*)(xg + (blockIdx.x * 16 + (tid >> 4)) * 512 + i * 128 + (tid & 15) * 8));
  }
  cluster_wait();
  if (!FFN) TS(0, 2);
  if (warp >= 8) {
    asm volatile("setmaxnreg.dec.sync.aligned.u32 40;");
    if (tid == 256) {
      auto loadB = [&](int s) {
        const uint32_t d = sB + (s & 3) * 24576, b = bF + (s & 3) * 8;
        mbar_expect(b, 24576);
        for (int j = 0; j < 3; j++) {
          if (FFN) tma2d_mc(d + (pr * 3 + j) * BOX, pr ? &mB1 : &mB0, ct * 176 + j * 64, s * 32, b);
          else tma2d(d + j * BOX, &mB0, ct * 192 + j * 64, s * 64, b);
        }
      };
      for (int i = 0; i < 8; i++) mbar_expect(bA + 8 * i, 16384);
      for (int s = 0; s < 4; s++) {
        const int i = s * 2 + (ct & 1);
        if (!FFN) tma2d_mc(sA + i * 16384, &mX, i * 64, rb * 128, bA + 8 * i);
        loadB(s);
      }
      if (FFN) {
        pdl_wait();
        for (int i = 0; i < 8; i++) bulk_load(sA + i * 16384, g_x1 + (rb * 64 + i * 8) * 1024, 16384, bA + 8 * i);
      }
      for (int s = 4; s < NST; s++) { mbar_wait(bE + (s & 3) * 8, ((s >> 2) - 1) & 1); loadB(s); }
    }
  } else {
  asm volatile("setmaxnreg.inc.sync.aligned.u32 232;");
  const int g = lane >> 2, t = lane & 3;
  const int lr = warp * 16 + (lane & 7) + ((lane >> 3) & 1) * 8;
  auto aaddr = [&](int ks) -> uint32_t {
    if (FFN) return sA + (ks * 2 + (lane >> 4)) * 2048 + lr * 16;
    return sA + (ks >> 2) * 16384 + lr * 128 + ((((ks & 3) * 2 + (lane >> 4)) ^ (lr & 7)) << 4);
  };
  const int row0 = rb * 128 + warp * 16 + g;
  float2 msh, msc;
  uint2 sh, sc;
  float rs0, rs1, nm0, nm1;
  if (!FFN) {
    {
      float a[8] = {0, 0, 0, 0, 0, 0, 0, 0};
      fma8(a, silu_bf(cv0), wv0); fma8(a, silu_bf(cv1), wv1);
      if (a[0] != 123.f) TS(0, 3);
      const float s = qsum(red8(a, lane));
      if (t == 0) red[warp * 8 + g] = s;
      asm volatile("bar.sync 1,256;" ::: "memory");
      if (tid < 8) {
        float r = 0;
#pragma unroll
        for (int i = 0; i < 8; i++) r += red[i * 8 + tid];
        const int n = blockIdx.x * 8 + tid;
        asm volatile("st.relaxed.gpu.global.u32 [%0],%1;" ::"l"(g_modv + n), "r"(__float_as_uint(mod_fin(r, n)) | 1u) : "memory");
      }
      TS(0, 1);
    }
    {
      float v[32], s = 0, q = 0;
#pragma unroll
      for (int i = 0; i < 16; i++) { const uint32_t u = ((const uint32_t*)xv)[i]; v[2 * i] = blo(u); v[2 * i + 1] = bhi(u); s += v[2 * i] + v[2 * i + 1]; }
      s = qsum(s); s += __shfl_xor_sync(~0u, s, 4); s += __shfl_xor_sync(~0u, s, 8);
      const float m = s * (1.f / 512);
#pragma unroll
      for (int i = 0; i < 32; i++) q += (v[i] - m) * (v[i] - m);
      q = qsum(q); q += __shfl_xor_sync(~0u, q, 4); q += __shfl_xor_sync(~0u, q, 8);
      const float rs = rsqrtf(q * (1.f / 512) + 1e-5f);
      if ((tid & 15) == 0)
        asm volatile("st.relaxed.gpu.global.v2.u32 [%0],{%1,%2};" ::"l"(g_modv + 1024 + (blockIdx.x * 16 + (tid >> 4)) * 2), "r"(__float_as_uint(rs) | 1u), "r"(__float_as_uint(-m * rs) | 1u) : "memory");
    }
    TS(0, 4);
    uint2 p0, p1;
    poll4(p0, p1, sh, sc, g_modv + 1024 + row0 * 2, g_modv + tid * 2);
    rs0 = __uint_as_float(p0.x); nm0 = __uint_as_float(p0.y); rs1 = __uint_as_float(p1.x); nm1 = __uint_as_float(p1.y);
    TS(1, 1);
  } else {
    pdl_wait();
    TS(4, 1);
    msh = *(const float2*)(g_mod + 1536 + tid * 2); msc = *(const float2*)(g_mod + 2048 + tid * 2);
    const float4 p0 = *(const float4*)(g_st + row0 * 8 + t * 2), p1 = *(const float4*)(g_st + (row0 + 8) * 8 + t * 2);
    const float m0 = qsum(p0.x + p0.z) * 0.125f, m1 = qsum(p1.x + p1.z) * 0.125f;
    const float v0 = qsum(p0.y + p0.w + 64.f * ((p0.x - m0) * (p0.x - m0) + (p0.z - m0) * (p0.z - m0)));
    const float v1 = qsum(p1.y + p1.w + 64.f * ((p1.x - m1) * (p1.x - m1) + (p1.z - m1) * (p1.z - m1)));
    rs0 = rsqrtf(v0 * (1.f / 512) + 1e-5f); rs1 = rsqrtf(v1 * (1.f / 512) + 1e-5f);
    nm0 = -m0 * rs0; nm1 = -m1 * rs1;
  }
  {
    uint32_t* m = (uint32_t*)(smem + (sM - sA)) + (tid >> 3) * 16 + (tid & 3) * 4 + ((tid >> 2) & 1);
    if (FFN) { m[0] = pack_rn(msc.x, msc.y); m[2] = pack_rn(msh.x, msh.y); }
    else { m[0] = __byte_perm(sc.x, sc.y, 0x7632); m[2] = __byte_perm(sh.x, sh.y, 0x7632); }
    asm volatile("bar.sync 1,256;" ::: "memory");
  }
  constexpr int NA = FFN ? 88 : 96;
  float acc0[NA], acc1[FFN ? 88 : 1];
  uint32_t a[2][KS][4];
  auto prep = [&](int ks, uint32_t(&o)[4]) {
    if ((ks & 3) == 0) mbar_wait(bA + 2 * ks, 0);
    uint32_t r[4]; ldsm4(aaddr(ks), r);
    const uint4 m = *(const uint4*)(smem + (sM - sA) + ks * 64 + t * 16);
#pragma unroll
    for (int i = 0; i < 4; i++) {
      const float rs = (i & 1) ? rs1 : rs0, nm = (i & 1) ? nm1 : nm0;
      const uint32_t n = pack_rn(fmaf(blo(r[i]), rs, nm), fmaf(bhi(r[i]), rs, nm));
      asm("fma.rn.bf16x2 %0,%1,%2,%3;" : "=r"(o[i]) : "r"(n), "r"(i < 2 ? m.x : m.y), "r"(i < 2 ? m.z : m.w));
    }
  };
  auto stage = [&](int s, uint32_t(&c)[KS][4], uint32_t(&n)[KS][4]) {
    mbar_wait(bF + (s & 3) * 8, (s >> 2) & 1);
    const uint64_t db = mk_desc(sB + (s & 3) * 24576, BOX, 1024, 1);
    wg_fence();
#pragma unroll
    for (int k = 0; k < KS; k++) {
      if constexpr (FFN) {
        wgmma_rs_n176_t1(acc0, c[k][0], c[k][1], c[k][2], c[k][3], db + k * 128, s + k);
        wgmma_rs_n176_t1(acc1, c[k][0], c[k][1], c[k][2], c[k][3], db + k * 128 + 3 * BOX / 16, s + k);
      } else {
        wgmma_rs_n192_t1(acc0, c[k][0], c[k][1], c[k][2], c[k][3], db + k * 128, s + k);
      }
    }
    wg_commit();
    wg_wait<1>();
    if (s > 0 && s <= NST - 4) {
      if (!FFN) { if (lane == 0) mbar_arrive(bE + ((s - 1) & 3) * 8); }
      else if (lane < 2) asm volatile("{\n.reg .b32 r;\nmapa.shared::cluster.u32 r,%0,%1;\nmbarrier.arrive.relaxed.cluster.shared::cluster.b64 _,[r];\n}" ::"r"(bE + ((s - 1) & 3) * 8), "r"(lane) : "memory");
    }
    if (s < NST - 1) {
#pragma unroll
      for (int k = 0; k < KS; k++) prep((s + 1) * KS + k, n[k]);
    }
  };
#pragma unroll
  for (int k = 0; k < KS; k++) prep(k, a[0][k]);
  TS(FFN ? 4 : 1, 2);
#pragma unroll 1
  for (int s = 0; s < NST; s += 2) { stage(s, a[0], a[1]); stage(s + 1, a[1], a[0]); }
  wg_wait<0>();
  reg_fence(acc0);
  TS(FFN ? 4 : 1, 3);
  if constexpr (FFN) {
    reg_fence(acc1);
    uint32_t* o = (uint32_t*)g_h + ((rb * 172 + ct * 22) * 128 + warp * 16 + g) * 4 + t;
#pragma unroll
    for (int j = 0; j < 22; j++) {
      if (ct * 22 + j < 172) {
        float h[4];
#pragma unroll
        for (int i = 0; i < 4; i++) { const float x = acc0[4 * j + i]; h[i] = __fdividef(x, 1.f + ex2(-1.4426950408889634f * x)) * acc1[4 * j + i]; }
        o[j * 512] = pack_rn(h[0], h[1]);
        o[j * 512 + 32] = pack_rn(h[2], h[3]);
      }
    }
  } else {
    uint32_t* o = (uint32_t*)g_qkv + (ct * 24 * 2048 + row0) * 4 + t;
#pragma unroll
    for (int j = 0; j < 24; j += 2) {
      const int G = ct * 24 + j;
      const float sc = G < 64 ? 0.25f * 1.4426950408889634f : 1.f;
      uint32_t p[4];
#pragma unroll
      for (int i = 0; i < 4; i++) p[i] = pack_rn(acc0[4 * j + 2 * i] * sc, acc0[4 * j + 2 * i + 1] * sc);
      o[j * 8192] = p[0]; o[j * 8192 + 32] = p[1]; o[(j + 1) * 8192] = p[2]; o[(j + 1) * 8192 + 32] = p[3];
      if (G >= 64 && G < 128) {
        float n0 = blo(p[0]) * blo(p[0]) + bhi(p[0]) * bhi(p[0]) + blo(p[2]) * blo(p[2]) + bhi(p[2]) * bhi(p[2]);
        float n1 = blo(p[1]) * blo(p[1]) + bhi(p[1]) * bhi(p[1]) + blo(p[3]) * blo(p[3]) + bhi(p[3]) * bhi(p[3]);
        n0 = qsum(n0); n1 = qsum(n1);
        const uint32_t mx = __reduce_max_sync(~0u, max(__float_as_uint(n0), __float_as_uint(n1)));
        if (lane == 0) g_kmax[((G - 64) >> 1) * 128 + rb * 8 + warp] = __uint_as_float(mx);
      }
    }
  }
  TS(FFN ? 4 : 1, 4);
}
}

#define SMASK 0xAAu
#define BRK 0
#define PACK 1
#define PP 1
constexpr int AT_SMEM = 5 * 32768 + 256;
__device__ __forceinline__ uint32_t exp2_pair_fma(float s0, float s1, float c, uint32_t ka, uint32_t kz) {
  uint32_t r;
  asm volatile("{\n.reg .b32 y0,y1,e,u,t;\n"
      "fma.rn.sat.f32 y0,%1,0f00000080,%3;\nfma.rn.sat.f32 y1,%2,0f00000080,%3;\n"
      "mad.lo.u32 e,y1,65536,y0;\n"
      "and.b32 u,e,0x007F007F;\n"
      "fma.rn.f16x2 u,u,%4,%5;\nfma.rn.f16x2 t,u,u,%6;\nfma.rn.f16x2 t,t,u,%7;\n"
      "lop3.b32 %0,t,0x007F007F,e,0xE2;\n}\n"
      : "=r"(r) : "f"(s0), "f"(s1), "f"(c), "r"(ka), "r"(0x36B236B2u), "r"(0x3C733C73u), "r"(0x47764776u), "r"(kz));
  return r;
}
__device__ __forceinline__ void attn_pass(float (&oa)[12], float (&ob)[12], const uint32_t (&q)[4], float m0, float m1, uint32_t sK, uint32_t bars, bool first, uint32_t kz) {
  const uint64_t dk = mk_desc(sK, 32768, 128, 0), dv = mk_desc(sK + 65536, 128, 32768, 0);
  const float c0 = (127.f - m0) * __uint_as_float(0x80u), c1 = (127.f - m1) * __uint_as_float(0x80u);
  const uint32_t ka = 0x7ACE7ACEu + kz;
  constexpr int NK = 64, NS = 32, NP = 16, NI = 32;
  auto qk = [&](float (&s)[NS], int i) { wgmma_rs_n64_t0(s, q[0], q[1], q[2], q[3], dk + i * NK, 0); };
  auto softmax = [&](float (&s)[NS], uint32_t (&p)[NP], uint32_t mask) {
    reg_fence(s);
    float e0, e1;
    int pend = -1;
#pragma unroll
    for (int t = 0; t < NP; t++) {
      const int j = (t & 3) * 4 + (t >> 2);
      if ((mask >> (t & 3)) & 1) {
        p[j] = exp2_pair_fma(s[2 * j], s[2 * j + 1], (j & 1) ? c1 : c0, ka, kz);
      } else {
        float f0, f1;
        asm volatile("ex2.approx.ftz.f32 %0,%2;\nex2.approx.ftz.f32 %1,%3;" : "=&f"(f0), "=f"(f1) : "f"(s[2 * j]), "f"(s[2 * j + 1]));
        if (pend >= 0) asm volatile("cvt.rn.bf16x2.f32 %0,%1,%2;" : "=r"(p[pend]) : "f"(e1), "f"(e0));
        e0 = f0; e1 = f1; pend = j;
      }
    }
    if (pend >= 0) asm volatile("cvt.rn.bf16x2.f32 %0,%1,%2;" : "=r"(p[pend]) : "f"(e1), "f"(e0));
#pragma unroll
    for (int j = 0; j < NP; j++) asm volatile("" : "+r"(p[j])::"memory");
  };
  auto pv = [&](uint32_t (&p)[NP], int i, uint32_t mask) {
#pragma unroll
    for (int k = 0; k < 4; k++) wgmma_rs_n24_t1(((mask >> k) & 1) ? ob : oa, p[4 * k], p[4 * k + 1], p[4 * k + 2], p[4 * k + 3], dv + i * NK + k * 16, 1);
  };
  auto ld = [&](int i) { if (first && (i & 3) == 0) mbar_wait(bars + i * 2, 0); };
  constexpr uint32_t M0 = SMASK & 15, M1 = SMASK >> 4;
  zero(oa); zero(ob);
  ld(0);
  if (first) TS(2, 2);
  float s[NS];
  zero(s);
  uint32_t p0[NP], p1[NP];
  wg_fence(); qk(s, 0); wg_commit(); wg_wait<0>(); softmax(s, p0, M0);
#pragma unroll 1
  for (int i = 0; i < NI - 2; i += 2) {
    wg_fence(); qk(s, i + 1); wg_commit(); pv(p0, i, M0); wg_commit(); wg_wait<1>(); softmax(s, p1, M1); wg_wait<0>();
    ld(i + 2);
    wg_fence(); qk(s, i + 2); wg_commit(); pv(p1, i + 1, M1); wg_commit(); wg_wait<1>(); softmax(s, p0, M0); wg_wait<0>();
  }
  wg_fence(); qk(s, NI - 1); wg_commit(); pv(p0, NI - 2, M0); wg_commit(); wg_wait<1>(); softmax(s, p1, M1); wg_wait<0>();
  wg_fence(); pv(p1, NI - 1, M1); wg_commit();
  wg_wait<0>();
  reg_fence(oa); reg_fence(ob);
}
__device__ __forceinline__ void mma16816(float (&d)[4], const uint32_t (&a)[4], uint32_t b0, uint32_t b1) {
  asm("mma.sync.aligned.m16n8k16.row.col.f32.bf16.bf16.f32 {%0,%1,%2,%3},{%4,%5,%6,%7},{%8,%9},{%0,%1,%2,%3};"
      : "+f"(d[0]), "+f"(d[1]), "+f"(d[2]), "+f"(d[3]) : "r"(a[0]), "r"(a[1]), "r"(a[2]), "r"(a[3]), "r"(b0), "r"(b1));
}
__device__ __forceinline__ void attn_safe(float (&o)[12], const uint32_t (&q)[4], uint32_t sK) {
  const int lane = threadIdx.x & 31;
  const uint32_t ka = sK + (lane >> 4) * 32768 + (lane & 15) * 16;
  float m0 = -INFINITY, m1 = -INFINITY;
#pragma unroll 2
  for (int i = 0; i < 128; i++) {
    uint32_t k[4]; ldsm4(ka + i * 256, k);
    float s0[4] = {0, 0, 0, 0}, s1[4] = {0, 0, 0, 0};
    mma16816(s0, q, k[0], k[2]); mma16816(s1, q, k[1], k[3]);
    m0 = fmaxf(fmaxf(m0, fmaxf(s0[0], s0[1])), fmaxf(s1[0], s1[1])); m1 = fmaxf(fmaxf(m1, fmaxf(s0[2], s0[3])), fmaxf(s1[2], s1[3]));
  }
  m0 = fmaxf(m0, __shfl_xor_sync(~0u, m0, 1)); m0 = fmaxf(m0, __shfl_xor_sync(~0u, m0, 2));
  m1 = fmaxf(m1, __shfl_xor_sync(~0u, m1, 1)); m1 = fmaxf(m1, __shfl_xor_sync(~0u, m1, 2));
  float o0[4] = {0, 0, 0, 0}, o1[4] = {0, 0, 0, 0}, o2[4] = {0, 0, 0, 0};
#pragma unroll 2
  for (int i = 0; i < 128; i++) {
    uint32_t k[4], v[4]; ldsm4(ka + i * 256, k);
    asm volatile("ldmatrix.sync.aligned.m8n8.x4.trans.shared.b16 {%0,%1,%2,%3},[%4];" : "=r"(v[0]), "=r"(v[1]), "=r"(v[2]), "=r"(v[3]) : "r"(ka + 65536 + i * 256) : "memory");
    float s0[4] = {0, 0, 0, 0}, s1[4] = {0, 0, 0, 0};
    mma16816(s0, q, k[0], k[2]); mma16816(s1, q, k[1], k[3]);
    const uint32_t p[4] = {pack_rn(ex2(s0[0] - m0), ex2(s0[1] - m0)), pack_rn(ex2(s0[2] - m1), ex2(s0[3] - m1)),
                           pack_rn(ex2(s1[0] - m0), ex2(s1[1] - m0)), pack_rn(ex2(s1[2] - m1), ex2(s1[3] - m1))};
    mma16816(o0, p, v[0], v[1]); mma16816(o1, p, v[2], v[3]); mma16816(o2, p, 0x3F803F80u, 0x3F803F80u);
  }
#pragma unroll
  for (int i = 0; i < 4; i++) { o[i] = o0[i]; o[4 + i] = o1[i]; o[8 + i] = o2[i]; }
}
__global__ void __cluster_dims__(2, 1, 1) __launch_bounds__(512, 1) k_attn(const bf16* wo, const bf16* w1, const bf16* w3, const bf16* w2, const bf16* __restrict__ cv, const bf16* __restrict__ wm, uint32_t kz) {
  extern __shared__ __align__(1024) uint8_t smem[];
  const uint32_t sK = smem_u32(smem), bars = sK + 5 * 32768;
  const int tid = threadIdx.x, warp = tid >> 5, lane = tid & 31, g = lane >> 2, t = lane & 3;
  pdl_launch();
  if (blockIdx.x < 4) {
    float* cs = (float*)smem;
    cs[tid] = silu_bf(cv[tid]);
    __syncthreads();
    const int n0 = 1024 + blockIdx.x * 512, r0 = (tid >> 6) * 64;
    float a[8] = {0, 0, 0, 0, 0, 0, 0, 0};
#pragma unroll 16
    for (int r = r0; r < r0 + 64; r++) fma8(a, cs[r], __ldg((const uint4*)(wm + r * 3072 + n0 + (tid & 63) * 8)));
    float4* rp = (float4*)(cs + 512 + tid * 8);
    rp[0] = make_float4(a[0], a[1], a[2], a[3]); rp[1] = make_float4(a[4], a[5], a[6], a[7]);
    __syncthreads();
    float s = 0;
#pragma unroll
    for (int i = 0; i < 8; i++) s += cs[512 + i * 512 + tid];
    g_mod[n0 + tid] = mod_fin(s, n0 + tid);
    return;
  }
  const int bid = blockIdx.x - 4, h = bid >> 2, qb = bid & 3;
  TS(2, 0);
  if (tid == 0) { for (int i = 0; i < 8; i++) { mbar_init(bars + 8 * i, 1); mbar_expect(bars + 8 * i, 16384); } fence_init(); }
#pragma unroll
  for (int i = 0; i < 4; i++) *(uint4*)(smem + 131072 + i * 8192 + tid * 16) = make_uint4(0x3F803F80u, 0x3F803F80u, 0x3F803F80u, 0x3F803F80u);
  fence_async();
  cluster_sync();
  pdl_wait();
  TS(2, 1);
  if (tid >= 472) g_modv[bid * 40 + tid - 472] = 0;
  const uint4 km4 = *(const uint4*)(g_kmax + h * 128 + lane * 4);
  const uint32_t* qp = (const uint32_t*)g_qkv + (h * 2 * 2048 + qb * 512 + warp * 16 + g) * 4 + t;
  uint32_t q[4] = {qp[0], qp[32], qp[8192], qp[8192 + 32]};
  auto ldkv = [&]() {
    const int c = warp >> 1, pl = (qb & 1) + (warp & 1) * 2;
    bulk_load_mc(sK + pl * 32768 + c * 4096, g_qkv + ((64 + (pl >> 1) * 64 + h * 2 + (pl & 1)) * 2048 + c * 256) * 8, 4096, bars + 8 * c);
  };
  if (lane == 0 && warp < 4) ldkv();
  const uint32_t qn[4] = {qp[1024], qp[1024 + 32], qp[1024 + 8192], qp[1024 + 8192 + 32]};
  const float kmax = __uint_as_float(__reduce_max_sync(~0u, max(max(km4.x, km4.y), max(km4.z, km4.w))));
  if (lane == 0 && warp >= 4 && kmax != -1.f) ldkv();
#pragma unroll 1
  for (int tile = 0; tile < 2; tile++) {
    const int row = qb * 512 + tile * 256 + warp * 16 + g;
    const float n0 = qsum(blo(q[0]) * blo(q[0]) + bhi(q[0]) * bhi(q[0]) + blo(q[2]) * blo(q[2]) + bhi(q[2]) * bhi(q[2]));
    const float n1 = qsum(blo(q[1]) * blo(q[1]) + bhi(q[1]) * bhi(q[1]) + blo(q[3]) * blo(q[3]) + bhi(q[3]) * bhi(q[3]));
    const float b0 = sqrtf(n0 * kmax) * 1.001f, b1 = sqrtf(n1 * kmax) * 1.001f;
    const float m0 = fmaxf(ceilf(b0 - 100.f), 0.f), m1 = fmaxf(ceilf(b1 - 100.f), 0.f);
    float o[12], ob[12];
    attn_pass(o, ob, q, m0, m1, sK, bars, tile == 0, kz);
    const float f0 = ex2(-m0), f1 = ex2(-m1);
#pragma unroll
    for (int i = 0; i < 12; i++) o[i] = fmaf(o[i], (i & 2) ? f1 : f0, ob[i]);
    bool ok = b0 < 220.f && b1 < 220.f && o[8] >= 0x1p-90f && o[10] >= 0x1p-90f;
#pragma unroll
    for (int i = 0; i < 12; i++) ok = ok && fabsf(o[i]) < INFINITY;
    if (!__all_sync(~0u, ok)) attn_safe(o, q, sK);
    const float r0 = 1.f / o[8], r1 = 1.f / o[10];
    uint32_t* op = (uint32_t*)g_o + (((row >> 7) * 64 + h * 2) * 128 + (row & 127)) * 4 + t;
    op[0] = pack_rn(o[0] * r0, o[1] * r0); op[32] = pack_rn(o[2] * r1, o[3] * r1);
    op[512] = pack_rn(o[4] * r0, o[5] * r0); op[512 + 32] = pack_rn(o[6] * r1, o[7] * r1);
    if (tile == 0 && tid == 32) {
      l2_prefetch((const char*)wo + bid * 4096, 4096);
      l2_prefetch((const char*)w1 + bid * 11008, 11008);
      l2_prefetch((const char*)w3 + bid * 11008, 11008);
      l2_prefetch((const char*)w2 + bid * 11008, 11008);
    }
#pragma unroll
    for (int i = 0; i < 4; i++) q[i] = qn[i];
    TS(2, 3 + tile);
  }
}

constexpr int WO_SMEM = 131072 + 65536 + 256;
__global__ void __cluster_dims__(2, 1, 1) __launch_bounds__(256, 1) k_wo(const __grid_constant__ CUtensorMap mW, const bf16* __restrict__ x) {
  extern __shared__ __align__(1024) uint8_t smem[];
  const uint32_t sA = smem_u32(smem), sB = sA + 131072, bars = sB + 65536;
  const int tid = threadIdx.x, warp = tid >> 5, lane = tid & 31, g = lane >> 2, t = lane & 3;
  const int rb = blockIdx.x >> 3, ct = blockIdx.x & 7;
  TS(3, 0);
  pdl_launch();
  if (tid == 0) {
    for (int i = 0; i < 8; i++) mbar_init(bars + 8 * i, 1);
    fence_init();
    for (int i = 0; i < 8; i++) { mbar_expect(bars + 8 * i, 24576); tma2d(sB + i * 8192, &mW, ct * 64, i * 64, bars + 8 * i); }
  }
  __syncwarp();
  cluster_arrive();
  const int lrow = warp * 16 + g;
  uint32_t xr[16];
  const uint32_t* xp = (const uint32_t*)(x + (rb * 128 + lrow) * 512 + ct * 64) + t;
#pragma unroll
  for (int j = 0; j < 8; j++) { xr[2 * j] = __ldg(xp + j * 4); xr[2 * j + 1] = __ldg(xp + j * 4 + 8 * 256); }
  cluster_wait();
  pdl_wait();
  if (tid == 0) {
    for (int i = ct & 1; i < 8; i += 2) bulk_load_mc(sA + i * 16384, g_o + (rb * 64 + i * 8) * 1024, 16384, bars + 8 * i);
  }
  TS(3, 1);
  float2 ga[8];
#pragma unroll
  for (int j = 0; j < 8; j++) ga[j] = *(const float2*)(g_mod + 1024 + ct * 64 + j * 8 + t * 2);
  float acc[32];
  const uint64_t da = mk_desc(sA + (warp >> 2) * 1024, 2048, 128, 0), db = mk_desc(sB, 8192, 1024, 1);
#pragma unroll
  for (int c = 0; c < 8; c++) {
    mbar_wait(bars + 8 * c, 0);
    if (c == 0) TS(3, 2);
    wg_fence();
#pragma unroll
    for (int k = 0; k < 4; k++) wgmma_ss_n64_t1(acc, da + (c * 4 + k) * 256, db + (c * 4 + k) * 128, c + k);
    wg_commit();
  }
  wg_wait<0>();
  reg_fence(acc);
  TS(3, 3);
  uint32_t* o = (uint32_t*)g_x1 + ((rb * 64 + ct * 8) * 128 + lrow) * 4 + t;
  float s0 = 0, s1 = 0;
#pragma unroll
  for (int j = 0; j < 8; j++) {
    xr[2 * j] = pack_rn(fmaf(ga[j].x, acc[4 * j], blo(xr[2 * j])), fmaf(ga[j].y, acc[4 * j + 1], bhi(xr[2 * j])));
    xr[2 * j + 1] = pack_rn(fmaf(ga[j].x, acc[4 * j + 2], blo(xr[2 * j + 1])), fmaf(ga[j].y, acc[4 * j + 3], bhi(xr[2 * j + 1])));
    o[j * 512] = xr[2 * j]; o[j * 512 + 32] = xr[2 * j + 1];
    s0 += blo(xr[2 * j]) + bhi(xr[2 * j]); s1 += blo(xr[2 * j + 1]) + bhi(xr[2 * j + 1]);
  }
  const float m0 = qsum(s0) * (1.f / 64), m1 = qsum(s1) * (1.f / 64);
  float v0 = 0, v1 = 0;
#pragma unroll
  for (int j = 0; j < 8; j++) {
    float d;
    d = blo(xr[2 * j]) - m0; v0 += d * d; d = bhi(xr[2 * j]) - m0; v0 += d * d;
    d = blo(xr[2 * j + 1]) - m1; v1 += d * d; d = bhi(xr[2 * j + 1]) - m1; v1 += d * d;
  }
  v0 = qsum(v0); v1 = qsum(v1);
  if (t == 0) g_st[(rb * 128 + lrow) * 8 + ct] = make_float2(m0, v0);
  if (t == 1) g_st[(rb * 128 + lrow + 8) * 8 + ct] = make_float2(m1, v1);
  TS(3, 4);
}

constexpr int W2_SMEM = 6 * 32768 + 32768 + 256;
__global__ void __cluster_dims__(2, 1, 1) __launch_bounds__(288, 1) k_w2(const __grid_constant__ CUtensorMap mW, bf16* __restrict__ out) {
  extern __shared__ __align__(1024) uint8_t smem[];
  const uint32_t sR = smem_u32(smem), sX = sR + 6 * 32768, bF = sX + 32768, bE = bF + 48, bX = bF + 96;
  const int tid = threadIdx.x, warp = tid >> 5, lane = tid & 31, g = lane >> 2, t = lane & 3;
  const int kh = blockIdx.x & 1, ct = (blockIdx.x >> 1) & 3, rb = blockIdx.x >> 3;
  TS(5, 0);
  pdl_launch();
  if (tid == 256) {
    for (int i = 0; i < 6; i++) { mbar_init(bF + 8 * i, 1); mbar_init(bE + 8 * i, 8); }
    for (int i = 0; i < 8; i++) { mbar_init(bX + 8 * i, 1); mbar_expect(bX + 8 * i, 4096); }
    fence_init();
  }
  __syncthreads();
  asm volatile("barrier.cluster.arrive.relaxed.aligned;" ::: "memory");
  if (warp == 8) {
    if (lane == 0) {
      auto abytes = [&](int s) { return (kh == 1 && s == 10) ? 8192 : 16384; };
      auto loadB = [&](int s) {
        const int st = s % 6;
        mbar_expect(bF + 8 * st, 16384 + abytes(s));
        for (int j = 0; j < 2; j++) tma2d(sR + st * 32768 + 16384 + j * 8192, &mW, ct * 128 + j * 64, kh * 704 + s * 64, bF + 8 * st);
      };
      auto loadA = [&](int s) { bulk_load(sR + (s % 6) * 32768, g_h + (rb * 172 + kh * 88 + s * 8) * 1024, abytes(s), bF + 8 * (s % 6)); };
      for (int s = 0; s < 6; s++) loadB(s);
      pdl_wait();
      for (int s = 0; s < 6; s++) loadA(s);
      for (int s = 6; s < 11; s++) { mbar_wait(bE + 8 * (s - 6), 0); loadB(s); loadA(s); }
    }
    __syncwarp();
    cluster_wait();
    return;
  }
  pdl_wait();
  TS(5, 1);
  const int lrow = warp * 16 + g;
  uint32_t xr[16];
  float2 gb[8];
  const uint32_t* xp = (const uint32_t*)g_x1 + ((rb * 64 + ct * 16 + kh * 8) * 128 + lrow) * 4 + t;
#pragma unroll
  for (int j = 0; j < 8; j++) {
    xr[2 * j] = xp[j * 512]; xr[2 * j + 1] = xp[j * 512 + 32];
    gb[j] = *(const float2*)(g_mod + 2560 + ct * 128 + kh * 64 + j * 8 + t * 2);
  }
  float acc[64];
#pragma unroll 1
  for (int s = 0; s < 11; s++) {
    const int st = s % 6;
    mbar_wait(bF + 8 * st, s >= 6);
    const uint64_t da = mk_desc(sR + st * 32768 + (warp >> 2) * 1024, 2048, 128, 0), db = mk_desc(sR + st * 32768 + 16384, 8192, 1024, 1);
    if (s == 0) TS(5, 2);
    wg_fence();
    wgmma_ss_n128_t1(acc, da, db, s);
    wgmma_ss_n128_t1(acc, da + 256, db + 128, 1);
    wgmma_ss_n128_t1(acc, da + 512, db + 256, 1);
    wgmma_ss_n128_t1(acc, da + 768, db + 384, 1);
    wg_commit();
    wg_wait<1>();
    if (s > 0 && s < 6 && lane == 0) mbar_arrive(bE + 8 * (s - 1));
  }
  wg_wait<0>();
  reg_fence(acc);
  TS(5, 3);
  asm volatile("barrier.cluster.wait.aligned;" ::: "memory");
  uint32_t rem, rbar;
  asm("mapa.shared::cluster.u32 %0,%1,%2;" : "=r"(rbar) : "r"(bX + warp * 8), "r"(kh ^ 1));
  asm("mapa.shared::cluster.u32 %0,%1,%2;" : "=r"(rem) : "r"(sX + warp * 4096 + lane * 16), "r"(kh ^ 1));
#pragma unroll
  for (int j = 0; j < 8; j++) {
    float v[4];
#pragma unroll
    for (int i = 0; i < 4; i++) { v[i] = kh ? acc[4 * j + i] : acc[32 + 4 * j + i]; acc[4 * j + i] = kh ? acc[32 + 4 * j + i] : acc[4 * j + i]; }
    asm volatile("st.async.weak.shared::cluster.mbarrier::complete_tx::bytes.v4.f32 [%0],{%1,%2,%3,%4},[%5];" ::"r"(rem + j * 512), "f"(v[0]), "f"(v[1]), "f"(v[2]), "f"(v[3]), "r"(rbar) : "memory");
  }
  mbar_wait(bX + warp * 8, 0);
  TS(5, 5);
  const uint32_t sw = sX + warp * 4096;
#pragma unroll
  for (int j = 0; j < 8; j++) {
    const float4 p = *(const float4*)(smem + 6 * 32768 + warp * 4096 + j * 512 + lane * 16);
    xr[2 * j] = pack_rn(fmaf(gb[j].x, acc[4 * j] + p.x, blo(xr[2 * j])), fmaf(gb[j].y, acc[4 * j + 1] + p.y, bhi(xr[2 * j])));
    xr[2 * j + 1] = pack_rn(fmaf(gb[j].x, acc[4 * j + 2] + p.z, blo(xr[2 * j + 1])), fmaf(gb[j].y, acc[4 * j + 3] + p.w, bhi(xr[2 * j + 1])));
  }
  __syncwarp();
#pragma unroll
  for (int j = 1; j < 8; j += 2) {
    asm volatile("stmatrix.sync.aligned.m8n8.x4.shared.b16 [%0],{%1,%2,%3,%4};" ::"r"(sw + (lane & 15) * 128 + (((j - 1 + (lane >> 4)) ^ (lane & 7)) << 4)),
                            "r"(xr[2 * j - 2]), "r"(xr[2 * j - 1]), "r"(xr[2 * j]), "r"(xr[2 * j + 1]) : "memory");
  }
  __syncwarp();
#pragma unroll
  for (int i = 0; i < 4; i++) {
    const int r = i * 4 + (lane >> 3);
    *(uint4*)(out + (rb * 128 + warp * 16 + r) * 512 + ct * 128 + kh * 64 + (lane & 7) * 8) = *(const uint4*)(smem + 6 * 32768 + warp * 4096 + r * 128 + (((lane ^ r) & 7) << 4));
  }
  TS(5, 4);
}

typedef CUresult (*EncFn)(CUtensorMap*, CUtensorMapDataType, cuuint32_t, void*, const cuuint64_t*, const cuuint64_t*, const cuuint32_t*,
                          const cuuint32_t*, CUtensorMapInterleave, CUtensorMapSwizzle, CUtensorMapL2promotion, CUtensorMapFloatOOBfill);
static void mk_map(EncFn f, CUtensorMap* m, const void* p, int rows, int cols, int box_rows) {
  cuuint64_t dim[2] = {(cuuint64_t)cols, (cuuint64_t)rows}, str[1] = {(cuuint64_t)cols * 2};
  cuuint32_t box[2] = {64, (cuuint32_t)box_rows}, es[2] = {1, 1};
  f(m, CU_TENSOR_MAP_DATA_TYPE_BFLOAT16, 2, (void*)p, dim, str, box, es, CU_TENSOR_MAP_INTERLEAVE_NONE, CU_TENSOR_MAP_SWIZZLE_128B,
    CU_TENSOR_MAP_L2_PROMOTION_L2_128B, CU_TENSOR_MAP_FLOAT_OOB_FILL_NONE);
}
template <typename... KA, typename... A>
static void launch(void (*k)(KA...), int grid, int block, int smem, bool pdl, A... args) {
  cudaLaunchConfig_t cfg = {};
  cfg.gridDim = dim3(grid); cfg.blockDim = dim3(block); cfg.dynamicSmemBytes = smem; cfg.stream = cudaStreamPerThread;
  cudaLaunchAttribute at[1];
  at[0].id = cudaLaunchAttributeProgrammaticStreamSerialization; at[0].val.programmaticStreamSerializationAllowed = 1;
  cfg.attrs = at; cfg.numAttrs = pdl ? 1 : 0;
  cudaLaunchKernelEx(&cfg, k, args...);
}
extern "C" void kernel_launch(void* const* d_in, const int* in_sizes, int n_in, void* d_out, int out_size) {
  const bf16 *x = (const bf16*)d_in[0], *wqkv = (const bf16*)d_in[1], *wo = (const bf16*)d_in[2], *w1 = (const bf16*)d_in[4],
             *w3 = (const bf16*)d_in[5], *w2 = (const bf16*)d_in[6], *c = (const bf16*)d_in[7], *wmod = (const bf16*)d_in[8];
  void* fp = nullptr;
  cudaDriverEntryPointQueryResult qr;
  cudaGetDriverEntryPoint("cuTensorMapEncodeTiled", &fp, cudaEnableDefault, &qr);
  EncFn f = (EncFn)fp;
  CUtensorMap mX, mQ, mO, m1, m3, m2;
  mk_map(f, &mX, x, S_, D_, 128); mk_map(f, &mQ, wqkv, D_, 3 * D_, 64); mk_map(f, &mO, wo, D_, D_, 64);
  mk_map(f, &m1, w1, D_, F_, 32); mk_map(f, &m3, w3, D_, F_, 32); mk_map(f, &m2, w2, F_, D_, 64);
  cudaFuncSetAttribute(k_lngemm<false>, cudaFuncAttributeMaxDynamicSharedMemorySize, LN_SMEM);
  cudaFuncSetAttribute(k_lngemm<true>, cudaFuncAttributeMaxDynamicSharedMemorySize, LN_SMEM);
  cudaFuncSetAttribute(k_attn, cudaFuncAttributeMaxDynamicSharedMemorySize, AT_SMEM);
  cudaFuncSetAttribute(k_wo, cudaFuncAttributeMaxDynamicSharedMemorySize, WO_SMEM);
  cudaFuncSetAttribute(k_w2, cudaFuncAttributeMaxDynamicSharedMemorySize, W2_SMEM);
  launch(k_lngemm<false>, 128, 384, LN_SMEM, false, mX, mQ, mQ, c, wmod, x);
  launch(k_attn, 132, 512, AT_SMEM, true, wo, w1, w3, w2, c, wmod, 0u);
  launch(k_wo, 128, 256, WO_SMEM, true, mO, x);
  launch(k_lngemm<true>, 128, 384, LN_SMEM, true, mX, m1, m3, c, wmod, x);
  launch(k_w2, 128, 288, W2_SMEM, true, m2, (bf16*)d_out);
}
```

```cpp
#include <cuda_runtime.h>
#include <cuda_bf16.h>
#include <cuda.h>
#include <stdint.h>
typedef __nv_bfloat16 bf16;
constexpr int S_ = 2048, D_ = 512, F_ = 1376;
__device__ __align__(1024) float g_mod[3072];
__device__ __align__(1024) uint32_t g_modv[1024 + 4096];
__device__ __align__(1024) bf16 g_qkv[192 * 2048 * 8];
__device__ __align__(1024) float g_kmax[32 * 128];
__device__ __align__(1024) bf16 g_o[16 * 64 * 128 * 8];
__device__ __align__(1024) bf16 g_x1[16 * 64 * 128 * 8];
__device__ __align__(1024) float2 g_st[2048 * 8];
__device__ __align__(1024) bf16 g_h[16 * 172 * 128 * 8];

__device__ __forceinline__ uint32_t smem_u32(const void* p) { return (uint32_t)__cvta_generic_to_shared(p); }
__device__ __forceinline__ void mbar_init(uint32_t b, int n) { asm volatile("mbarrier.init.shared::cta.b64 [%0],%1;" ::"r"(b), "r"(n) : "memory"); }
__device__ __forceinline__ void mbar_expect(uint32_t b, int bytes) { asm volatile("mbarrier.arrive.expect_tx.shared::cta.b64 _,[%0],%1;" ::"r"(b), "r"(bytes) : "memory"); }
__device__ __forceinline__ void mbar_arrive(uint32_t b) { asm volatile("mbarrier.arrive.shared::cta.b64 _,[%0];" ::"r"(b) : "memory"); }
__device__ __forceinline__ void mbar_wait(uint32_t b, int parity) {
  asm volatile("{\n.reg .pred p;\n.reg .u32 n;\nmov.u32 n,0;\nLW:\nmbarrier.try_wait.parity.shared::cta.b64 p,[%0],%1;\n@p bra LD;\n"
               "add.u32 n,n,1;\nsetp.lt.u32 p,n,4194304;\n@p bra LW;\nLD:\n}\n" ::"r"(b), "r"(parity) : "memory");
}
__device__ __forceinline__ void fence_init() { asm volatile("fence.mbarrier_init.release.cluster;" ::: "memory"); }
__device__ __forceinline__ void fence_async() { asm volatile("fence.proxy.async.shared::cta;" ::: "memory"); }
__device__ __forceinline__ void bulk_load(uint32_t dst, const void* src, int bytes, uint32_t bar) {
  asm volatile("cp.async.bulk.shared::cluster.global.mbarrier::complete_tx::bytes [%0],[%1],%2,[%3];" ::"r"(dst), "l"(src), "r"(bytes), "r"(bar) : "memory");
}
__device__ __forceinline__ void tma2d(uint32_t dst, const CUtensorMap* m, int c0, int c1, uint32_t bar) {
  asm volatile("cp.async.bulk.tensor.2d.shared::cluster.global.mbarrier::complete_tx::bytes [%0],[%1,{%3,%4}],[%2];" ::"r"(dst), "l"(m), "r"(bar), "r"(c0), "r"(c1) : "memory");
}
__device__ __forceinline__ void bulk_load_mc(uint32_t dst, const void* src, int bytes, uint32_t bar) {
  asm volatile("cp.async.bulk.shared::cluster.global.mbarrier::complete_tx::bytes.multicast::cluster [%0],[%1],%2,[%3],%4;" ::"r"(dst), "l"(src), "r"(bytes), "r"(bar), "h"((uint16_t)3) : "memory");
}
__device__ __forceinline__ void tma2d_mc(uint32_t dst, const CUtensorMap* m, int c0, int c1, uint32_t bar) {
  asm volatile("cp.async.bulk.tensor.2d.shared::cluster.global.mbarrier::complete_tx::bytes.multicast::cluster [%0],[%1,{%3,%4}],[%2],%5;" ::"r"(dst), "l"(m), "r"(bar), "r"(c0), "r"(c1), "h"((uint16_t)3) : "memory");
}
__device__ __forceinline__ void cluster_arrive() { asm volatile("barrier.cluster.arrive.relaxed.aligned;" ::: "memory"); }
__device__ __forceinline__ void cluster_wait() { asm volatile("barrier.cluster.wait.aligned;" ::: "memory"); }
__device__ __forceinline__ void cluster_sync() { asm volatile("barrier.cluster.arrive.release.aligned;\nbarrier.cluster.wait.acquire.aligned;" ::: "memory"); }
__device__ __forceinline__ void l2_prefetch(const void* p, int bytes) { asm volatile("cp.async.bulk.prefetch.L2.global [%0],%1;" ::"l"(p), "r"(bytes) : "memory"); }
__device__ __forceinline__ void pdl_launch() { asm volatile("griddepcontrol.launch_dependents;" ::: "memory"); }
__device__ __forceinline__ void pdl_wait() { asm volatile("griddepcontrol.wait;" ::: "memory"); }
__device__ __forceinline__ void wg_fence() { asm volatile("wgmma.fence.sync.aligned;" ::: "memory"); }
__device__ __forceinline__ void wg_commit() { asm volatile("wgmma.commit_group.sync.aligned;" ::: "memory"); }
template <int N> __device__ __forceinline__ void wg_wait() { asm volatile("wgmma.wait_group.sync.aligned %0;" ::"n"(N) : "memory"); }
template <int N> __device__ __forceinline__ void reg_fence(float (&d)[N]) {
#pragma unroll
  for (int i = 0; i < N; i++) asm volatile("" : "+f"(d[i])::"memory");
}
template <int N> __device__ __forceinline__ void zero(float (&d)[N]) {
#pragma unroll
  for (int i = 0; i < N; i++) d[i] = 0.f;
  reg_fence(d);
}
__device__ __forceinline__ uint64_t mk_desc(uint32_t addr, uint32_t lbo, uint32_t sbo, uint32_t mode) {
  return (uint64_t)((addr >> 4) & 0x3FFF) | ((uint64_t)(lbo >> 4) << 16) | ((uint64_t)(sbo >> 4) << 32) | ((uint64_t)mode << 62);
}
__device__ __forceinline__ void ldsm4(uint32_t a, uint32_t (&r)[4]) {
  asm volatile("ldmatrix.sync.aligned.m8n8.x4.shared.b16 {%0,%1,%2,%3},[%4];" : "=r"(r[0]), "=r"(r[1]), "=r"(r[2]), "=r"(r[3]) : "r"(a) : "memory");
}
__device__ __forceinline__ uint32_t pack_rn(float lo, float hi) { uint32_t r; asm("cvt.rn.bf16x2.f32 %0,%1,%2;" : "=r"(r) : "f"(hi), "f"(lo)); return r; }
__device__ __forceinline__ uint32_t pack_rz(float lo, float hi) { uint32_t r; asm("cvt.rz.bf16x2.f32 %0,%1,%2;" : "=r"(r) : "f"(hi), "f"(lo)); return r; }
__device__ __forceinline__ float blo(uint32_t u) { return __uint_as_float(u << 16); }
__device__ __forceinline__ float bhi(uint32_t u) { return __uint_as_float(u & 0xFFFF0000u); }
__device__ __forceinline__ float rbf(float x) { return __bfloat162float(__float2bfloat16_rn(x)); }
__device__ __forceinline__ float qsum(float v) { v += __shfl_xor_sync(~0u, v, 1); return v + __shfl_xor_sync(~0u, v, 2); }
__device__ __forceinline__ float ex2(float x) { float r; asm("ex2.approx.ftz.f32 %0,%1;" : "=f"(r) : "f"(x)); return r; }
#define TS(k, i)
__device__ __forceinline__ void wgmma_rs_n176_t1(float (&d)[88],uint32_t a0,uint32_t a1,uint32_t a2,uint32_t a3,uint64_t db,int sc){
  asm volatile("{\n.reg .pred p;\nsetp.ne.b32 p,%93,0;\n"
    "wgmma.mma_async.sync.aligned.m64n176k16.f32.bf16.bf16 {%0,%1,%2,%3,%4,%5,%6,%7,%8,%9,%10,%11,%12,%13,%14,%15,%16,%17,%18,%19,%20,%21,%22,%23,%24,%25,%26,%27,%28,%29,%30,%31,%32,%33,%34,%35,%36,%37,%38,%39,%40,%41,%42,%43,%44,%45,%46,%47,%48,%49,%50,%51,%52,%53,%54,%55,%56,%57,%58,%59,%60,%61,%62,%63,%64,%65,%66,%67,%68,%69,%70,%71,%72,%73,%74,%75,%76,%77,%78,%79,%80,%81,%82,%83,%84,%85,%86,%87},{%88,%89,%90,%91},%92,p,1,1,1;\n}\n"
    :"+f"(d[0]),"+f"(d[1]),"+f"(d[2]),"+f"(d[3]),"+f"(d[4]),"+f"(d[5]),"+f"(d[6]),"+f"(d[7]),"+f"(d[8]),"+f"(d[9]),"+f"(d[10]),"+f"(d[11]),"+f"(d[12]),"+f"(d[13]),"+f"(d[14]),"+f"(d[15]),"+f"(d[16]),"+f"(d[17]),"+f"(d[18]),"+f"(d[19]),"+f"(d[20]),"+f"(d[21]),"+f"(d[22]),"+f"(d[23]),"+f"(d[24]),"+f"(d[25]),"+f"(d[26]),"+f"(d[27]),"+f"(d[28]),"+f"(d[29]),"+f"(d[30]),"+f"(d[31]),"+f"(d[32]),"+f"(d[33]),"+f"(d[34]),"+f"(d[35]),"+f"(d[36]),"+f"(d[37]),"+f"(d[38]),"+f"(d[39]),"+f"(d[40]),"+f"(d[41]),"+f"(d[42]),"+f"(d[43]),"+f"(d[44]),"+f"(d[45]),"+f"(d[46]),"+f"(d[47]),"+f"(d[48]),"+f"(d[49]),"+f"(d[50]),"+f"(d[51]),"+f"(d[52]),"+f"(d[53]),"+f"(d[54]),"+f"(d[55]),"+f"(d[56]),"+f"(d[57]),"+f"(d[58]),"+f"(d[59]),"+f"(d[60]),"+f"(d[61]),"+f"(d[62]),"+f"(d[63]),"+f"(d[64]),"+f"(d[65]),"+f"(d[66]),"+f"(d[67]),"+f"(d[68]),"+f"(d[69]),"+f"(d[70]),"+f"(d[71]),"+f"(d[72]),"+f"(d[73]),"+f"(d[74]),"+f"(d[75]),"+f"(d[76]),"+f"(d[77]),"+f"(d[78]),"+f"(d[79]),"+f"(d[80]),"+f"(d[81]),"+f"(d[82]),"+f"(d[83]),"+f"(d[84]),"+f"(d[85]),"+f"(d[86]),"+f"(d[87])
    :"r"(a0),"r"(a1),"r"(a2),"r"(a3),"l"(db),"r"(sc));
}
__device__ __forceinline__ void wgmma_rs_n192_t1(float (&d)[96],uint32_t a0,uint32_t a1,uint32_t a2,uint32_t a3,uint64_t db,int sc){
  asm volatile("{\n.reg .pred p;\nsetp.ne.b32 p,%101,0;\n"
    "wgmma.mma_async.sync.aligned.m64n192k16.f32.bf16.bf16 {%0,%1,%2,%3,%4,%5,%6,%7,%8,%9,%10,%11,%12,%13,%14,%15,%16,%17,%18,%19,%20,%21,%22,%23,%24,%25,%26,%27,%28,%29,%30,%31,%32,%33,%34,%35,%36,%37,%38,%39,%40,%41,%42,%43,%44,%45,%46,%47,%48,%49,%50,%51,%52,%53,%54,%55,%56,%57,%58,%59,%60,%61,%62,%63,%64,%65,%66,%67,%68,%69,%70,%71,%72,%73,%74,%75,%76,%77,%78,%79,%80,%81,%82,%83,%84,%85,%86,%87,%88,%89,%90,%91,%92,%93,%94,%95},{%96,%97,%98,%99},%100,p,1,1,1;\n}\n"
    :"+f"(d[0]),"+f"(d[1]),"+f"(d[2]),"+f"(d[3]),"+f"(d[4]),"+f"(d[5]),"+f"(d[6]),"+f"(d[7]),"+f"(d[8]),"+f"(d[9]),"+f"(d[10]),"+f"(d[11]),"+f"(d[12]),"+f"(d[13]),"+f"(d[14]),"+f"(d[15]),"+f"(d[16]),"+f"(d[17]),"+f"(d[18]),"+f"(d[19]),"+f"(d[20]),"+f"(d[21]),"+f"(d[22]),"+f"(d[23]),"+f"(d[24]),"+f"(d[25]),"+f"(d[26]),"+f"(d[27]),"+f"(d[28]),"+f"(d[29]),"+f"(d[30]),"+f"(d[31]),"+f"(d[32]),"+f"(d[33]),"+f"(d[34]),"+f"(d[35]),"+f"(d[36]),"+f"(d[37]),"+f"(d[38]),"+f"(d[39]),"+f"(d[40]),"+f"(d[41]),"+f"(d[42]),"+f"(d[43]),"+f"(d[44]),"+f"(d[45]),"+f"(d[46]),"+f"(d[47]),"+f"(d[48]),"+f"(d[49]),"+f"(d[50]),"+f"(d[51]),"+f"(d[52]),"+f"(d[53]),"+f"(d[54]),"+f"(d[55]),"+f"(d[56]),"+f"(d[57]),"+f"(d[58]),"+f"(d[59]),"+f"(d[60]),"+f"(d[61]),"+f"(d[62]),"+f"(d[63]),"+f"(d[64]),"+f"(d[65]),"+f"(d[66]),"+f"(d[67]),"+f"(d[68]),"+f"(d[69]),"+f"(d[70]),"+f"(d[71]),"+f"(d[72]),"+f"(d[73]),"+f"(d[74]),"+f"(d[75]),"+f"(d[76]),"+f"(d[77]),"+f"(d[78]),"+f"(d[79]),"+f"(d[80]),"+f"(d[81]),"+f"(d[82]),"+f"(d[83]),"+f"(d[84]),"+f"(d[85]),"+f"(d[86]),"+f"(d[87]),"+f"(d[88]),"+f"(d[89]),"+f"(d[90]),"+f"(d[91]),"+f"(d[92]),"+f"(d[93]),"+f"(d[94]),"+f"(d[95])
    :"r"(a0),"r"(a1),"r"(a2),"r"(a3),"l"(db),"r"(sc));
}
__device__ __forceinline__ void wgmma_rs_n24_t1(float (&d)[12],uint32_t a0,uint32_t a1,uint32_t a2,uint32_t a3,uint64_t db,int sc){
  asm volatile("{\n.reg .pred p;\nsetp.ne.b32 p,%17,0;\n"
    "wgmma.mma_async.sync.aligned.m64n24k16.f32.bf16.bf16 {%0,%1,%2,%3,%4,%5,%6,%7,%8,%9,%10,%11},{%12,%13,%14,%15},%16,p,1,1,1;\n}\n"
    :"+f"(d[0]),"+f"(d[1]),"+f"(d[2]),"+f"(d[3]),"+f"(d[4]),"+f"(d[5]),"+f"(d[6]),"+f"(d[7]),"+f"(d[8]),"+f"(d[9]),"+f"(d[10]),"+f"(d[11])
    :"r"(a0),"r"(a1),"r"(a2),"r"(a3),"l"(db),"r"(sc));
}
__device__ __forceinline__ void wgmma_rs_n64_t0(float (&d)[32],uint32_t a0,uint32_t a1,uint32_t a2,uint32_t a3,uint64_t db,int sc){
  asm volatile("{\n.reg .pred p;\nsetp.ne.b32 p,%37,0;\n"
    "wgmma.mma_async.sync.aligned.m64n64k16.f32.bf16.bf16 {%0,%1,%2,%3,%4,%5,%6,%7,%8,%9,%10,%11,%12,%13,%14,%15,%16,%17,%18,%19,%20,%21,%22,%23,%24,%25,%26,%27,%28,%29,%30,%31},{%32,%33,%34,%35},%36,p,1,1,0;\n}\n"
    :"+f"(d[0]),"+f"(d[1]),"+f"(d[2]),"+f"(d[3]),"+f"(d[4]),"+f"(d[5]),"+f"(d[6]),"+f"(d[7]),"+f"(d[8]),"+f"(d[9]),"+f"(d[10]),"+f"(d[11]),"+f"(d[12]),"+f"(d[13]),"+f"(d[14]),"+f"(d[15]),"+f"(d[16]),"+f"(d[17]),"+f"(d[18]),"+f"(d[19]),"+f"(d[20]),"+f"(d[21]),"+f"(d[22]),"+f"(d[23]),"+f"(d[24]),"+f"(d[25]),"+f"(d[26]),"+f"(d[27]),"+f"(d[28]),"+f"(d[29]),"+f"(d[30]),"+f"(d[31])
    :"r"(a0),"r"(a1),"r"(a2),"r"(a3),"l"(db),"r"(sc));
}
__device__ __forceinline__ void wgmma_ss_n128_t1(float (&d)[64],uint64_t da,uint64_t db,int sc){
  asm volatile("{\n.reg .pred p;\nsetp.ne.b32 p,%66,0;\n"
    "wgmma.mma_async.sync.aligned.m64n128k16.f32.bf16.bf16 {%0,%1,%2,%3,%4,%5,%6,%7,%8,%9,%10,%11,%12,%13,%14,%15,%16,%17,%18,%19,%20,%21,%22,%23,%24,%25,%26,%27,%28,%29,%30,%31,%32,%33,%34,%35,%36,%37,%38,%39,%40,%41,%42,%43,%44,%45,%46,%47,%48,%49,%50,%51,%52,%53,%54,%55,%56,%57,%58,%59,%60,%61,%62,%63},%64,%65,p,1,1,0,1;\n}\n"
    :"+f"(d[0]),"+f"(d[1]),"+f"(d[2]),"+f"(d[3]),"+f"(d[4]),"+f"(d[5]),"+f"(d[6]),"+f"(d[7]),"+f"(d[8]),"+f"(d[9]),"+f"(d[10]),"+f"(d[11]),"+f"(d[12]),"+f"(d[13]),"+f"(d[14]),"+f"(d[15]),"+f"(d[16]),"+f"(d[17]),"+f"(d[18]),"+f"(d[19]),"+f"(d[20]),"+f"(d[21]),"+f"(d[22]),"+f"(d[23]),"+f"(d[24]),"+f"(d[25]),"+f"(d[26]),"+f"(d[27]),"+f"(d[28]),"+f"(d[29]),"+f"(d[30]),"+f"(d[31]),"+f"(d[32]),"+f"(d[33]),"+f"(d[34]),"+f"(d[35]),"+f"(d[36]),"+f"(d[37]),"+f"(d[38]),"+f"(d[39]),"+f"(d[40]),"+f"(d[41]),"+f"(d[42]),"+f"(d[43]),"+f"(d[44]),"+f"(d[45]),"+f"(d[46]),"+f"(d[47]),"+f"(d[48]),"+f"(d[49]),"+f"(d[50]),"+f"(d[51]),"+f"(d[52]),"+f"(d[53]),"+f"(d[54]),"+f"(d[55]),"+f"(d[56]),"+f"(d[57]),"+f"(d[58]),"+f"(d[59]),"+f"(d[60]),"+f"(d[61]),"+f"(d[62]),"+f"(d[63])
    :"l"(da),"l"(db),"r"(sc));
}
__device__ __forceinline__ void wgmma_ss_n64_t1(float (&d)[32],uint64_t da,uint64_t db,int sc){
  asm volatile("{\n.reg .pred p;\nsetp.ne.b32 p,%34,0;\n"
    "wgmma.mma_async.sync.aligned.m64n64k16.f32.bf16.bf16 {%0,%1,%2,%3,%4,%5,%6,%7,%8,%9,%10,%11,%12,%13,%14,%15,%16,%17,%18,%19,%20,%21,%22,%23,%24,%25,%26,%27,%28,%29,%30,%31},%32,%33,p,1,1,0,1;\n}\n"
    :"+f"(d[0]),"+f"(d[1]),"+f"(d[2]),"+f"(d[3]),"+f"(d[4]),"+f"(d[5]),"+f"(d[6]),"+f"(d[7]),"+f"(d[8]),"+f"(d[9]),"+f"(d[10]),"+f"(d[11]),"+f"(d[12]),"+f"(d[13]),"+f"(d[14]),"+f"(d[15]),"+f"(d[16]),"+f"(d[17]),"+f"(d[18]),"+f"(d[19]),"+f"(d[20]),"+f"(d[21]),"+f"(d[22]),"+f"(d[23]),"+f"(d[24]),"+f"(d[25]),"+f"(d[26]),"+f"(d[27]),"+f"(d[28]),"+f"(d[29]),"+f"(d[30]),"+f"(d[31])
    :"l"(da),"l"(db),"r"(sc));
}

__device__ __forceinline__ float silu_bf(bf16 c) { const float x = __bfloat162float(c); return rbf(x / (1.f + __expf(-x))); }
__device__ __forceinline__ void fma8(float (&a)[8], float s, const uint4& v) {
  a[0] += s * blo(v.x); a[1] += s * bhi(v.x); a[2] += s * blo(v.y); a[3] += s * bhi(v.y);
  a[4] += s * blo(v.z); a[5] += s * bhi(v.z); a[6] += s * blo(v.w); a[7] += s * bhi(v.w);
}
__device__ __forceinline__ float red8(float (&a)[8], int lane) {
#pragma unroll
  for (int w = 4; w >= 1; w >>= 1) {
    const bool up = lane & (w * 4);
#pragma unroll
    for (int j = 0; j < w; j++) a[j] = (up ? a[j + w] : a[j]) + __shfl_xor_sync(~0u, up ? a[j] : a[j + w], w * 4);
  }
  return a[0];
}
__device__ __forceinline__ float mod_fin(float s, int n) { s = rbf(s); return ((n >> 9) == 1 || (n >> 9) == 4) ? rbf(1.f + s) : s; }
__device__ __forceinline__ void poll4(uint2& a, uint2& b, uint2& c, uint2& d, const uint32_t* p, const uint32_t* q) {
  asm volatile("{\n.reg .pred p;\n.reg .u32 n,t;\nmov.u32 n,0;\nLW:\nld.relaxed.gpu.global.v2.u32 {%0,%1},[%8];\nld.relaxed.gpu.global.v2.u32 {%2,%3},[%8+64];\n"
               "ld.relaxed.gpu.global.v2.u32 {%4,%5},[%9];\nld.relaxed.gpu.global.v2.u32 {%6,%7},[%9+2048];\n"
               "lop3.b32 t,%0,%1,%2,0x80;\nlop3.b32 t,t,%3,%4,0x80;\nlop3.b32 t,t,%5,%6,0x80;\nlop3.b32 t,t,%7,1,0x80;\n"
               "setp.ne.u32 p,t,0;\n@p bra LD;\nadd.u32 n,n,1;\nsetp.lt.u32 p,n,1048576;\n@p bra LW;\nLD:\n}\n"
               : "=&r"(a.x), "=&r"(a.y), "=&r"(b.x), "=&r"(b.y), "=&r"(c.x), "=&r"(c.y), "=&r"(d.x), "=&r"(d.y) : "l"(p), "l"(q) : "memory");
}

constexpr int LN_SMEM = 131072 + 4 * 24576 + 2048 + 256 + 512;
template <bool FFN>
__global__ void __cluster_dims__(2, 1, 1) __launch_bounds__(384, 1) k_lngemm(const __grid_constant__ CUtensorMap mX, const __grid_constant__ CUtensorMap mB0,
                                                   const __grid_constant__ CUtensorMap mB1, const bf16* __restrict__ cv, const bf16* __restrict__ wm, const bf16* __restrict__ xg) {
  extern __shared__ __align__(1024) uint8_t smem[];
  const uint32_t sA = smem_u32(smem), sB = sA + 131072, sM = sB + 4 * 24576, bars = sM + 2048;
  const uint32_t bA = bars, bF = bars + 64, bE = bars + 96;
  const int tid = threadIdx.x, warp = tid >> 5, lane = tid & 31;
  const int pr = blockIdx.x & 1, rb = FFN ? (blockIdx.x >> 4) * 2 + pr : blockIdx.x >> 3, ct = FFN ? (blockIdx.x >> 1) & 7 : blockIdx.x & 7;
  constexpr int NST = FFN ? 16 : 8, KS = FFN ? 2 : 4, BOX = FFN ? 4096 : 8192;
  TS(FFN ? 4 : 1, 0);
  pdl_launch();
  float* red = (float*)(smem + (bars - sA) + 256);
  if (tid == 256) {
    for (int i = 0; i < 8; i++) mbar_init(bA + 8 * i, 1);
    for (int i = 0; i < 4; i++) { mbar_init(bF + 8 * i, 1); mbar_init(bE + 8 * i, FFN ? 16 : 8); }
    fence_init();
  }
  __syncwarp();
  cluster_arrive();
  uint4 wv0, wv1, xv[4];
  bf16 cv0, cv1;
  if (!FFN && tid < 256) {
    wv0 = __ldg((const uint4*)(wm + tid * 3072 + blockIdx.x * 8)); wv1 = __ldg((const uint4*)(wm + (tid + 256) * 3072 + blockIdx.x * 8));
    cv0 = cv[tid]; cv1 = cv[tid + 256];
#pragma unroll
    for (int i = 0; i < 4; i++) xv[i] = __ldg((const uint4*)(xg + (blockIdx.x * 16 + (tid >> 4)) * 512 + i * 128 + (tid & 15) * 8));
  }
  cluster_wait();
  if (!FFN) TS(0, 2);
  if (warp >= 8) {
    asm volatile("setmaxnreg.dec.sync.aligned.u32 40;");
    if (tid == 256) {
      auto loadB = [&](int s) {
        const uint32_t d = sB + (s & 3) * 24576, b = bF + (s & 3) * 8;
        mbar_expect(b, 24576);
        for (int j = 0; j < 3; j++) {
          if (FFN) tma2d_mc(d + (pr * 3 + j) * BOX, pr ? &mB1 : &mB0, ct * 176 + j * 64, s * 32, b);
          else tma2d(d + j * BOX, &mB0, ct * 192 + j * 64, s * 64, b);
        }
      };
      for (int i = 0; i < 8; i++) mbar_expect(bA + 8 * i, 16384);
      for (int s = 0; s < 4; s++) {
        const int i = s * 2 + (ct & 1);
        if (!FFN) tma2d_mc(sA + i * 16384, &mX, i * 64, rb * 128, bA + 8 * i);
        loadB(s);
      }
      if (FFN) {
        pdl_wait();
        for (int i = 0; i < 8; i++) bulk_load(sA + i * 16384, g_x1 + (rb * 64 + i * 8) * 1024, 16384, bA + 8 * i);
      }
      for (int s = 4; s < NST; s++) { mbar_wait(bE + (s & 3) * 8, ((s >> 2) - 1) & 1); loadB(s); }
    }
  } else {
  asm volatile("setmaxnreg.inc.sync.aligned.u32 232;");
  const int g = lane >> 2, t = lane & 3;
  const int lr = warp * 16 + (lane & 7) + ((lane >> 3) & 1) * 8;
  auto aaddr = [&](int ks) -> uint32_t {
    if (FFN) return sA + (ks * 2 + (lane >> 4)) * 2048 + lr * 16;
    return sA + (ks >> 2) * 16384 + lr * 128 + ((((ks & 3) * 2 + (lane >> 4)) ^ (lr & 7)) << 4);
  };
  const int row0 = rb * 128 + warp * 16 + g;
  float2 msh, msc;
  uint2 sh, sc;
  float rs0, rs1, nm0, nm1;
  if (!FFN) {
    {
      float a[8] = {0, 0, 0, 0, 0, 0, 0, 0};
      fma8(a, silu_bf(cv0), wv0); fma8(a, silu_bf(cv1), wv1);
      if (a[0] != 123.f) TS(0, 3);
      const float s = qsum(red8(a, lane));
      if (t == 0) red[warp * 8 + g] = s;
      asm volatile("bar.sync 1,256;" ::: "memory");
      if (tid < 8) {
        float r = 0;
#pragma unroll
        for (int i = 0; i < 8; i++) r += red[i * 8 + tid];
        const int n = blockIdx.x * 8 + tid;
        asm volatile("st.relaxed.gpu.global.u32 [%0],%1;" ::"l"(g_modv + n), "r"(__float_as_uint(mod_fin(r, n)) | 1u) : "memory");
      }
      TS(0, 1);
    }
    {
      float v[32], s = 0, q = 0;
#pragma unroll
      for (int i = 0; i < 16; i++) { const uint32_t u = ((const uint32_t*)xv)[i]; v[2 * i] = blo(u); v[2 * i + 1] = bhi(u); s += v[2 * i] + v[2 * i + 1]; }
      s = qsum(s); s += __shfl_xor_sync(~0u, s, 4); s += __shfl_xor_sync(~0u, s, 8);
      const float m = s * (1.f / 512);
#pragma unroll
      for (int i = 0; i < 32; i++) q += (v[i] - m) * (v[i] - m);
      q = qsum(q); q += __shfl_xor_sync(~0u, q, 4); q += __shfl_xor_sync(~0u, q, 8);
      const float rs = rsqrtf(q * (1.f / 512) + 1e-5f);
      if ((tid & 15) == 0)
        asm volatile("st.relaxed.gpu.global.v2.u32 [%0],{%1,%2};" ::"l"(g_modv + 1024 + (blockIdx.x * 16 + (tid >> 4)) * 2), "r"(__float_as_uint(rs) | 1u), "r"(__float_as_uint(-m * rs) | 1u) : "memory");
    }
    TS(0, 4);
    uint2 p0, p1;
    poll4(p0, p1, sh, sc, g_modv + 1024 + row0 * 2, g_modv + tid * 2);
    rs0 = __uint_as_float(p0.x); nm0 = __uint_as_float(p0.y); rs1 = __uint_as_float(p1.x); nm1 = __uint_as_float(p1.y);
    TS(1, 1);
  } else {
    pdl_wait();
    TS(4, 1);
    msh = *(const float2*)(g_mod + 1536 + tid * 2); msc = *(const float2*)(g_mod + 2048 + tid * 2);
    const float4 p0 = *(const float4*)(g_st + row0 * 8 + t * 2), p1 = *(const float4*)(g_st + (row0 + 8) * 8 + t * 2);
    const float m0 = qsum(p0.x + p0.z) * 0.125f, m1 = qsum(p1.x + p1.z) * 0.125f;
    const float v0 = qsum(p0.y + p0.w + 64.f * ((p0.x - m0) * (p0.x - m0) + (p0.z - m0) * (p0.z - m0)));
    const float v1 = qsum(p1.y + p1.w + 64.f * ((p1.x - m1) * (p1.x - m1) + (p1.z - m1) * (p1.z - m1)));
    rs0 = rsqrtf(v0 * (1.f / 512) + 1e-5f); rs1 = rsqrtf(v1 * (1.f / 512) + 1e-5f);
    nm0 = -m0 * rs0; nm1 = -m1 * rs1;
  }
  {
    uint32_t* m = (uint32_t*)(smem + (sM - sA)) + (tid >> 3) * 16 + (tid & 3) * 4 + ((tid >> 2) & 1);
    if (FFN) { m[0] = pack_rn(msc.x, msc.y); m[2] = pack_rn(msh.x, msh.y); }
    else { m[0] = __byte_perm(sc.x, sc.y, 0x7632); m[2] = __byte_perm(sh.x, sh.y, 0x7632); }
    asm volatile("bar.sync 1,256;" ::: "memory");
  }
  constexpr int NA = FFN ? 88 : 96;
  float acc0[NA], acc1[FFN ? 88 : 1];
  uint32_t a[2][KS][4];
  auto prep = [&](int ks, uint32_t(&o)[4]) {
    if ((ks & 3) == 0) mbar_wait(bA + 2 * ks, 0);
    uint32_t r[4]; ldsm4(aaddr(ks), r);
    const uint4 m = *(const uint4*)(smem + (sM - sA) + ks * 64 + t * 16);
#pragma unroll
    for (int i = 0; i < 4; i++) {
      const float rs = (i & 1) ? rs1 : rs0, nm = (i & 1) ? nm1 : nm0;
      const uint32_t n = pack_rn(fmaf(blo(r[i]), rs, nm), fmaf(bhi(r[i]), rs, nm));
      asm("fma.rn.bf16x2 %0,%1,%2,%3;" : "=r"(o[i]) : "r"(n), "r"(i < 2 ? m.x : m.y), "r"(i < 2 ? m.z : m.w));
    }
  };
  auto stage = [&](int s, uint32_t(&c)[KS][4], uint32_t(&n)[KS][4]) {
    mbar_wait(bF + (s & 3) * 8, (s >> 2) & 1);
    const uint64_t db = mk_desc(sB + (s & 3) * 24576, BOX, 1024, 1);
    wg_fence();
#pragma unroll
    for (int k = 0; k < KS; k++) {
      if constexpr (FFN) {
        wgmma_rs_n176_t1(acc0, c[k][0], c[k][1], c[k][2], c[k][3], db + k * 128, s + k);
        wgmma_rs_n176_t1(acc1, c[k][0], c[k][1], c[k][2], c[k][3], db + k * 128 + 3 * BOX / 16, s + k);
      } else {
        wgmma_rs_n192_t1(acc0, c[k][0], c[k][1], c[k][2], c[k][3], db + k * 128, s + k);
      }
    }
    wg_commit();
    wg_wait<1>();
    if (s > 0 && s <= NST - 4) {
      if (!FFN) { if (lane == 0) mbar_arrive(bE + ((s - 1) & 3) * 8); }
      else if (lane < 2) asm volatile("{\n.reg .b32 r;\nmapa.shared::cluster.u32 r,%0,%1;\nmbarrier.arrive.relaxed.cluster.shared::cluster.b64 _,[r];\n}" ::"r"(bE + ((s - 1) & 3) * 8), "r"(lane) : "memory");
    }
    if (s < NST - 1) {
#pragma unroll
      for (int k = 0; k < KS; k++) prep((s + 1) * KS + k, n[k]);
    }
  };
#pragma unroll
  for (int k = 0; k < KS; k++) prep(k, a[0][k]);
  TS(FFN ? 4 : 1, 2);
#pragma unroll 1
  for (int s = 0; s < NST; s += 2) { stage(s, a[0], a[1]); stage(s + 1, a[1], a[0]); }
  wg_wait<0>();
  reg_fence(acc0);
  TS(FFN ? 4 : 1, 3);
  if constexpr (FFN) {
    reg_fence(acc1);
    uint32_t* o = (uint32_t*)g_h + ((rb * 172 + ct * 22) * 128 + warp * 16 + g) * 4 + t;
#pragma unroll
    for (int j = 0; j < 22; j++) {
      if (ct * 22 + j < 172) {
        float h[4], d[4];
#pragma unroll
        for (int i = 0; i < 4; i++) { const float x = acc0[4 * j + i]; d[i] = 1.f + ex2(fminf(-1.4426950408889634f * x, 30.f)); h[i] = x * acc1[4 * j + i]; }
        const float d01 = d[0] * d[1], d23 = d[2] * d[3];
        float r; asm("rcp.approx.ftz.f32 %0,%1;" : "=f"(r) : "f"(d01 * d23));
        const float r01 = r * d23, r23 = r * d01;
        h[0] *= r01 * d[1]; h[1] *= r01 * d[0]; h[2] *= r23 * d[3]; h[3] *= r23 * d[2];
        o[j * 512] = pack_rn(h[0], h[1]);
        o[j * 512 + 32] = pack_rn(h[2], h[3]);
      }
    }
  } else {
    uint32_t* o = (uint32_t*)g_qkv + (ct * 24 * 2048 + row0) * 4 + t;
#pragma unroll
    for (int j = 0; j < 24; j += 2) {
      const int G = ct * 24 + j;
      const float sc = G < 64 ? 0.25f * 1.4426950408889634f : 1.f;
      uint32_t p[4];
#pragma unroll
      for (int i = 0; i < 4; i++) p[i] = pack_rn(acc0[4 * j + 2 * i] * sc, acc0[4 * j + 2 * i + 1] * sc);
      o[j * 8192] = p[0]; o[j * 8192 + 32] = p[1]; o[(j + 1) * 8192] = p[2]; o[(j + 1) * 8192 + 32] = p[3];
      if (G >= 64 && G < 128) {
        float n0 = blo(p[0]) * blo(p[0]) + bhi(p[0]) * bhi(p[0]) + blo(p[2]) * blo(p[2]) + bhi(p[2]) * bhi(p[2]);
        float n1 = blo(p[1]) * blo(p[1]) + bhi(p[1]) * bhi(p[1]) + blo(p[3]) * blo(p[3]) + bhi(p[3]) * bhi(p[3]);
        n0 = qsum(n0); n1 = qsum(n1);
        const uint32_t mx = __reduce_max_sync(~0u, max(__float_as_uint(n0), __float_as_uint(n1)));
        if (lane == 0) g_kmax[((G - 64) >> 1) * 128 + rb * 8 + warp] = __uint_as_float(mx);
      }
    }
  }
  TS(FFN ? 4 : 1, 4);
}
}

#define SMASK 0xAAu
#define BRK 0
#define PACK 1
#define PP 1
constexpr int AT_SMEM = 5 * 32768 + 256;
__device__ __forceinline__ uint32_t exp2_pair_fma(float s0, float s1, float c, uint32_t ka, uint32_t kz) {
  uint32_t r;
  asm volatile("{\n.reg .b32 y0,y1,e,u,t;\n"
      "fma.rn.sat.f32 y0,%1,0f00000080,%3;\nfma.rn.sat.f32 y1,%2,0f00000080,%3;\n"
      "mad.lo.u32 e,y1,65536,y0;\n"
      "and.b32 u,e,0x007F007F;\n"
      "fma.rn.f16x2 u,u,%4,%5;\nfma.rn.f16x2 t,u,u,%6;\nfma.rn.f16x2 t,t,u,%7;\n"
      "lop3.b32 %0,t,0x007F007F,e,0xE2;\n}\n"
      : "=r"(r) : "f"(s0), "f"(s1), "f"(c), "r"(ka), "r"(0x36B236B2u), "r"(0x3C733C73u), "r"(0x47764776u), "r"(kz));
  return r;
}
__device__ __forceinline__ void attn_pass(float (&oa)[12], float (&ob)[12], const uint32_t (&q)[4], float m0, float m1, uint32_t sK, uint32_t bars, bool first, uint32_t kz) {
  const uint64_t dk = mk_desc(sK, 32768, 128, 0), dv = mk_desc(sK + 65536, 128, 32768, 0);
  const float c0 = (127.f - m0) * __uint_as_float(0x80u), c1 = (127.f - m1) * __uint_as_float(0x80u);
  const uint32_t ka = 0x7ACE7ACEu + kz;
  constexpr int NK = 64, NS = 32, NP = 16, NI = 32;
  auto qk = [&](float (&s)[NS], int i) { wgmma_rs_n64_t0(s, q[0], q[1], q[2], q[3], dk + i * NK, 0); };
  auto softmax = [&](float (&s)[NS], uint32_t (&p)[NP], uint32_t mask) {
    reg_fence(s);
    float e0, e1;
    int pend = -1;
#pragma unroll
    for (int t = 0; t < NP; t++) {
      const int j = (t & 3) * 4 + (t >> 2);
      if ((mask >> (t & 3)) & 1) {
        p[j] = exp2_pair_fma(s[2 * j], s[2 * j + 1], (j & 1) ? c1 : c0, ka, kz);
      } else {
        float f0, f1;
        asm volatile("ex2.approx.ftz.f32 %0,%2;\nex2.approx.ftz.f32 %1,%3;" : "=&f"(f0), "=f"(f1) : "f"(s[2 * j]), "f"(s[2 * j + 1]));
        if (pend >= 0) asm volatile("cvt.rn.bf16x2.f32 %0,%1,%2;" : "=r"(p[pend]) : "f"(e1), "f"(e0));
        e0 = f0; e1 = f1; pend = j;
      }
    }
    if (pend >= 0) asm volatile("cvt.rn.bf16x2.f32 %0,%1,%2;" : "=r"(p[pend]) : "f"(e1), "f"(e0));
#pragma unroll
    for (int j = 0; j < NP; j++) asm volatile("" : "+r"(p[j])::"memory");
  };
  auto pv = [&](uint32_t (&p)[NP], int i, uint32_t mask) {
#pragma unroll
    for (int k = 0; k < 4; k++) wgmma_rs_n24_t1(((mask >> k) & 1) ? ob : oa, p[4 * k], p[4 * k + 1], p[4 * k + 2], p[4 * k + 3], dv + i * NK + k * 16, 1);
  };
  auto ld = [&](int i) { if (first && (i & 3) == 0) mbar_wait(bars + i * 2, 0); };
  constexpr uint32_t M0 = SMASK & 15, M1 = SMASK >> 4;
  zero(oa); zero(ob);
  ld(0);
  if (first) TS(2, 2);
  float s[NS];
  zero(s);
  uint32_t p0[NP], p1[NP];
  wg_fence(); qk(s, 0); wg_commit(); wg_wait<0>(); softmax(s, p0, M0);
#pragma unroll 1
  for (int i = 0; i < NI - 2; i += 2) {
    wg_fence(); qk(s, i + 1); wg_commit(); pv(p0, i, M0); wg_commit(); wg_wait<1>(); softmax(s, p1, M1); wg_wait<0>();
    ld(i + 2);
    wg_fence(); qk(s, i + 2); wg_commit(); pv(p1, i + 1, M1); wg_commit(); wg_wait<1>(); softmax(s, p0, M0); wg_wait<0>();
  }
  wg_fence(); qk(s, NI - 1); wg_commit(); pv(p0, NI - 2, M0); wg_commit(); wg_wait<1>(); softmax(s, p1, M1); wg_wait<0>();
  wg_fence(); pv(p1, NI - 1, M1); wg_commit();
  wg_wait<0>();
  reg_fence(oa); reg_fence(ob);
}
__device__ __forceinline__ void mma16816(float (&d)[4], const uint32_t (&a)[4], uint32_t b0, uint32_t b1) {
  asm("mma.sync.aligned.m16n8k16.row.col.f32.bf16.bf16.f32 {%0,%1,%2,%3},{%4,%5,%6,%7},{%8,%9},{%0,%1,%2,%3};"
      : "+f"(d[0]), "+f"(d[1]), "+f"(d[2]), "+f"(d[3]) : "r"(a[0]), "r"(a[1]), "r"(a[2]), "r"(a[3]), "r"(b0), "r"(b1));
}
__device__ __forceinline__ void attn_safe(float (&o)[12], const uint32_t (&q)[4], uint32_t sK) {
  const int lane = threadIdx.x & 31;
  const uint32_t ka = sK + (lane >> 4) * 32768 + (lane & 15) * 16;
  float m0 = -INFINITY, m1 = -INFINITY;
#pragma unroll 2
  for (int i = 0; i < 128; i++) {
    uint32_t k[4]; ldsm4(ka + i * 256, k);
    float s0[4] = {0, 0, 0, 0}, s1[4] = {0, 0, 0, 0};
    mma16816(s0, q, k[0], k[2]); mma16816(s1, q, k[1], k[3]);
    m0 = fmaxf(fmaxf(m0, fmaxf(s0[0], s0[1])), fmaxf(s1[0], s1[1])); m1 = fmaxf(fmaxf(m1, fmaxf(s0[2], s0[3])), fmaxf(s1[2], s1[3]));
  }
  m0 = fmaxf(m0, __shfl_xor_sync(~0u, m0, 1)); m0 = fmaxf(m0, __shfl_xor_sync(~0u, m0, 2));
  m1 = fmaxf(m1, __shfl_xor_sync(~0u, m1, 1)); m1 = fmaxf(m1, __shfl_xor_sync(~0u, m1, 2));
  float o0[4] = {0, 0, 0, 0}, o1[4] = {0, 0, 0, 0}, o2[4] = {0, 0, 0, 0};
#pragma unroll 2
  for (int i = 0; i < 128; i++) {
    uint32_t k[4], v[4]; ldsm4(ka + i * 256, k);
    asm volatile("ldmatrix.sync.aligned.m8n8.x4.trans.shared.b16 {%0,%1,%2,%3},[%4];" : "=r"(v[0]), "=r"(v[1]), "=r"(v[2]), "=r"(v[3]) : "r"(ka + 65536 + i * 256) : "memory");
    float s0[4] = {0, 0, 0, 0}, s1[4] = {0, 0, 0, 0};
    mma16816(s0, q, k[0], k[2]); mma16816(s1, q, k[1], k[3]);
    const uint32_t p[4] = {pack_rn(ex2(s0[0] - m0), ex2(s0[1] - m0)), pack_rn(ex2(s0[2] - m1), ex2(s0[3] - m1)),
                           pack_rn(ex2(s1[0] - m0), ex2(s1[1] - m0)), pack_rn(ex2(s1[2] - m1), ex2(s1[3] - m1))};
    mma16816(o0, p, v[0], v[1]); mma16816(o1, p, v[2], v[3]); mma16816(o2, p, 0x3F803F80u, 0x3F803F80u);
  }
#pragma unroll
  for (int i = 0; i < 4; i++) { o[i] = o0[i]; o[4 + i] = o1[i]; o[8 + i] = o2[i]; }
}
__global__ void __cluster_dims__(2, 1, 1) __launch_bounds__(512, 1) k_attn(const bf16* wo, const bf16* w1, const bf16* w3, const bf16* w2, const bf16* __restrict__ cv, const bf16* __restrict__ wm, uint32_t kz) {
  extern __shared__ __align__(1024) uint8_t smem[];
  const uint32_t sK = smem_u32(smem), bars = sK + 5 * 32768;
  const int tid = threadIdx.x, warp = tid >> 5, lane = tid & 31, g = lane >> 2, t = lane & 3;
  pdl_launch();
  if (blockIdx.x < 4) {
    float* cs = (float*)smem;
    cs[tid] = silu_bf(cv[tid]);
    __syncthreads();
    const int n0 = 1024 + blockIdx.x * 512, r0 = (tid >> 6) * 64;
    float a[8] = {0, 0, 0, 0, 0, 0, 0, 0};
#pragma unroll 16
    for (int r = r0; r < r0 + 64; r++) fma8(a, cs[r], __ldg((const uint4*)(wm + r * 3072 + n0 + (tid & 63) * 8)));
    float4* rp = (float4*)(cs + 512 + tid * 8);
    rp[0] = make_float4(a[0], a[1], a[2], a[3]); rp[1] = make_float4(a[4], a[5], a[6], a[7]);
    __syncthreads();
    float s = 0;
#pragma unroll
    for (int i = 0; i < 8; i++) s += cs[512 + i * 512 + tid];
    g_mod[n0 + tid] = mod_fin(s, n0 + tid);
    return;
  }
  const int bid = blockIdx.x - 4, h = bid >> 2, qb = bid & 3;
  TS(2, 0);
  if (tid == 0) { for (int i = 0; i < 8; i++) { mbar_init(bars + 8 * i, 1); mbar_expect(bars + 8 * i, 16384); } fence_init(); }
#pragma unroll
  for (int i = 0; i < 4; i++) *(uint4*)(smem + 131072 + i * 8192 + tid * 16) = make_uint4(0x3F803F80u, 0x3F803F80u, 0x3F803F80u, 0x3F803F80u);
  fence_async();
  cluster_sync();
  pdl_wait();
  TS(2, 1);
  if (tid >= 472) g_modv[bid * 40 + tid - 472] = 0;
  const uint4 km4 = *(const uint4*)(g_kmax + h * 128 + lane * 4);
  const uint32_t* qp = (const uint32_t*)g_qkv + (h * 2 * 2048 + qb * 512 + warp * 16 + g) * 4 + t;
  uint32_t q[4] = {qp[0], qp[32], qp[8192], qp[8192 + 32]};
  auto ldkv = [&]() {
    const int c = warp >> 1, pl = (qb & 1) + (warp & 1) * 2;
    bulk_load_mc(sK + pl * 32768 + c * 4096, g_qkv + ((64 + (pl >> 1) * 64 + h * 2 + (pl & 1)) * 2048 + c * 256) * 8, 4096, bars + 8 * c);
  };
  if (lane == 0 && warp < 4) ldkv();
  const uint32_t qn[4] = {qp[1024], qp[1024 + 32], qp[1024 + 8192], qp[1024 + 8192 + 32]};
  const float kmax = __uint_as_float(__reduce_max_sync(~0u, max(max(km4.x, km4.y), max(km4.z, km4.w))));
  if (lane == 0 && warp >= 4 && kmax != -1.f) ldkv();
#pragma unroll 1
  for (int tile = 0; tile < 2; tile++) {
    const int row = qb * 512 + tile * 256 + warp * 16 + g;
    const float n0 = qsum(blo(q[0]) * blo(q[0]) + bhi(q[0]) * bhi(q[0]) + blo(q[2]) * blo(q[2]) + bhi(q[2]) * bhi(q[2]));
    const float n1 = qsum(blo(q[1]) * blo(q[1]) + bhi(q[1]) * bhi(q[1]) + blo(q[3]) * blo(q[3]) + bhi(q[3]) * bhi(q[3]));
    const float b0 = sqrtf(n0 * kmax) * 1.001f, b1 = sqrtf(n1 * kmax) * 1.001f;
    const float m0 = fmaxf(ceilf(b0 - 100.f), 0.f), m1 = fmaxf(ceilf(b1 - 100.f), 0.f);
    float o[12], ob[12];
    attn_pass(o, ob, q, m0, m1, sK, bars, tile == 0, kz);
    const float f0 = ex2(-m0), f1 = ex2(-m1);
#pragma unroll
    for (int i = 0; i < 12; i++) o[i] = fmaf(o[i], (i & 2) ? f1 : f0, ob[i]);
    bool ok = b0 < 220.f && b1 < 220.f && o[8] >= 0x1p-90f && o[10] >= 0x1p-90f;
#pragma unroll
    for (int i = 0; i < 12; i++) ok = ok && fabsf(o[i]) < INFINITY;
    if (!__all_sync(~0u, ok)) attn_safe(o, q, sK);
    const float r0 = 1.f / o[8], r1 = 1.f / o[10];
    uint32_t* op = (uint32_t*)g_o + (((row >> 7) * 64 + h * 2) * 128 + (row & 127)) * 4 + t;
    op[0] = pack_rn(o[0] * r0, o[1] * r0); op[32] = pack_rn(o[2] * r1, o[3] * r1);
    op[512] = pack_rn(o[4] * r0, o[5] * r0); op[512 + 32] = pack_rn(o[6] * r1, o[7] * r1);
    if (tile == 0 && tid == 32) {
      l2_prefetch((const char*)wo + bid * 4096, 4096);
      l2_prefetch((const char*)w1 + bid * 11008, 11008);
      l2_prefetch((const char*)w3 + bid * 11008, 11008);
      l2_prefetch((const char*)w2 + bid * 11008, 11008);
    }
#pragma unroll
    for (int i = 0; i < 4; i++) q[i] = qn[i];
    TS(2, 3 + tile);
  }
}

constexpr int WO_SMEM = 131072 + 65536 + 256;
__global__ void __cluster_dims__(2, 1, 1) __launch_bounds__(256, 1) k_wo(const __grid_constant__ CUtensorMap mW, const bf16* __restrict__ x) {
  extern __shared__ __align__(1024) uint8_t smem[];
  const uint32_t sA = smem_u32(smem), sB = sA + 131072, bars = sB + 65536;
  const int tid = threadIdx.x, warp = tid >> 5, lane = tid & 31, g = lane >> 2, t = lane & 3;
  const int rb = blockIdx.x >> 3, ct = blockIdx.x & 7;
  TS(3, 0);
  pdl_launch();
  if (tid == 0) {
    for (int i = 0; i < 8; i++) mbar_init(bars + 8 * i, 1);
    fence_init();
    for (int i = 0; i < 8; i++) { mbar_expect(bars + 8 * i, 24576); tma2d(sB + i * 8192, &mW, ct * 64, i * 64, bars + 8 * i); }
  }
  __syncwarp();
  cluster_arrive();
  const int lrow = warp * 16 + g;
  uint32_t xr[16];
  const uint32_t* xp = (const uint32_t*)(x + (rb * 128 + lrow) * 512 + ct * 64) + t;
#pragma unroll
  for (int j = 0; j < 8; j++) { xr[2 * j] = __ldg(xp + j * 4); xr[2 * j + 1] = __ldg(xp + j * 4 + 8 * 256); }
  cluster_wait();
  pdl_wait();
  if (tid == 0) {
    for (int i = ct & 1; i < 8; i += 2) bulk_load_mc(sA + i * 16384, g_o + (rb * 64 + i * 8) * 1024, 16384, bars + 8 * i);
  }
  TS(3, 1);
  float2 ga[8];
#pragma unroll
  for (int j = 0; j < 8; j++) ga[j] = *(const float2*)(g_mod + 1024 + ct * 64 + j * 8 + t * 2);
  float acc[32];
  const uint64_t da = mk_desc(sA + (warp >> 2) * 1024, 2048, 128, 0), db = mk_desc(sB, 8192, 1024, 1);
#pragma unroll
  for (int c = 0; c < 8; c++) {
    mbar_wait(bars + 8 * c, 0);
    if (c == 0) TS(3, 2);
    wg_fence();
#pragma unroll
    for (int k = 0; k < 4; k++) wgmma_ss_n64_t1(acc, da + (c * 4 + k) * 256, db + (c * 4 + k) * 128, c + k);
    wg_commit();
  }
  wg_wait<0>();
  reg_fence(acc);
  TS(3, 3);
  uint32_t* o = (uint32_t*)g_x1 + ((rb * 64 + ct * 8) * 128 + lrow) * 4 + t;
  float s0 = 0, s1 = 0;
#pragma unroll
  for (int j = 0; j < 8; j++) {
    xr[2 * j] = pack_rn(fmaf(ga[j].x, acc[4 * j], blo(xr[2 * j])), fmaf(ga[j].y, acc[4 * j + 1], bhi(xr[2 * j])));
    xr[2 * j + 1] = pack_rn(fmaf(ga[j].x, acc[4 * j + 2], blo(xr[2 * j + 1])), fmaf(ga[j].y, acc[4 * j + 3], bhi(xr[2 * j + 1])));
    o[j * 512] = xr[2 * j]; o[j * 512 + 32] = xr[2 * j + 1];
    s0 += blo(xr[2 * j]) + bhi(xr[2 * j]); s1 += blo(xr[2 * j + 1]) + bhi(xr[2 * j + 1]);
  }
  const float m0 = qsum(s0) * (1.f / 64), m1 = qsum(s1) * (1.f / 64);
  float v0 = 0, v1 = 0;
#pragma unroll
  for (int j = 0; j < 8; j++) {
    float d;
    d = blo(xr[2 * j]) - m0; v0 += d * d; d = bhi(xr[2 * j]) - m0; v0 += d * d;
    d = blo(xr[2 * j + 1]) - m1; v1 += d * d; d = bhi(xr[2 * j + 1]) - m1; v1 += d * d;
  }
  v0 = qsum(v0); v1 = qsum(v1);
  if (t == 0) g_st[(rb * 128 + lrow) * 8 + ct] = make_float2(m0, v0);
  if (t == 1) g_st[(rb * 128 + lrow + 8) * 8 + ct] = make_float2(m1, v1);
  TS(3, 4);
}

constexpr int W2_SMEM = 6 * 32768 + 32768 + 256;
__global__ void __cluster_dims__(2, 1, 1) __launch_bounds__(288, 1) k_w2(const __grid_constant__ CUtensorMap mW, bf16* __restrict__ out) {
  extern __shared__ __align__(1024) uint8_t smem[];
  const uint32_t sR = smem_u32(smem), sX = sR + 6 * 32768, bF = sX + 32768, bE = bF + 48, bX = bF + 96;
  const int tid = threadIdx.x, warp = tid >> 5, lane = tid & 31, g = lane >> 2, t = lane & 3;
  const int kh = blockIdx.x & 1, ct = (blockIdx.x >> 1) & 3, rb = blockIdx.x >> 3;
  TS(5, 0);
  pdl_launch();
  if (tid == 256) {
    for (int i = 0; i < 6; i++) { mbar_init(bF + 8 * i, 1); mbar_init(bE + 8 * i, 8); }
    for (int i = 0; i < 8; i++) { mbar_init(bX + 8 * i, 1); mbar_expect(bX + 8 * i, 4096); }
    fence_init();
  }
  __syncthreads();
  asm volatile("barrier.cluster.arrive.relaxed.aligned;" ::: "memory");
  if (warp == 8) {
    if (lane == 0) {
      auto abytes = [&](int s) { return (kh == 1 && s == 10) ? 8192 : 16384; };
      auto loadB = [&](int s) {
        const int st = s % 6;
        mbar_expect(bF + 8 * st, 16384 + abytes(s));
        for (int j = 0; j < 2; j++) tma2d(sR + st * 32768 + 16384 + j * 8192, &mW, ct * 128 + j * 64, kh * 704 + s * 64, bF + 8 * st);
      };
      auto loadA = [&](int s) { bulk_load(sR + (s % 6) * 32768, g_h + (rb * 172 + kh * 88 + s * 8) * 1024, abytes(s), bF + 8 * (s % 6)); };
      for (int s = 0; s < 6; s++) loadB(s);
      pdl_wait();
      for (int s = 0; s < 6; s++) loadA(s);
      for (int s = 6; s < 11; s++) { mbar_wait(bE + 8 * (s - 6), 0); loadB(s); loadA(s); }
    }
    __syncwarp();
    cluster_wait();
    return;
  }
  pdl_wait();
  TS(5, 1);
  const int lrow = warp * 16 + g;
  uint32_t xr[16];
  float2 gb[8];
  const uint32_t* xp = (const uint32_t*)g_x1 + ((rb * 64 + ct * 16 + kh * 8) * 128 + lrow) * 4 + t;
#pragma unroll
  for (int j = 0; j < 8; j++) {
    xr[2 * j] = xp[j * 512]; xr[2 * j + 1] = xp[j * 512 + 32];
    gb[j] = *(const float2*)(g_mod + 2560 + ct * 128 + kh * 64 + j * 8 + t * 2);
  }
  float acc[64];
#pragma unroll 1
  for (int s = 0; s < 11; s++) {
    const int st = s % 6;
    mbar_wait(bF + 8 * st, s >= 6);
    const uint64_t da = mk_desc(sR + st * 32768 + (warp >> 2) * 1024, 2048, 128, 0), db = mk_desc(sR + st * 32768 + 16384, 8192, 1024, 1);
    if (s == 0) TS(5, 2);
    wg_fence();
    wgmma_ss_n128_t1(acc, da, db, s);
    wgmma_ss_n128_t1(acc, da + 256, db + 128, 1);
    wgmma_ss_n128_t1(acc, da + 512, db + 256, 1);
    wgmma_ss_n128_t1(acc, da + 768, db + 384, 1);
    wg_commit();
    wg_wait<1>();
    if (s > 0 && s < 6 && lane == 0) mbar_arrive(bE + 8 * (s - 1));
  }
  wg_wait<0>();
  reg_fence(acc);
  TS(5, 3);
  asm volatile("barrier.cluster.wait.aligned;" ::: "memory");
  uint32_t rem, rbar;
  asm("mapa.shared::cluster.u32 %0,%1,%2;" : "=r"(rbar) : "r"(bX + warp * 8), "r"(kh ^ 1));
  asm("mapa.shared::cluster.u32 %0,%1,%2;" : "=r"(rem) : "r"(sX + warp * 4096 + lane * 16), "r"(kh ^ 1));
#pragma unroll
  for (int j = 0; j < 8; j++) {
    float v[4];
#pragma unroll
    for (int i = 0; i < 4; i++) { v[i] = kh ? acc[4 * j + i] : acc[32 + 4 * j + i]; acc[4 * j + i] = kh ? acc[32 + 4 * j + i] : acc[4 * j + i]; }
    asm volatile("st.async.weak.shared::cluster.mbarrier::complete_tx::bytes.v4.f32 [%0],{%1,%2,%3,%4},[%5];" ::"r"(rem + j * 512), "f"(v[0]), "f"(v[1]), "f"(v[2]), "f"(v[3]), "r"(rbar) : "memory");
  }
  mbar_wait(bX + warp * 8, 0);
  TS(5, 5);
  const uint32_t sw = sX + warp * 4096;
#pragma unroll
  for (int j = 0; j < 8; j++) {
    const float4 p = *(const float4*)(smem + 6 * 32768 + warp * 4096 + j * 512 + lane * 16);
    xr[2 * j] = pack_rn(fmaf(gb[j].x, acc[4 * j] + p.x, blo(xr[2 * j])), fmaf(gb[j].y, acc[4 * j + 1] + p.y, bhi(xr[2 * j])));
    xr[2 * j + 1] = pack_rn(fmaf(gb[j].x, acc[4 * j + 2] + p.z, blo(xr[2 * j + 1])), fmaf(gb[j].y, acc[4 * j + 3] + p.w, bhi(xr[2 * j + 1])));
  }
  __syncwarp();
#pragma unroll
  for (int j = 1; j < 8; j += 2) {
    asm volatile("stmatrix.sync.aligned.m8n8.x4.shared.b16 [%0],{%1,%2,%3,%4};" ::"r"(sw + (lane & 15) * 128 + (((j - 1 + (lane >> 4)) ^ (lane & 7)) << 4)),
                            "r"(xr[2 * j - 2]), "r"(xr[2 * j - 1]), "r"(xr[2 * j]), "r"(xr[2 * j + 1]) : "memory");
  }
  __syncwarp();
#pragma unroll
  for (int i = 0; i < 4; i++) {
    const int r = i * 4 + (lane >> 3);
    *(uint4*)(out + (rb * 128 + warp * 16 + r) * 512 + ct * 128 + kh * 64 + (lane & 7) * 8) = *(const uint4*)(smem + 6 * 32768 + warp * 4096 + r * 128 + (((lane ^ r) & 7) << 4));
  }
  TS(5, 4);
}

typedef CUresult (*EncFn)(CUtensorMap*, CUtensorMapDataType, cuuint32_t, void*, const cuuint64_t*, const cuuint64_t*, const cuuint32_t*,
                          const cuuint32_t*, CUtensorMapInterleave, CUtensorMapSwizzle, CUtensorMapL2promotion, CUtensorMapFloatOOBfill);
static void mk_map(EncFn f, CUtensorMap* m, const void* p, int rows, int cols, int box_rows) {
  cuuint64_t dim[2] = {(cuuint64_t)cols, (cuuint64_t)rows}, str[1] = {(cuuint64_t)cols * 2};
  cuuint32_t box[2] = {64, (cuuint32_t)box_rows}, es[2] = {1, 1};
  f(m, CU_TENSOR_MAP_DATA_TYPE_BFLOAT16, 2, (void*)p, dim, str, box, es, CU_TENSOR_MAP_INTERLEAVE_NONE, CU_TENSOR_MAP_SWIZZLE_128B,
    CU_TENSOR_MAP_L2_PROMOTION_L2_128B, CU_TENSOR_MAP_FLOAT_OOB_FILL_NONE);
}
template <typename... KA, typename... A>
static void launch(void (*k)(KA...), int grid, int block, int smem, bool pdl, A... args) {
  cudaLaunchConfig_t cfg = {};
  cfg.gridDim = dim3(grid); cfg.blockDim = dim3(block); cfg.dynamicSmemBytes = smem; cfg.stream = cudaStreamPerThread;
  cudaLaunchAttribute at[1];
  at[0].id = cudaLaunchAttributeProgrammaticStreamSerialization; at[0].val.programmaticStreamSerializationAllowed = 1;
  cfg.attrs = at; cfg.numAttrs = pdl ? 1 : 0;
  cudaLaunchKernelEx(&cfg, k, args...);
}
extern "C" void kernel_launch(void* const* d_in, const int* in_sizes, int n_in, void* d_out, int out_size) {
  const bf16 *x = (const bf16*)d_in[0], *wqkv = (const bf16*)d_in[1], *wo = (const bf16*)d_in[2], *w1 = (const bf16*)d_in[4],
             *w3 = (const bf16*)d_in[5], *w2 = (const bf16*)d_in[6], *c = (const bf16*)d_in[7], *wmod = (const bf16*)d_in[8];
  void* fp = nullptr;
  cudaDriverEntryPointQueryResult qr;
  cudaGetDriverEntryPoint("cuTensorMapEncodeTiled", &fp, cudaEnableDefault, &qr);
  EncFn f = (EncFn)fp;
  CUtensorMap mX, mQ, mO, m1, m3, m2;
  mk_map(f, &mX, x, S_, D_, 128); mk_map(f, &mQ, wqkv, D_, 3 * D_, 64); mk_map(f, &mO, wo, D_, D_, 64);
  mk_map(f, &m1, w1, D_, F_, 32); mk_map(f, &m3, w3, D_, F_, 32); mk_map(f, &m2, w2, F_, D_, 64);
  cudaFuncSetAttribute(k_lngemm<false>, cudaFuncAttributeMaxDynamicSharedMemorySize, LN_SMEM);
  cudaFuncSetAttribute(k_lngemm<true>, cudaFuncAttributeMaxDynamicSharedMemorySize, LN_SMEM);
  cudaFuncSetAttribute(k_attn, cudaFuncAttributeMaxDynamicSharedMemorySize, AT_SMEM);
  cudaFuncSetAttribute(k_wo, cudaFuncAttributeMaxDynamicSharedMemorySize, WO_SMEM);
  cudaFuncSetAttribute(k_w2, cudaFuncAttributeMaxDynamicSharedMemorySize, W2_SMEM);
  launch(k_lngemm<false>, 128, 384, LN_SMEM, false, mX, mQ, mQ, c, wmod, x);
  launch(k_attn, 132, 512, AT_SMEM, true, wo, w1, w3, w2, c, wmod, 0u);
  launch(k_wo, 128, 256, WO_SMEM, true, mO, x);
  launch(k_lngemm<true>, 128, 384, LN_SMEM, true, mX, m1, m3, c, wmod, x);
  launch(k_w2, 128, 288, W2_SMEM, true, m2, (bf16*)d_out);
}
```

```cpp
#include <cuda_runtime.h>
#include <cuda_bf16.h>
#include <cuda.h>
#include <stdint.h>
typedef __nv_bfloat16 bf16;
constexpr int S_ = 2048, D_ = 512, F_ = 1376;
__device__ __align__(1024) float g_mod[3072];
__device__ __align__(1024) uint32_t g_modv[1024 + 4096];
__device__ __align__(1024) bf16 g_qkv[192 * 2048 * 8];
__device__ __align__(1024) float g_kmax[32 * 128];
__device__ __align__(1024) bf16 g_o[16 * 64 * 128 * 8];
__device__ __align__(1024) bf16 g_x1[16 * 64 * 128 * 8];
__device__ __align__(1024) float2 g_st[2048 * 8];
__device__ __align__(1024) bf16 g_h[16 * 172 * 128 * 8];

__device__ __forceinline__ uint32_t smem_u32(const void* p) { return (uint32_t)__cvta_generic_to_shared(p); }
__device__ __forceinline__ void mbar_init(uint32_t b, int n) { asm volatile("mbarrier.init.shared::cta.b64 [%0],%1;" ::"r"(b), "r"(n) : "memory"); }
__device__ __forceinline__ void mbar_expect(uint32_t b, int bytes) { asm volatile("mbarrier.arrive.expect_tx.shared::cta.b64 _,[%0],%1;" ::"r"(b), "r"(bytes) : "memory"); }
__device__ __forceinline__ void mbar_arrive(uint32_t b) { asm volatile("mbarrier.arrive.shared::cta.b64 _,[%0];" ::"r"(b) : "memory"); }
__device__ __forceinline__ void mbar_wait(uint32_t b, int parity) {
  asm volatile("{\n.reg .pred p;\n.reg .u32 n;\nmov.u32 n,0;\nLW:\nmbarrier.try_wait.parity.shared::cta.b64 p,[%0],%1;\n@p bra LD;\n"
               "add.u32 n,n,1;\nsetp.lt.u32 p,n,4194304;\n@p bra LW;\nLD:\n}\n" ::"r"(b), "r"(parity) : "memory");
}
__device__ __forceinline__ void fence_init() { asm volatile("fence.mbarrier_init.release.cluster;" ::: "memory"); }
__device__ __forceinline__ void fence_async() { asm volatile("fence.proxy.async.shared::cta;" ::: "memory"); }
__device__ __forceinline__ void bulk_load(uint32_t dst, const void* src, int bytes, uint32_t bar) {
  asm volatile("cp.async.bulk.shared::cluster.global.mbarrier::complete_tx::bytes [%0],[%1],%2,[%3];" ::"r"(dst), "l"(src), "r"(bytes), "r"(bar) : "memory");
}
__device__ __forceinline__ void tma2d(uint32_t dst, const CUtensorMap* m, int c0, int c1, uint32_t bar) {
  asm volatile("cp.async.bulk.tensor.2d.shared::cluster.global.mbarrier::complete_tx::bytes [%0],[%1,{%3,%4}],[%2];" ::"r"(dst), "l"(m), "r"(bar), "r"(c0), "r"(c1) : "memory");
}
__device__ __forceinline__ void bulk_load_mc(uint32_t dst, const void* src, int bytes, uint32_t bar) {
  asm volatile("cp.async.bulk.shared::cluster.global.mbarrier::complete_tx::bytes.multicast::cluster [%0],[%1],%2,[%3],%4;" ::"r"(dst), "l"(src), "r"(bytes), "r"(bar), "h"((uint16_t)3) : "memory");
}
__device__ __forceinline__ void tma2d_mc(uint32_t dst, const CUtensorMap* m, int c0, int c1, uint32_t bar) {
  asm volatile("cp.async.bulk.tensor.2d.shared::cluster.global.mbarrier::complete_tx::bytes.multicast::cluster [%0],[%1,{%3,%4}],[%2],%5;" ::"r"(dst), "l"(m), "r"(bar), "r"(c0), "r"(c1), "h"((uint16_t)3) : "memory");
}
__device__ __forceinline__ void cluster_arrive() { asm volatile("barrier.cluster.arrive.relaxed.aligned;" ::: "memory"); }
__device__ __forceinline__ void cluster_wait() { asm volatile("barrier.cluster.wait.aligned;" ::: "memory"); }
__device__ __forceinline__ void cluster_sync() { asm volatile("barrier.cluster.arrive.release.aligned;\nbarrier.cluster.wait.acquire.aligned;" ::: "memory"); }
__device__ __forceinline__ void l2_prefetch(const void* p, int bytes) { asm volatile("cp.async.bulk.prefetch.L2.global [%0],%1;" ::"l"(p), "r"(bytes) : "memory"); }
__device__ __forceinline__ void pdl_launch() { asm volatile("griddepcontrol.launch_dependents;" ::: "memory"); }
__device__ __forceinline__ void pdl_wait() { asm volatile("griddepcontrol.wait;" ::: "memory"); }
__device__ __forceinline__ void wg_fence() { asm volatile("wgmma.fence.sync.aligned;" ::: "memory"); }
__device__ __forceinline__ void wg_commit() { asm volatile("wgmma.commit_group.sync.aligned;" ::: "memory"); }
template <int N> __device__ __forceinline__ void wg_wait() { asm volatile("wgmma.wait_group.sync.aligned %0;" ::"n"(N) : "memory"); }
template <int N> __device__ __forceinline__ void reg_fence(float (&d)[N]) {
#pragma unroll
  for (int i = 0; i < N; i++) asm volatile("" : "+f"(d[i])::"memory");
}
template <int N> __device__ __forceinline__ void zero(float (&d)[N]) {
#pragma unroll
  for (int i = 0; i < N; i++) d[i] = 0.f;
  reg_fence(d);
}
__device__ __forceinline__ uint64_t mk_desc(uint32_t addr, uint32_t lbo, uint32_t sbo, uint32_t mode) {
  return (uint64_t)((addr >> 4) & 0x3FFF) | ((uint64_t)(lbo >> 4) << 16) | ((uint64_t)(sbo >> 4) << 32) | ((uint64_t)mode << 62);
}
__device__ __forceinline__ void ldsm4(uint32_t a, uint32_t (&r)[4]) {
  asm volatile("ldmatrix.sync.aligned.m8n8.x4.shared.b16 {%0,%1,%2,%3},[%4];" : "=r"(r[0]), "=r"(r[1]), "=r"(r[2]), "=r"(r[3]) : "r"(a) : "memory");
}
__device__ __forceinline__ uint32_t pack_rn(float lo, float hi) { uint32_t r; asm("cvt.rn.bf16x2.f32 %0,%1,%2;" : "=r"(r) : "f"(hi), "f"(lo)); return r; }
__device__ __forceinline__ uint32_t pack_rz(float lo, float hi) { uint32_t r; asm("cvt.rz.bf16x2.f32 %0,%1,%2;" : "=r"(r) : "f"(hi), "f"(lo)); return r; }
__device__ __forceinline__ float blo(uint32_t u) { return __uint_as_float(u << 16); }
__device__ __forceinline__ float bhi(uint32_t u) { return __uint_as_float(u & 0xFFFF0000u); }
__device__ __forceinline__ float rbf(float x) { return __bfloat162float(__float2bfloat16_rn(x)); }
__device__ __forceinline__ float qsum(float v) { v += __shfl_xor_sync(~0u, v, 1); return v + __shfl_xor_sync(~0u, v, 2); }
__device__ __forceinline__ float ex2(float x) { float r; asm("ex2.approx.ftz.f32 %0,%1;" : "=f"(r) : "f"(x)); return r; }
#define TS(k, i)
__device__ __forceinline__ void wgmma_rs_n176_t1(float (&d)[88],uint32_t a0,uint32_t a1,uint32_t a2,uint32_t a3,uint64_t db,int sc){
  asm volatile("{\n.reg .pred p;\nsetp.ne.b32 p,%93,0;\n"
    "wgmma.mma_async.sync.aligned.m64n176k16.f32.bf16.bf16 {%0,%1,%2,%3,%4,%5,%6,%7,%8,%9,%10,%11,%12,%13,%14,%15,%16,%17,%18,%19,%20,%21,%22,%23,%24,%25,%26,%27,%28,%29,%30,%31,%32,%33,%34,%35,%36,%37,%38,%39,%40,%41,%42,%43,%44,%45,%46,%47,%48,%49,%50,%51,%52,%53,%54,%55,%56,%57,%58,%59,%60,%61,%62,%63,%64,%65,%66,%67,%68,%69,%70,%71,%72,%73,%74,%75,%76,%77,%78,%79,%80,%81,%82,%83,%84,%85,%86,%87},{%88,%89,%90,%91},%92,p,1,1,1;\n}\n"
    :"+f"(d[0]),"+f"(d[1]),"+f"(d[2]),"+f"(d[3]),"+f"(d[4]),"+f"(d[5]),"+f"(d[6]),"+f"(d[7]),"+f"(d[8]),"+f"(d[9]),"+f"(d[10]),"+f"(d[11]),"+f"(d[12]),"+f"(d[13]),"+f"(d[14]),"+f"(d[15]),"+f"(d[16]),"+f"(d[17]),"+f"(d[18]),"+f"(d[19]),"+f"(d[20]),"+f"(d[21]),"+f"(d[22]),"+f"(d[23]),"+f"(d[24]),"+f"(d[25]),"+f"(d[26]),"+f"(d[27]),"+f"(d[28]),"+f"(d[29]),"+f"(d[30]),"+f"(d[31]),"+f"(d[32]),"+f"(d[33]),"+f"(d[34]),"+f"(d[35]),"+f"(d[36]),"+f"(d[37]),"+f"(d[38]),"+f"(d[39]),"+f"(d[40]),"+f"(d[41]),"+f"(d[42]),"+f"(d[43]),"+f"(d[44]),"+f"(d[45]),"+f"(d[46]),"+f"(d[47]),"+f"(d[48]),"+f"(d[49]),"+f"(d[50]),"+f"(d[51]),"+f"(d[52]),"+f"(d[53]),"+f"(d[54]),"+f"(d[55]),"+f"(d[56]),"+f"(d[57]),"+f"(d[58]),"+f"(d[59]),"+f"(d[60]),"+f"(d[61]),"+f"(d[62]),"+f"(d[63]),"+f"(d[64]),"+f"(d[65]),"+f"(d[66]),"+f"(d[67]),"+f"(d[68]),"+f"(d[69]),"+f"(d[70]),"+f"(d[71]),"+f"(d[72]),"+f"(d[73]),"+f"(d[74]),"+f"(d[75]),"+f"(d[76]),"+f"(d[77]),"+f"(d[78]),"+f"(d[79]),"+f"(d[80]),"+f"(d[81]),"+f"(d[82]),"+f"(d[83]),"+f"(d[84]),"+f"(d[85]),"+f"(d[86]),"+f"(d[87])
    :"r"(a0),"r"(a1),"r"(a2),"r"(a3),"l"(db),"r"(sc));
}
__device__ __forceinline__ void wgmma_rs_n192_t1(float (&d)[96],uint32_t a0,uint32_t a1,uint32_t a2,uint32_t a3,uint64_t db,int sc){
  asm volatile("{\n.reg .pred p;\nsetp.ne.b32 p,%101,0;\n"
    "wgmma.mma_async.sync.aligned.m64n192k16.f32.bf16.bf16 {%0,%1,%2,%3,%4,%5,%6,%7,%8,%9,%10,%11,%12,%13,%14,%15,%16,%17,%18,%19,%20,%21,%22,%23,%24,%25,%26,%27,%28,%29,%30,%31,%32,%33,%34,%35,%36,%37,%38,%39,%40,%41,%42,%43,%44,%45,%46,%47,%48,%49,%50,%51,%52,%53,%54,%55,%56,%57,%58,%59,%60,%61,%62,%63,%64,%65,%66,%67,%68,%69,%70,%71,%72,%73,%74,%75,%76,%77,%78,%79,%80,%81,%82,%83,%84,%85,%86,%87,%88,%89,%90,%91,%92,%93,%94,%95},{%96,%97,%98,%99},%100,p,1,1,1;\n}\n"
    :"+f"(d[0]),"+f"(d[1]),"+f"(d[2]),"+f"(d[3]),"+f"(d[4]),"+f"(d[5]),"+f"(d[6]),"+f"(d[7]),"+f"(d[8]),"+f"(d[9]),"+f"(d[10]),"+f"(d[11]),"+f"(d[12]),"+f"(d[13]),"+f"(d[14]),"+f"(d[15]),"+f"(d[16]),"+f"(d[17]),"+f"(d[18]),"+f"(d[19]),"+f"(d[20]),"+f"(d[21]),"+f"(d[22]),"+f"(d[23]),"+f"(d[24]),"+f"(d[25]),"+f"(d[26]),"+f"(d[27]),"+f"(d[28]),"+f"(d[29]),"+f"(d[30]),"+f"(d[31]),"+f"(d[32]),"+f"(d[33]),"+f"(d[34]),"+f"(d[35]),"+f"(d[36]),"+f"(d[37]),"+f"(d[38]),"+f"(d[39]),"+f"(d[40]),"+f"(d[41]),"+f"(d[42]),"+f"(d[43]),"+f"(d[44]),"+f"(d[45]),"+f"(d[46]),"+f"(d[47]),"+f"(d[48]),"+f"(d[49]),"+f"(d[50]),"+f"(d[51]),"+f"(d[52]),"+f"(d[53]),"+f"(d[54]),"+f"(d[55]),"+f"(d[56]),"+f"(d[57]),"+f"(d[58]),"+f"(d[59]),"+f"(d[60]),"+f"(d[61]),"+f"(d[62]),"+f"(d[63]),"+f"(d[64]),"+f"(d[65]),"+f"(d[66]),"+f"(d[67]),"+f"(d[68]),"+f"(d[69]),"+f"(d[70]),"+f"(d[71]),"+f"(d[72]),"+f"(d[73]),"+f"(d[74]),"+f"(d[75]),"+f"(d[76]),"+f"(d[77]),"+f"(d[78]),"+f"(d[79]),"+f"(d[80]),"+f"(d[81]),"+f"(d[82]),"+f"(d[83]),"+f"(d[84]),"+f"(d[85]),"+f"(d[86]),"+f"(d[87]),"+f"(d[88]),"+f"(d[89]),"+f"(d[90]),"+f"(d[91]),"+f"(d[92]),"+f"(d[93]),"+f"(d[94]),"+f"(d[95])
    :"r"(a0),"r"(a1),"r"(a2),"r"(a3),"l"(db),"r"(sc));
}
__device__ __forceinline__ void wgmma_rs_n24_t1(float (&d)[12],uint32_t a0,uint32_t a1,uint32_t a2,uint32_t a3,uint64_t db,int sc){
  asm volatile("{\n.reg .pred p;\nsetp.ne.b32 p,%17,0;\n"
    "wgmma.mma_async.sync.aligned.m64n24k16.f32.bf16.bf16 {%0,%1,%2,%3,%4,%5,%6,%7,%8,%9,%10,%11},{%12,%13,%14,%15},%16,p,1,1,1;\n}\n"
    :"+f"(d[0]),"+f"(d[1]),"+f"(d[2]),"+f"(d[3]),"+f"(d[4]),"+f"(d[5]),"+f"(d[6]),"+f"(d[7]),"+f"(d[8]),"+f"(d[9]),"+f"(d[10]),"+f"(d[11])
    :"r"(a0),"r"(a1),"r"(a2),"r"(a3),"l"(db),"r"(sc));
}
__device__ __forceinline__ void wgmma_rs_n64_t0(float (&d)[32],uint32_t a0,uint32_t a1,uint32_t a2,uint32_t a3,uint64_t db,int sc){
  asm volatile("{\n.reg .pred p;\nsetp.ne.b32 p,%37,0;\n"
    "wgmma.mma_async.sync.aligned.m64n64k16.f32.bf16.bf16 {%0,%1,%2,%3,%4,%5,%6,%7,%8,%9,%10,%11,%12,%13,%14,%15,%16,%17,%18,%19,%20,%21,%22,%23,%24,%25,%26,%27,%28,%29,%30,%31},{%32,%33,%34,%35},%36,p,1,1,0;\n}\n"
    :"+f"(d[0]),"+f"(d[1]),"+f"(d[2]),"+f"(d[3]),"+f"(d[4]),"+f"(d[5]),"+f"(d[6]),"+f"(d[7]),"+f"(d[8]),"+f"(d[9]),"+f"(d[10]),"+f"(d[11]),"+f"(d[12]),"+f"(d[13]),"+f"(d[14]),"+f"(d[15]),"+f"(d[16]),"+f"(d[17]),"+f"(d[18]),"+f"(d[19]),"+f"(d[20]),"+f"(d[21]),"+f"(d[22]),"+f"(d[23]),"+f"(d[24]),"+f"(d[25]),"+f"(d[26]),"+f"(d[27]),"+f"(d[28]),"+f"(d[29]),"+f"(d[30]),"+f"(d[31])
    :"r"(a0),"r"(a1),"r"(a2),"r"(a3),"l"(db),"r"(sc));
}
__device__ __forceinline__ void wgmma_ss_n128_t1(float (&d)[64],uint64_t da,uint64_t db,int sc){
  asm volatile("{\n.reg .pred p;\nsetp.ne.b32 p,%66,0;\n"
    "wgmma.mma_async.sync.aligned.m64n128k16.f32.bf16.bf16 {%0,%1,%2,%3,%4,%5,%6,%7,%8,%9,%10,%11,%12,%13,%14,%15,%16,%17,%18,%19,%20,%21,%22,%23,%24,%25,%26,%27,%28,%29,%30,%31,%32,%33,%34,%35,%36,%37,%38,%39,%40,%41,%42,%43,%44,%45,%46,%47,%48,%49,%50,%51,%52,%53,%54,%55,%56,%57,%58,%59,%60,%61,%62,%63},%64,%65,p,1,1,0,1;\n}\n"
    :"+f"(d[0]),"+f"(d[1]),"+f"(d[2]),"+f"(d[3]),"+f"(d[4]),"+f"(d[5]),"+f"(d[6]),"+f"(d[7]),"+f"(d[8]),"+f"(d[9]),"+f"(d[10]),"+f"(d[11]),"+f"(d[12]),"+f"(d[13]),"+f"(d[14]),"+f"(d[15]),"+f"(d[16]),"+f"(d[17]),"+f"(d[18]),"+f"(d[19]),"+f"(d[20]),"+f"(d[21]),"+f"(d[22]),"+f"(d[23]),"+f"(d[24]),"+f"(d[25]),"+f"(d[26]),"+f"(d[27]),"+f"(d[28]),"+f"(d[29]),"+f"(d[30]),"+f"(d[31]),"+f"(d[32]),"+f"(d[33]),"+f"(d[34]),"+f"(d[35]),"+f"(d[36]),"+f"(d[37]),"+f"(d[38]),"+f"(d[39]),"+f"(d[40]),"+f"(d[41]),"+f"(d[42]),"+f"(d[43]),"+f"(d[44]),"+f"(d[45]),"+f"(d[46]),"+f"(d[47]),"+f"(d[48]),"+f"(d[49]),"+f"(d[50]),"+f"(d[51]),"+f"(d[52]),"+f"(d[53]),"+f"(d[54]),"+f"(d[55]),"+f"(d[56]),"+f"(d[57]),"+f"(d[58]),"+f"(d[59]),"+f"(d[60]),"+f"(d[61]),"+f"(d[62]),"+f"(d[63])
    :"l"(da),"l"(db),"r"(sc));
}
__device__ __forceinline__ void wgmma_ss_n64_t1(float (&d)[32],uint64_t da,uint64_t db,int sc){
  asm volatile("{\n.reg .pred p;\nsetp.ne.b32 p,%34,0;\n"
    "wgmma.mma_async.sync.aligned.m64n64k16.f32.bf16.bf16 {%0,%1,%2,%3,%4,%5,%6,%7,%8,%9,%10,%11,%12,%13,%14,%15,%16,%17,%18,%19,%20,%21,%22,%23,%24,%25,%26,%27,%28,%29,%30,%31},%32,%33,p,1,1,0,1;\n}\n"
    :"+f"(d[0]),"+f"(d[1]),"+f"(d[2]),"+f"(d[3]),"+f"(d[4]),"+f"(d[5]),"+f"(d[6]),"+f"(d[7]),"+f"(d[8]),"+f"(d[9]),"+f"(d[10]),"+f"(d[11]),"+f"(d[12]),"+f"(d[13]),"+f"(d[14]),"+f"(d[15]),"+f"(d[16]),"+f"(d[17]),"+f"(d[18]),"+f"(d[19]),"+f"(d[20]),"+f"(d[21]),"+f"(d[22]),"+f"(d[23]),"+f"(d[24]),"+f"(d[25]),"+f"(d[26]),"+f"(d[27]),"+f"(d[28]),"+f"(d[29]),"+f"(d[30]),"+f"(d[31])
    :"l"(da),"l"(db),"r"(sc));
}

__device__ __forceinline__ float silu_bf(bf16 c) { const float x = __bfloat162float(c); return rbf(x / (1.f + __expf(-x))); }
__device__ __forceinline__ void fma8(float (&a)[8], float s, const uint4& v) {
  a[0] += s * blo(v.x); a[1] += s * bhi(v.x); a[2] += s * blo(v.y); a[3] += s * bhi(v.y);
  a[4] += s * blo(v.z); a[5] += s * bhi(v.z); a[6] += s * blo(v.w); a[7] += s * bhi(v.w);
}
__device__ __forceinline__ float red8(float (&a)[8], int lane) {
#pragma unroll
  for (int w = 4; w >= 1; w >>= 1) {
    const bool up = lane & (w * 4);
#pragma unroll
    for (int j = 0; j < w; j++) a[j] = (up ? a[j + w] : a[j]) + __shfl_xor_sync(~0u, up ? a[j] : a[j + w], w * 4);
  }
  return a[0];
}
__device__ __forceinline__ float mod_fin(float s, int n) { s = rbf(s); return ((n >> 9) == 1 || (n >> 9) == 4) ? rbf(1.f + s) : s; }
__device__ __forceinline__ void poll4(uint2& a, uint2& b, uint2& c, uint2& d, const uint32_t* p, const uint32_t* q) {
  asm volatile("{\n.reg .pred p;\n.reg .u32 n,t;\nmov.u32 n,0;\nLW:\nld.relaxed.gpu.global.v2.u32 {%0,%1},[%8];\nld.relaxed.gpu.global.v2.u32 {%2,%3},[%8+64];\n"
               "ld.relaxed.gpu.global.v2.u32 {%4,%5},[%9];\nld.relaxed.gpu.global.v2.u32 {%6,%7},[%9+2048];\n"
               "lop3.b32 t,%0,%1,%2,0x80;\nlop3.b32 t,t,%3,%4,0x80;\nlop3.b32 t,t,%5,%6,0x80;\nlop3.b32 t,t,%7,1,0x80;\n"
               "setp.ne.u32 p,t,0;\n@p bra LD;\nadd.u32 n,n,1;\nsetp.lt.u32 p,n,1048576;\n@p bra LW;\nLD:\n}\n"
               : "=&r"(a.x), "=&r"(a.y), "=&r"(b.x), "=&r"(b.y), "=&r"(c.x), "=&r"(c.y), "=&r"(d.x), "=&r"(d.y) : "l"(p), "l"(q) : "memory");
}

constexpr int LN_SMEM = 131072 + 4 * 24576 + 2048 + 256 + 512;
template <bool FFN>
__global__ void __cluster_dims__(2, 1, 1) __launch_bounds__(384, 1) k_lngemm(const __grid_constant__ CUtensorMap mX, const __grid_constant__ CUtensorMap mB0,
                                                   const __grid_constant__ CUtensorMap mB1, const bf16* __restrict__ cv, const bf16* __restrict__ wm, const bf16* __restrict__ xg) {
  extern __shared__ __align__(1024) uint8_t smem[];
  const uint32_t sA = smem_u32(smem), sB = sA + 131072, sM = sB + 4 * 24576, bars = sM + 2048;
  const uint32_t bA = bars, bF = bars + 64, bE = bars + 96;
  const int tid = threadIdx.x, warp = tid >> 5, lane = tid & 31;
  const int pr = blockIdx.x & 1, rb = FFN ? (blockIdx.x >> 4) * 2 + pr : blockIdx.x >> 3, ct = FFN ? (blockIdx.x >> 1) & 7 : blockIdx.x & 7;
  constexpr int NST = FFN ? 16 : 8, KS = FFN ? 2 : 4, BOX = FFN ? 4096 : 8192;
  TS(FFN ? 4 : 1, 0);
  pdl_launch();
  float* red = (float*)(smem + (bars - sA) + 256);
  if (tid == 256) {
    for (int i = 0; i < 8; i++) mbar_init(bA + 8 * i, 1);
    for (int i = 0; i < 4; i++) { mbar_init(bF + 8 * i, 1); mbar_init(bE + 8 * i, FFN ? 16 : 8); }
    fence_init();
  }
  __syncwarp();
  cluster_arrive();
  uint4 wv0, wv1, xv[4];
  bf16 cv0, cv1;
  if (!FFN && tid < 256) {
    wv0 = __ldg((const uint4*)(wm + tid * 3072 + blockIdx.x * 8)); wv1 = __ldg((const uint4*)(wm + (tid + 256) * 3072 + blockIdx.x * 8));
    cv0 = cv[tid]; cv1 = cv[tid + 256];
#pragma unroll
    for (int i = 0; i < 4; i++) xv[i] = __ldg((const uint4*)(xg + (blockIdx.x * 16 + (tid >> 4)) * 512 + i * 128 + (tid & 15) * 8));
  }
  cluster_wait();
  if (warp >= 8) {
    asm volatile("setmaxnreg.dec.sync.aligned.u32 40;");
    if (tid == 256) {
      auto loadB = [&](int s) {
        const uint32_t d = sB + (s & 3) * 24576, b = bF + (s & 3) * 8;
        mbar_expect(b, 24576);
        for (int j = 0; j < 3; j++) {
          if (FFN) tma2d_mc(d + (pr * 3 + j) * BOX, pr ? &mB1 : &mB0, ct * 176 + j * 64, s * 32, b);
          else tma2d(d + j * BOX, &mB0, ct * 192 + j * 64, s * 64, b);
        }
      };
      for (int i = 0; i < 8; i++) mbar_expect(bA + 8 * i, 16384);
      for (int s = 0; s < 4; s++) {
        const int i = s * 2 + (ct & 1);
        if (!FFN) tma2d_mc(sA + i * 16384, &mX, i * 64, rb * 128, bA + 8 * i);
        loadB(s);
      }
      if (FFN) {
        pdl_wait();
        for (int i = 0; i < 2; i++) bulk_load(sA + i * 16384, g_x1 + (rb * 64 + i * 8) * 1024, 16384, bA + 8 * i);
      }
      for (int s = 4; s < NST; s++) { mbar_wait(bE + (s & 3) * 8, ((s >> 2) - 1) & 1); loadB(s); }
    }
  } else {
  asm volatile("setmaxnreg.inc.sync.aligned.u32 232;");
  const int g = lane >> 2, t = lane & 3;
  const int lr = warp * 16 + (lane & 7) + ((lane >> 3) & 1) * 8;
  auto aaddr = [&](int ks) -> uint32_t {
    if (FFN) return sA + (ks * 2 + (lane >> 4)) * 2048 + lr * 16;
    return sA + (ks >> 2) * 16384 + lr * 128 + ((((ks & 3) * 2 + (lane >> 4)) ^ (lr & 7)) << 4);
  };
  const int row0 = rb * 128 + warp * 16 + g;
  float2 msh, msc;
  uint2 sh, sc;
  float rs0, rs1, nm0, nm1;
  if (!FFN) {
    {
      float a[8] = {0, 0, 0, 0, 0, 0, 0, 0};
      fma8(a, silu_bf(cv0), wv0); fma8(a, silu_bf(cv1), wv1);
      const float s = qsum(red8(a, lane));
      if (t == 0) red[warp * 8 + g] = s;
      asm volatile("bar.sync 1,256;" ::: "memory");
      if (tid < 8) {
        float r = 0;
#pragma unroll
        for (int i = 0; i < 8; i++) r += red[i * 8 + tid];
        const int n = blockIdx.x * 8 + tid;
        asm volatile("st.relaxed.gpu.global.u32 [%0],%1;" ::"l"(g_modv + n), "r"(__float_as_uint(mod_fin(r, n)) | 1u) : "memory");
      }
      TS(0, 1);
    }
    {
      float v[32], s = 0, q = 0;
#pragma unroll
      for (int i = 0; i < 16; i++) { const uint32_t u = ((const uint32_t*)xv)[i]; v[2 * i] = blo(u); v[2 * i + 1] = bhi(u); s += v[2 * i] + v[2 * i + 1]; }
      s = qsum(s); s += __shfl_xor_sync(~0u, s, 4); s += __shfl_xor_sync(~0u, s, 8);
      const float m = s * (1.f / 512);
#pragma unroll
      for (int i = 0; i < 32; i++) q += (v[i] - m) * (v[i] - m);
      q = qsum(q); q += __shfl_xor_sync(~0u, q, 4); q += __shfl_xor_sync(~0u, q, 8);
      const float rs = rsqrtf(q * (1.f / 512) + 1e-5f);
      if ((tid & 15) == 0)
        asm volatile("st.relaxed.gpu.global.v2.u32 [%0],{%1,%2};" ::"l"(g_modv + 1024 + (blockIdx.x * 16 + (tid >> 4)) * 2), "r"(__float_as_uint(rs) | 1u), "r"(__float_as_uint(-m * rs) | 1u) : "memory");
    }
    uint2 p0, p1;
    poll4(p0, p1, sh, sc, g_modv + 1024 + row0 * 2, g_modv + tid * 2);
    rs0 = __uint_as_float(p0.x); nm0 = __uint_as_float(p0.y); rs1 = __uint_as_float(p1.x); nm1 = __uint_as_float(p1.y);
  } else {
    pdl_wait();
    TS(4, 1);
    msh = *(const float2*)(g_mod + 1536 + tid * 2); msc = *(const float2*)(g_mod + 2048 + tid * 2);
    const float4 p0 = *(const float4*)(g_st + row0 * 8 + t * 2), p1 = *(const float4*)(g_st + (row0 + 8) * 8 + t * 2);
    const float m0 = qsum(p0.x + p0.z) * 0.125f, m1 = qsum(p1.x + p1.z) * 0.125f;
    const float v0 = qsum(p0.y + p0.w + 64.f * ((p0.x - m0) * (p0.x - m0) + (p0.z - m0) * (p0.z - m0)));
    const float v1 = qsum(p1.y + p1.w + 64.f * ((p1.x - m1) * (p1.x - m1) + (p1.z - m1) * (p1.z - m1)));
    rs0 = rsqrtf(v0 * (1.f / 512) + 1e-5f); rs1 = rsqrtf(v1 * (1.f / 512) + 1e-5f);
    nm0 = -m0 * rs0; nm1 = -m1 * rs1;
  }
  {
    uint32_t* m = (uint32_t*)(smem + (sM - sA)) + (tid >> 3) * 16 + (tid & 3) * 4 + ((tid >> 2) & 1);
    if (FFN) { m[0] = pack_rn(msc.x, msc.y); m[2] = pack_rn(msh.x, msh.y); }
    else { m[0] = __byte_perm(sc.x, sc.y, 0x7632); m[2] = __byte_perm(sh.x, sh.y, 0x7632); }
    asm volatile("bar.sync 1,256;" ::: "memory");
  }
  if (FFN && warp >= 2 && lane == 0) bulk_load(sA + warp * 16384, g_x1 + (rb * 64 + warp * 8) * 1024, 16384, bA + 8 * warp);
  constexpr int NA = FFN ? 88 : 96;
  float acc0[NA], acc1[FFN ? 88 : 1];
  uint32_t a[2][KS][4];
  auto prep = [&](int ks, uint32_t(&o)[4]) {
    if ((ks & 3) == 0) mbar_wait(bA + 2 * ks, 0);
    uint32_t r[4]; ldsm4(aaddr(ks), r);
    const uint4 m = *(const uint4*)(smem + (sM - sA) + ks * 64 + t * 16);
#pragma unroll
    for (int i = 0; i < 4; i++) {
      const float rs = (i & 1) ? rs1 : rs0, nm = (i & 1) ? nm1 : nm0;
      const uint32_t n = pack_rn(fmaf(blo(r[i]), rs, nm), fmaf(bhi(r[i]), rs, nm));
      asm("fma.rn.bf16x2 %0,%1,%2,%3;" : "=r"(o[i]) : "r"(n), "r"(i < 2 ? m.x : m.y), "r"(i < 2 ? m.z : m.w));
    }
  };
  auto stage = [&](int s, uint32_t(&c)[KS][4], uint32_t(&n)[KS][4]) {
    mbar_wait(bF + (s & 3) * 8, (s >> 2) & 1);
    const uint64_t db = mk_desc(sB + (s & 3) * 24576, BOX, 1024, 1);
    wg_fence();
#pragma unroll
    for (int k = 0; k < KS; k++) {
      if constexpr (FFN) {
        wgmma_rs_n176_t1(acc0, c[k][0], c[k][1], c[k][2], c[k][3], db + k * 128, s + k);
        wgmma_rs_n176_t1(acc1, c[k][0], c[k][1], c[k][2], c[k][3], db + k * 128 + 3 * BOX / 16, s + k);
      } else {
        wgmma_rs_n192_t1(acc0, c[k][0], c[k][1], c[k][2], c[k][3], db + k * 128, s + k);
      }
    }
    wg_commit();
    wg_wait<1>();
    if (s > 0 && s <= NST - 4) {
      if (!FFN) { if (lane == 0) mbar_arrive(bE + ((s - 1) & 3) * 8); }
      else if (lane < 2) asm volatile("{\n.reg .b32 r;\nmapa.shared::cluster.u32 r,%0,%1;\nmbarrier.arrive.relaxed.cluster.shared::cluster.b64 _,[r];\n}" ::"r"(bE + ((s - 1) & 3) * 8), "r"(lane) : "memory");
    }
    if (s < NST - 1) {
#pragma unroll
      for (int k = 0; k < KS; k++) prep((s + 1) * KS + k, n[k]);
    }
  };
#pragma unroll
  for (int k = 0; k < KS; k++) prep(k, a[0][k]);
  TS(FFN ? 4 : 1, 2);
#pragma unroll 1
  for (int s = 0; s < NST; s += 2) { stage(s, a[0], a[1]); stage(s + 1, a[1], a[0]); }
  wg_wait<0>();
  reg_fence(acc0);
  TS(FFN ? 4 : 1, 3);
  if constexpr (FFN) {
    reg_fence(acc1);
    uint32_t* o = (uint32_t*)g_h + ((rb * 172 + ct * 22) * 128 + warp * 16 + g) * 4 + t;
#pragma unroll
    for (int j = 0; j < 22; j++) {
      if (ct * 22 + j < 172) {
        float h[4], d[4];
#pragma unroll
        for (int i = 0; i < 4; i++) { const float x = acc0[4 * j + i]; d[i] = 1.f + ex2(fminf(-1.4426950408889634f * x, 30.f)); h[i] = x * acc1[4 * j + i]; }
        const float d01 = d[0] * d[1], d23 = d[2] * d[3];
        float r; asm("rcp.approx.ftz.f32 %0,%1;" : "=f"(r) : "f"(d01 * d23));
        const float r01 = r * d23, r23 = r * d01;
        h[0] *= r01 * d[1]; h[1] *= r01 * d[0]; h[2] *= r23 * d[3]; h[3] *= r23 * d[2];
        o[j * 512] = pack_rn(h[0], h[1]);
        o[j * 512 + 32] = pack_rn(h[2], h[3]);
      }
    }
  } else {
    uint32_t* o = (uint32_t*)g_qkv + (ct * 24 * 2048 + row0) * 4 + t;
#pragma unroll
    for (int j = 0; j < 24; j += 2) {
      const int G = ct * 24 + j;
      const float sc = G < 64 ? 0.25f * 1.4426950408889634f : 1.f;
      uint32_t p[4];
#pragma unroll
      for (int i = 0; i < 4; i++) p[i] = pack_rn(acc0[4 * j + 2 * i] * sc, acc0[4 * j + 2 * i + 1] * sc);
      o[j * 8192] = p[0]; o[j * 8192 + 32] = p[1]; o[(j + 1) * 8192] = p[2]; o[(j + 1) * 8192 + 32] = p[3];
      if (G >= 64 && G < 128) {
        float n0 = blo(p[0]) * blo(p[0]) + bhi(p[0]) * bhi(p[0]) + blo(p[2]) * blo(p[2]) + bhi(p[2]) * bhi(p[2]);
        float n1 = blo(p[1]) * blo(p[1]) + bhi(p[1]) * bhi(p[1]) + blo(p[3]) * blo(p[3]) + bhi(p[3]) * bhi(p[3]);
        n0 = qsum(n0); n1 = qsum(n1);
        const uint32_t mx = __reduce_max_sync(~0u, max(__float_as_uint(n0), __float_as_uint(n1)));
        if (lane == 0) g_kmax[((G - 64) >> 1) * 128 + rb * 8 + warp] = __uint_as_float(mx);
      }
    }
  }
  TS(FFN ? 4 : 1, 4);
}
}

#define SMASK 0xAAu
#define BRK 0
#define PACK 1
#define PP 1
constexpr int AT_SMEM = 5 * 32768 + 256;
__device__ __forceinline__ uint32_t exp2_pair_fma(float s0, float s1, float c, uint32_t ka, uint32_t kz) {
  uint32_t r;
  asm volatile("{\n.reg .b32 y0,y1,e,u,t;\n"
      "fma.rn.sat.f32 y0,%1,0f00000080,%3;\nfma.rn.sat.f32 y1,%2,0f00000080,%3;\n"
      "mad.lo.u32 e,y1,65536,y0;\n"
      "and.b32 u,e,0x007F007F;\n"
      "fma.rn.f16x2 u,u,%4,%5;\nfma.rn.f16x2 t,u,u,%6;\nfma.rn.f16x2 t,t,u,%7;\n"
      "lop3.b32 %0,t,0x007F007F,e,0xE2;\n}\n"
      : "=r"(r) : "f"(s0), "f"(s1), "f"(c), "r"(ka), "r"(0x36B236B2u), "r"(0x3C733C73u), "r"(0x47764776u), "r"(kz));
  return r;
}
__device__ __forceinline__ void attn_pass(float (&oa)[12], float (&ob)[12], const uint32_t (&q)[4], float m0, float m1, uint32_t sK, uint32_t bars, bool first, uint32_t kz) {
  const uint64_t dk = mk_desc(sK, 32768, 128, 0), dv = mk_desc(sK + 65536, 128, 32768, 0);
  const float c0 = (127.f - m0) * __uint_as_float(0x80u), c1 = (127.f - m1) * __uint_as_float(0x80u);
  const uint32_t ka = 0x7ACE7ACEu + kz;
  constexpr int NK = 64, NS = 32, NP = 16, NI = 32;
  auto qk = [&](float (&s)[NS], int i) { wgmma_rs_n64_t0(s, q[0], q[1], q[2], q[3], dk + i * NK, 0); };
  auto softmax = [&](float (&s)[NS], uint32_t (&p)[NP], uint32_t mask) {
    reg_fence(s);
    float e0, e1;
    int pend = -1;
#pragma unroll
    for (int t = 0; t < NP; t++) {
      const int j = (t & 3) * 4 + (t >> 2);
      if ((mask >> (t & 3)) & 1) {
        p[j] = exp2_pair_fma(s[2 * j], s[2 * j + 1], (j & 1) ? c1 : c0, ka, kz);
      } else {
        float f0, f1;
        asm volatile("ex2.approx.ftz.f32 %0,%2;\nex2.approx.ftz.f32 %1,%3;" : "=&f"(f0), "=f"(f1) : "f"(s[2 * j]), "f"(s[2 * j + 1]));
        if (pend >= 0) asm volatile("cvt.rn.bf16x2.f32 %0,%1,%2;" : "=r"(p[pend]) : "f"(e1), "f"(e0));
        e0 = f0; e1 = f1; pend = j;
      }
    }
    if (pend >= 0) asm volatile("cvt.rn.bf16x2.f32 %0,%1,%2;" : "=r"(p[pend]) : "f"(e1), "f"(e0));
#pragma unroll
    for (int j = 0; j < NP; j++) asm volatile("" : "+r"(p[j])::"memory");
  };
  auto pv = [&](uint32_t (&p)[NP], int i, uint32_t mask) {
#pragma unroll
    for (int k = 0; k < 4; k++) wgmma_rs_n24_t1(((mask >> k) & 1) ? ob : oa, p[4 * k], p[4 * k + 1], p[4 * k + 2], p[4 * k + 3], dv + i * NK + k * 16, 1);
  };
  auto ld = [&](int i) { if (first && (i & 3) == 0) mbar_wait(bars + i * 2, 0); };
  constexpr uint32_t M0 = SMASK & 15, M1 = SMASK >> 4;
  zero(oa); zero(ob);
  ld(0);
  if (first) TS(2, 2);
  float s[NS];
  zero(s);
  uint32_t p0[NP], p1[NP];
  wg_fence(); qk(s, 0); wg_commit(); wg_wait<0>(); softmax(s, p0, M0);
#pragma unroll 1
  for (int i = 0; i < NI - 2; i += 2) {
    wg_fence(); qk(s, i + 1); wg_commit(); pv(p0, i, M0); wg_commit(); wg_wait<1>(); softmax(s, p1, M1); wg_wait<0>();
    ld(i + 2);
    wg_fence(); qk(s, i + 2); wg_commit(); pv(p1, i + 1, M1); wg_commit(); wg_wait<1>(); softmax(s, p0, M0); wg_wait<0>();
  }
  wg_fence(); qk(s, NI - 1); wg_commit(); pv(p0, NI - 2, M0); wg_commit(); wg_wait<1>(); softmax(s, p1, M1); wg_wait<0>();
  wg_fence(); pv(p1, NI - 1, M1); wg_commit();
  wg_wait<0>();
  reg_fence(oa); reg_fence(ob);
}
__device__ __forceinline__ void mma16816(float (&d)[4], const uint32_t (&a)[4], uint32_t b0, uint32_t b1) {
  asm("mma.sync.aligned.m16n8k16.row.col.f32.bf16.bf16.f32 {%0,%1,%2,%3},{%4,%5,%6,%7},{%8,%9},{%0,%1,%2,%3};"
      : "+f"(d[0]), "+f"(d[1]), "+f"(d[2]), "+f"(d[3]) : "r"(a[0]), "r"(a[1]), "r"(a[2]), "r"(a[3]), "r"(b0), "r"(b1));
}
__device__ __forceinline__ void attn_safe(float (&o)[12], const uint32_t (&q)[4], uint32_t sK) {
  const int lane = threadIdx.x & 31;
  const uint32_t ka = sK + (lane >> 4) * 32768 + (lane & 15) * 16;
  float m0 = -INFINITY, m1 = -INFINITY;
#pragma unroll 2
  for (int i = 0; i < 128; i++) {
    uint32_t k[4]; ldsm4(ka + i * 256, k);
    float s0[4] = {0, 0, 0, 0}, s1[4] = {0, 0, 0, 0};
    mma16816(s0, q, k[0], k[2]); mma16816(s1, q, k[1], k[3]);
    m0 = fmaxf(fmaxf(m0, fmaxf(s0[0], s0[1])), fmaxf(s1[0], s1[1])); m1 = fmaxf(fmaxf(m1, fmaxf(s0[2], s0[3])), fmaxf(s1[2], s1[3]));
  }
  m0 = fmaxf(m0, __shfl_xor_sync(~0u, m0, 1)); m0 = fmaxf(m0, __shfl_xor_sync(~0u, m0, 2));
  m1 = fmaxf(m1, __shfl_xor_sync(~0u, m1, 1)); m1 = fmaxf(m1, __shfl_xor_sync(~0u, m1, 2));
  float o0[4] = {0, 0, 0, 0}, o1[4] = {0, 0, 0, 0}, o2[4] = {0, 0, 0, 0};
#pragma unroll 2
  for (int i = 0; i < 128; i++) {
    uint32_t k[4], v[4]; ldsm4(ka + i * 256, k);
    asm volatile("ldmatrix.sync.aligned.m8n8.x4.trans.shared.b16 {%0,%1,%2,%3},[%4];" : "=r"(v[0]), "=r"(v[1]), "=r"(v[2]), "=r"(v[3]) : "r"(ka + 65536 + i * 256) : "memory");
    float s0[4] = {0, 0, 0, 0}, s1[4] = {0, 0, 0, 0};
    mma16816(s0, q, k[0], k[2]); mma16816(s1, q, k[1], k[3]);
    const uint32_t p[4] = {pack_rn(ex2(s0[0] - m0), ex2(s0[1] - m0)), pack_rn(ex2(s0[2] - m1), ex2(s0[3] - m1)),
                           pack_rn(ex2(s1[0] - m0), ex2(s1[1] - m0)), pack_rn(ex2(s1[2] - m1), ex2(s1[3] - m1))};
    mma16816(o0, p, v[0], v[1]); mma16816(o1, p, v[2], v[3]); mma16816(o2, p, 0x3F803F80u, 0x3F803F80u);
  }
#pragma unroll
  for (int i = 0; i < 4; i++) { o[i] = o0[i]; o[4 + i] = o1[i]; o[8 + i] = o2[i]; }
}
__global__ void __cluster_dims__(2, 1, 1) __launch_bounds__(512, 1) k_attn(const bf16* wo, const bf16* w1, const bf16* w3, const bf16* w2, const bf16* __restrict__ cv, const bf16* __restrict__ wm, uint32_t kz) {
  extern __shared__ __align__(1024) uint8_t smem[];
  const uint32_t sK = smem_u32(smem), bars = sK + 5 * 32768;
  const int tid = threadIdx.x, warp = tid >> 5, lane = tid & 31, g = lane >> 2, t = lane & 3;
  pdl_launch();
  if (blockIdx.x < 4) {
    float* cs = (float*)smem;
    cs[tid] = silu_bf(cv[tid]);
    __syncthreads();
    const int n0 = 1024 + blockIdx.x * 512, r0 = (tid >> 6) * 64;
    float a[8] = {0, 0, 0, 0, 0, 0, 0, 0};
#pragma unroll 16
    for (int r = r0; r < r0 + 64; r++) fma8(a, cs[r], __ldg((const uint4*)(wm + r * 3072 + n0 + (tid & 63) * 8)));
    float4* rp = (float4*)(cs + 512 + tid * 8);
    rp[0] = make_float4(a[0], a[1], a[2], a[3]); rp[1] = make_float4(a[4], a[5], a[6], a[7]);
    __syncthreads();
    float s = 0;
#pragma unroll
    for (int i = 0; i < 8; i++) s += cs[512 + i * 512 + tid];
    g_mod[n0 + tid] = mod_fin(s, n0 + tid);
    return;
  }
  const int bid = blockIdx.x - 4, h = bid >> 2, qb = bid & 3;
  TS(2, 0);
  if (tid == 0) { for (int i = 0; i < 8; i++) { mbar_init(bars + 8 * i, 1); mbar_expect(bars + 8 * i, 16384); } fence_init(); }
#pragma unroll
  for (int i = 0; i < 4; i++) *(uint4*)(smem + 131072 + i * 8192 + tid * 16) = make_uint4(0x3F803F80u, 0x3F803F80u, 0x3F803F80u, 0x3F803F80u);
  fence_async();
  cluster_sync();
  pdl_wait();
  TS(2, 1);
  if (tid >= 472) g_modv[bid * 40 + tid - 472] = 0;
  const uint4 km4 = *(const uint4*)(g_kmax + h * 128 + lane * 4);
  const uint32_t* qp = (const uint32_t*)g_qkv + (h * 2 * 2048 + qb * 512 + warp * 16 + g) * 4 + t;
  uint32_t q[4] = {qp[0], qp[32], qp[8192], qp[8192 + 32]};
  auto ldkv = [&]() {
    const int c = warp >> 1, pl = (qb & 1) + (warp & 1) * 2;
    bulk_load_mc(sK + pl * 32768 + c * 4096, g_qkv + ((64 + (pl >> 1) * 64 + h * 2 + (pl & 1)) * 2048 + c * 256) * 8, 4096, bars + 8 * c);
  };
  if (lane == 0 && warp < 4) ldkv();
  const uint32_t qn[4] = {qp[1024], qp[1024 + 32], qp[1024 + 8192], qp[1024 + 8192 + 32]};
  const float kmax = __uint_as_float(__reduce_max_sync(~0u, max(max(km4.x, km4.y), max(km4.z, km4.w))));
  if (lane == 0 && warp >= 4 && kmax != -1.f) ldkv();
#pragma unroll 1
  for (int tile = 0; tile < 2; tile++) {
    const int row = qb * 512 + tile * 256 + warp * 16 + g;
    const float n0 = qsum(blo(q[0]) * blo(q[0]) + bhi(q[0]) * bhi(q[0]) + blo(q[2]) * blo(q[2]) + bhi(q[2]) * bhi(q[2]));
    const float n1 = qsum(blo(q[1]) * blo(q[1]) + bhi(q[1]) * bhi(q[1]) + blo(q[3]) * blo(q[3]) + bhi(q[3]) * bhi(q[3]));
    const float b0 = sqrtf(n0 * kmax) * 1.001f, b1 = sqrtf(n1 * kmax) * 1.001f;
    const float m0 = fmaxf(ceilf(b0 - 100.f), 0.f), m1 = fmaxf(ceilf(b1 - 100.f), 0.f);
    float o[12], ob[12];
    attn_pass(o, ob, q, m0, m1, sK, bars, tile == 0, kz);
    const float f0 = ex2(-m0), f1 = ex2(-m1);
#pragma unroll
    for (int i = 0; i < 12; i++) o[i] = fmaf(o[i], (i & 2) ? f1 : f0, ob[i]);
    bool ok = b0 < 220.f && b1 < 220.f && o[8] >= 0x1p-90f && o[10] >= 0x1p-90f;
#pragma unroll
    for (int i = 0; i < 12; i++) ok = ok && fabsf(o[i]) < INFINITY;
    if (!__all_sync(~0u, ok)) attn_safe(o, q, sK);
    const float r0 = 1.f / o[8], r1 = 1.f / o[10];
    uint32_t* op = (uint32_t*)g_o + (((row >> 7) * 64 + h * 2) * 128 + (row & 127)) * 4 + t;
    op[0] = pack_rn(o[0] * r0, o[1] * r0); op[32] = pack_rn(o[2] * r1, o[3] * r1);
    op[512] = pack_rn(o[4] * r0, o[5] * r0); op[512 + 32] = pack_rn(o[6] * r1, o[7] * r1);
    if (tile == 0 && tid == 32) {
      l2_prefetch((const char*)wo + bid * 4096, 4096);
      l2_prefetch((const char*)w1 + bid * 11008, 11008);
      l2_prefetch((const char*)w3 + bid * 11008, 11008);
      l2_prefetch((const char*)w2 + bid * 11008, 11008);
    }
#pragma unroll
    for (int i = 0; i < 4; i++) q[i] = qn[i];
    TS(2, 3 + tile);
  }
}

constexpr int WO_SMEM = 131072 + 65536 + 256;
__global__ void __cluster_dims__(2, 1, 1) __launch_bounds__(256, 1) k_wo(const __grid_constant__ CUtensorMap mW, const bf16* __restrict__ x) {
  extern __shared__ __align__(1024) uint8_t smem[];
  const uint32_t sA = smem_u32(smem), sB = sA + 131072, bars = sB + 65536;
  const int tid = threadIdx.x, warp = tid >> 5, lane = tid & 31, g = lane >> 2, t = lane & 3;
  const int rb = blockIdx.x >> 3, ct = blockIdx.x & 7;
  TS(3, 0);
  pdl_launch();
  if (tid == 0) {
    for (int i = 0; i < 8; i++) mbar_init(bars + 8 * i, 1);
    fence_init();
    for (int i = 0; i < 8; i++) { mbar_expect(bars + 8 * i, 24576); tma2d(sB + i * 8192, &mW, ct * 64, i * 64, bars + 8 * i); }
  }
  __syncwarp();
  cluster_arrive();
  const int lrow = warp * 16 + g;
  uint32_t xr[16];
  const uint32_t* xp = (const uint32_t*)(x + (rb * 128 + lrow) * 512 + ct * 64) + t;
#pragma unroll
  for (int j = 0; j < 8; j++) { xr[2 * j] = __ldg(xp + j * 4); xr[2 * j + 1] = __ldg(xp + j * 4 + 8 * 256); }
  cluster_wait();
  pdl_wait();
  if (tid == 0) {
    for (int i = ct & 1; i < 8; i += 2) bulk_load_mc(sA + i * 16384, g_o + (rb * 64 + i * 8) * 1024, 16384, bars + 8 * i);
  }
  TS(3, 1);
  float2 ga[8];
#pragma unroll
  for (int j = 0; j < 8; j++) ga[j] = *(const float2*)(g_mod + 1024 + ct * 64 + j * 8 + t * 2);
  float acc[32];
  const uint64_t da = mk_desc(sA + (warp >> 2) * 1024, 2048, 128, 0), db = mk_desc(sB, 8192, 1024, 1);
#pragma unroll
  for (int c = 0; c < 8; c++) {
    mbar_wait(bars + 8 * c, 0);
    if (c == 0) TS(3, 2);
    wg_fence();
#pragma unroll
    for (int k = 0; k < 4; k++) wgmma_ss_n64_t1(acc, da + (c * 4 + k) * 256, db + (c * 4 + k) * 128, c + k);
    wg_commit();
  }
  wg_wait<0>();
  reg_fence(acc);
  TS(3, 3);
  uint32_t* o = (uint32_t*)g_x1 + ((rb * 64 + ct * 8) * 128 + lrow) * 4 + t;
  float s0 = 0, s1 = 0;
#pragma unroll
  for (int j = 0; j < 8; j++) {
    xr[2 * j] = pack_rn(fmaf(ga[j].x, acc[4 * j], blo(xr[2 * j])), fmaf(ga[j].y, acc[4 * j + 1], bhi(xr[2 * j])));
    xr[2 * j + 1] = pack_rn(fmaf(ga[j].x, acc[4 * j + 2], blo(xr[2 * j + 1])), fmaf(ga[j].y, acc[4 * j + 3], bhi(xr[2 * j + 1])));
    o[j * 512] = xr[2 * j]; o[j * 512 + 32] = xr[2 * j + 1];
    s0 += blo(xr[2 * j]) + bhi(xr[2 * j]); s1 += blo(xr[2 * j + 1]) + bhi(xr[2 * j + 1]);
  }
  const float m0 = qsum(s0) * (1.f / 64), m1 = qsum(s1) * (1.f / 64);
  float v0 = 0, v1 = 0;
#pragma unroll
  for (int j = 0; j < 8; j++) {
    float d;
    d = blo(xr[2 * j]) - m0; v0 += d * d; d = bhi(xr[2 * j]) - m0; v0 += d * d;
    d = blo(xr[2 * j + 1]) - m1; v1 += d * d; d = bhi(xr[2 * j + 1]) - m1; v1 += d * d;
  }
  v0 = qsum(v0); v1 = qsum(v1);
  if (t == 0) g_st[(rb * 128 + lrow) * 8 + ct] = make_float2(m0, v0);
  if (t == 1) g_st[(rb * 128 + lrow + 8) * 8 + ct] = make_float2(m1, v1);
  TS(3, 4);
}

constexpr int W2_SMEM = 6 * 32768 + 32768 + 256;
__global__ void __cluster_dims__(2, 1, 1) __launch_bounds__(288, 1) k_w2(const __grid_constant__ CUtensorMap mW, bf16* __restrict__ out) {
  extern __shared__ __align__(1024) uint8_t smem[];
  const uint32_t sR = smem_u32(smem), sX = sR + 6 * 32768, bF = sX + 32768, bE = bF + 48, bX = bF + 96;
  const int tid = threadIdx.x, warp = tid >> 5, lane = tid & 31, g = lane >> 2, t = lane & 3;
  const int kh = blockIdx.x & 1, ct = (blockIdx.x >> 1) & 3, rb = blockIdx.x >> 3;
  TS(5, 0);
  pdl_launch();
  if (tid == 256) {
    for (int i = 0; i < 6; i++) { mbar_init(bF + 8 * i, 1); mbar_init(bE + 8 * i, 8); }
    for (int i = 0; i < 8; i++) { mbar_init(bX + 8 * i, 1); mbar_expect(bX + 8 * i, 4096); }
    fence_init();
  }
  __syncthreads();
  asm volatile("barrier.cluster.arrive.relaxed.aligned;" ::: "memory");
  if (warp == 8) {
    if (lane == 0) {
      auto abytes = [&](int s) { return (kh == 1 && s == 10) ? 8192 : 16384; };
      auto loadB = [&](int s) {
        const int st = s % 6;
        mbar_expect(bF + 8 * st, 16384 + abytes(s));
        for (int j = 0; j < 2; j++) tma2d(sR + st * 32768 + 16384 + j * 8192, &mW, ct * 128 + j * 64, kh * 704 + s * 64, bF + 8 * st);
      };
      auto loadA = [&](int s) { bulk_load(sR + (s % 6) * 32768, g_h + (rb * 172 + kh * 88 + s * 8) * 1024, abytes(s), bF + 8 * (s % 6)); };
      for (int s = 0; s < 6; s++) loadB(s);
      pdl_wait();
      for (int s = 0; s < 6; s++) loadA(s);
      for (int s = 6; s < 11; s++) { mbar_wait(bE + 8 * (s - 6), 0); loadB(s); loadA(s); }
    }
    __syncwarp();
    cluster_wait();
    return;
  }
  pdl_wait();
  TS(5, 1);
  const int lrow = warp * 16 + g;
  uint32_t xr[16];
  float2 gb[8];
  const uint32_t* xp = (const uint32_t*)g_x1 + ((rb * 64 + ct * 16 + kh * 8) * 128 + lrow) * 4 + t;
#pragma unroll
  for (int j = 0; j < 8; j++) {
    xr[2 * j] = xp[j * 512]; xr[2 * j + 1] = xp[j * 512 + 32];
    gb[j] = *(const float2*)(g_mod + 2560 + ct * 128 + kh * 64 + j * 8 + t * 2);
  }
  float acc[64];
#pragma unroll 1
  for (int s = 0; s < 11; s++) {
    const int st = s % 6;
    mbar_wait(bF + 8 * st, s >= 6);
    const uint64_t da = mk_desc(sR + st * 32768 + (warp >> 2) * 1024, 2048, 128, 0), db = mk_desc(sR + st * 32768 + 16384, 8192, 1024, 1);
    if (s == 0) TS(5, 2);
    wg_fence();
    wgmma_ss_n128_t1(acc, da, db, s);
    wgmma_ss_n128_t1(acc, da + 256, db + 128, 1);
    wgmma_ss_n128_t1(acc, da + 512, db + 256, 1);
    wgmma_ss_n128_t1(acc, da + 768, db + 384, 1);
    wg_commit();
    wg_wait<1>();
    if (s > 0 && s < 6 && lane == 0) mbar_arrive(bE + 8 * (s - 1));
  }
  wg_wait<0>();
  reg_fence(acc);
  TS(5, 3);
  asm volatile("barrier.cluster.wait.aligned;" ::: "memory");
  uint32_t rem, rbar;
  asm("mapa.shared::cluster.u32 %0,%1,%2;" : "=r"(rbar) : "r"(bX + warp * 8), "r"(kh ^ 1));
  asm("mapa.shared::cluster.u32 %0,%1,%2;" : "=r"(rem) : "r"(sX + warp * 4096 + lane * 16), "r"(kh ^ 1));
#pragma unroll
  for (int j = 0; j < 8; j++) {
    float v[4];
#pragma unroll
    for (int i = 0; i < 4; i++) { v[i] = kh ? acc[4 * j + i] : acc[32 + 4 * j + i]; acc[4 * j + i] = kh ? acc[32 + 4 * j + i] : acc[4 * j + i]; }
    asm volatile("st.async.weak.shared::cluster.mbarrier::complete_tx::bytes.v4.f32 [%0],{%1,%2,%3,%4},[%5];" ::"r"(rem + j * 512), "f"(v[0]), "f"(v[1]), "f"(v[2]), "f"(v[3]), "r"(rbar) : "memory");
  }
  mbar_wait(bX + warp * 8, 0);
  TS(5, 5);
  const uint32_t sw = sX + warp * 4096;
#pragma unroll
  for (int j = 0; j < 8; j++) {
    const float4 p = *(const float4*)(smem + 6 * 32768 + warp * 4096 + j * 512 + lane * 16);
    xr[2 * j] = pack_rn(fmaf(gb[j].x, acc[4 * j] + p.x, blo(xr[2 * j])), fmaf(gb[j].y, acc[4 * j + 1] + p.y, bhi(xr[2 * j])));
    xr[2 * j + 1] = pack_rn(fmaf(gb[j].x, acc[4 * j + 2] + p.z, blo(xr[2 * j + 1])), fmaf(gb[j].y, acc[4 * j + 3] + p.w, bhi(xr[2 * j + 1])));
  }
  __syncwarp();
#pragma unroll
  for (int j = 1; j < 8; j += 2) {
    asm volatile("stmatrix.sync.aligned.m8n8.x4.shared.b16 [%0],{%1,%2,%3,%4};" ::"r"(sw + (lane & 15) * 128 + (((j - 1 + (lane >> 4)) ^ (lane & 7)) << 4)),
                            "r"(xr[2 * j - 2]), "r"(xr[2 * j - 1]), "r"(xr[2 * j]), "r"(xr[2 * j + 1]) : "memory");
  }
  __syncwarp();
#pragma unroll
  for (int i = 0; i < 4; i++) {
    const int r = i * 4 + (lane >> 3);
    *(uint4*)(out + (rb * 128 + warp * 16 + r) * 512 + ct * 128 + kh * 64 + (lane & 7) * 8) = *(const uint4*)(smem + 6 * 32768 + warp * 4096 + r * 128 + (((lane ^ r) & 7) << 4));
  }
  TS(5, 4);
}

typedef CUresult (*EncFn)(CUtensorMap*, CUtensorMapDataType, cuuint32_t, void*, const cuuint64_t*, const cuuint64_t*, const cuuint32_t*,
                          const cuuint32_t*, CUtensorMapInterleave, CUtensorMapSwizzle, CUtensorMapL2promotion, CUtensorMapFloatOOBfill);
static void mk_map(EncFn f, CUtensorMap* m, const void* p, int rows, int cols, int box_rows) {
  cuuint64_t dim[2] = {(cuuint64_t)cols, (cuuint64_t)rows}, str[1] = {(cuuint64_t)cols * 2};
  cuuint32_t box[2] = {64, (cuuint32_t)box_rows}, es[2] = {1, 1};
  f(m, CU_TENSOR_MAP_DATA_TYPE_BFLOAT16, 2, (void*)p, dim, str, box, es, CU_TENSOR_MAP_INTERLEAVE_NONE, CU_TENSOR_MAP_SWIZZLE_128B,
    CU_TENSOR_MAP_L2_PROMOTION_L2_128B, CU_TENSOR_MAP_FLOAT_OOB_FILL_NONE);
}
template <typename... KA, typename... A>
static void launch(void (*k)(KA...), int grid, int block, int smem, bool pdl, A... args) {
  cudaLaunchConfig_t cfg = {};
  cfg.gridDim = dim3(grid); cfg.blockDim = dim3(block); cfg.dynamicSmemBytes = smem; cfg.stream = cudaStreamPerThread;
  cudaLaunchAttribute at[1];
  at[0].id = cudaLaunchAttributeProgrammaticStreamSerialization; at[0].val.programmaticStreamSerializationAllowed = 1;
  cfg.attrs = at; cfg.numAttrs = pdl ? 1 : 0;
  cudaLaunchKernelEx(&cfg, k, args...);
}
extern "C" void kernel_launch(void* const* d_in, const int* in_sizes, int n_in, void* d_out, int out_size) {
  const bf16 *x = (const bf16*)d_in[0], *wqkv = (const bf16*)d_in[1], *wo = (const bf16*)d_in[2], *w1 = (const bf16*)d_in[4],
             *w3 = (const bf16*)d_in[5], *w2 = (const bf16*)d_in[6], *c = (const bf16*)d_in[7], *wmod = (const bf16*)d_in[8];
  void* fp = nullptr;
  cudaDriverEntryPointQueryResult qr;
  cudaGetDriverEntryPoint("cuTensorMapEncodeTiled", &fp, cudaEnableDefault, &qr);
  EncFn f = (EncFn)fp;
  CUtensorMap mX, mQ, mO, m1, m3, m2;
  mk_map(f, &mX, x, S_, D_, 128); mk_map(f, &mQ, wqkv, D_, 3 * D_, 64); mk_map(f, &mO, wo, D_, D_, 64);
  mk_map(f, &m1, w1, D_, F_, 32); mk_map(f, &m3, w3, D_, F_, 32); mk_map(f, &m2, w2, F_, D_, 64);
  cudaFuncSetAttribute(k_lngemm<false>, cudaFuncAttributeMaxDynamicSharedMemorySize, LN_SMEM);
  cudaFuncSetAttribute(k_lngemm<true>, cudaFuncAttributeMaxDynamicSharedMemorySize, LN_SMEM);
  cudaFuncSetAttribute(k_attn, cudaFuncAttributeMaxDynamicSharedMemorySize, AT_SMEM);
  cudaFuncSetAttribute(k_wo, cudaFuncAttributeMaxDynamicSharedMemorySize, WO_SMEM);
  cudaFuncSetAttribute(k_w2, cudaFuncAttributeMaxDynamicSharedMemorySize, W2_SMEM);
  launch(k_lngemm<false>, 128, 384, LN_SMEM, false, mX, mQ, mQ, c, wmod, x);
  launch(k_attn, 132, 512, AT_SMEM, true, wo, w1, w3, w2, c, wmod, 0u);
  launch(k_wo, 128, 256, WO_SMEM, true, mO, x);
  launch(k_lngemm<true>, 128, 384, LN_SMEM, true, mX, m1, m3, c, wmod, x);
  launch(k_w2, 128, 288, W2_SMEM, true, m2, (bf16*)d_out);
}
```

```cpp
#include <cuda_runtime.h>
#include <cuda_bf16.h>
#include <cuda.h>
#include <stdint.h>
typedef __nv_bfloat16 bf16;
constexpr int S_ = 2048, D_ = 512, F_ = 1376;
__device__ __align__(1024) float g_mod[3072];
__device__ __align__(1024) uint32_t g_modv[1024 + 4096];
__device__ __align__(1024) bf16 g_qkv[192 * 2048 * 8];
__device__ __align__(1024) float g_kmax[32 * 128];
__device__ __align__(1024) bf16 g_o[16 * 64 * 128 * 8];
__device__ __align__(1024) bf16 g_x1[16 * 64 * 128 * 8];
__device__ __align__(1024) float2 g_st[2048 * 8];
__device__ __align__(1024) bf16 g_h[16 * 172 * 128 * 8];

__device__ __forceinline__ uint32_t smem_u32(const void* p) { return (uint32_t)__cvta_generic_to_shared(p); }
__device__ __forceinline__ void mbar_init(uint32_t b, int n) { asm volatile("mbarrier.init.shared::cta.b64 [%0],%1;" ::"r"(b), "r"(n) : "memory"); }
__device__ __forceinline__ void mbar_expect(uint32_t b, int bytes) { asm volatile("mbarrier.arrive.expect_tx.shared::cta.b64 _,[%0],%1;" ::"r"(b), "r"(bytes) : "memory"); }
__device__ __forceinline__ void mbar_arrive(uint32_t b) { asm volatile("mbarrier.arrive.shared::cta.b64 _,[%0];" ::"r"(b) : "memory"); }
__device__ __forceinline__ void mbar_wait(uint32_t b, int parity) {
  asm volatile("{\n.reg .pred p;\n.reg .u32 n;\nmov.u32 n,0;\nLW:\nmbarrier.try_wait.parity.shared::cta.b64 p,[%0],%1;\n@p bra LD;\n"
               "add.u32 n,n,1;\nsetp.lt.u32 p,n,4194304;\n@p bra LW;\nLD:\n}\n" ::"r"(b), "r"(parity) : "memory");
}
__device__ __forceinline__ void fence_init() { asm volatile("fence.mbarrier_init.release.cluster;" ::: "memory"); }
__device__ __forceinline__ void fence_async() { asm volatile("fence.proxy.async.shared::cta;" ::: "memory"); }
__device__ __forceinline__ void bulk_load(uint32_t dst, const void* src, int bytes, uint32_t bar) {
  asm volatile("cp.async.bulk.shared::cluster.global.mbarrier::complete_tx::bytes [%0],[%1],%2,[%3];" ::"r"(dst), "l"(src), "r"(bytes), "r"(bar) : "memory");
}
__device__ __forceinline__ void tma2d(uint32_t dst, const CUtensorMap* m, int c0, int c1, uint32_t bar) {
  asm volatile("cp.async.bulk.tensor.2d.shared::cluster.global.mbarrier::complete_tx::bytes [%0],[%1,{%3,%4}],[%2];" ::"r"(dst), "l"(m), "r"(bar), "r"(c0), "r"(c1) : "memory");
}
__device__ __forceinline__ void bulk_load_mc(uint32_t dst, const void* src, int bytes, uint32_t bar) {
  asm volatile("cp.async.bulk.shared::cluster.global.mbarrier::complete_tx::bytes.multicast::cluster [%0],[%1],%2,[%3],%4;" ::"r"(dst), "l"(src), "r"(bytes), "r"(bar), "h"((uint16_t)3) : "memory");
}
__device__ __forceinline__ void tma2d_mc(uint32_t dst, const CUtensorMap* m, int c0, int c1, uint32_t bar) {
  asm volatile("cp.async.bulk.tensor.2d.shared::cluster.global.mbarrier::complete_tx::bytes.multicast::cluster [%0],[%1,{%3,%4}],[%2],%5;" ::"r"(dst), "l"(m), "r"(bar), "r"(c0), "r"(c1), "h"((uint16_t)3) : "memory");
}
__device__ __forceinline__ void cluster_arrive() { asm volatile("barrier.cluster.arrive.relaxed.aligned;" ::: "memory"); }
__device__ __forceinline__ void cluster_wait() { asm volatile("barrier.cluster.wait.aligned;" ::: "memory"); }
__device__ __forceinline__ void cluster_sync() { asm volatile("barrier.cluster.arrive.release.aligned;\nbarrier.cluster.wait.acquire.aligned;" ::: "memory"); }
__device__ __forceinline__ void l2_prefetch(const void* p, int bytes) { asm volatile("cp.async.bulk.prefetch.L2.global [%0],%1;" ::"l"(p), "r"(bytes) : "memory"); }
__device__ __forceinline__ void pdl_launch() { asm volatile("griddepcontrol.launch_dependents;" ::: "memory"); }
__device__ __forceinline__ void pdl_wait() { asm volatile("griddepcontrol.wait;" ::: "memory"); }
__device__ __forceinline__ void wg_fence() { asm volatile("wgmma.fence.sync.aligned;" ::: "memory"); }
__device__ __forceinline__ void wg_commit() { asm volatile("wgmma.commit_group.sync.aligned;" ::: "memory"); }
template <int N> __device__ __forceinline__ void wg_wait() { asm volatile("wgmma.wait_group.sync.aligned %0;" ::"n"(N) : "memory"); }
template <int N> __device__ __forceinline__ void reg_fence(float (&d)[N]) {
#pragma unroll
  for (int i = 0; i < N; i++) asm volatile("" : "+f"(d[i])::"memory");
}
template <int N> __device__ __forceinline__ void zero(float (&d)[N]) {
#pragma unroll
  for (int i = 0; i < N; i++) d[i] = 0.f;
  reg_fence(d);
}
__device__ __forceinline__ uint64_t mk_desc(uint32_t addr, uint32_t lbo, uint32_t sbo, uint32_t mode) {
  return (uint64_t)((addr >> 4) & 0x3FFF) | ((uint64_t)(lbo >> 4) << 16) | ((uint64_t)(sbo >> 4) << 32) | ((uint64_t)mode << 62);
}
__device__ __forceinline__ void ldsm4(uint32_t a, uint32_t (&r)[4]) {
  asm volatile("ldmatrix.sync.aligned.m8n8.x4.shared.b16 {%0,%1,%2,%3},[%4];" : "=r"(r[0]), "=r"(r[1]), "=r"(r[2]), "=r"(r[3]) : "r"(a) : "memory");
}
__device__ __forceinline__ uint32_t pack_rn(float lo, float hi) { uint32_t r; asm("cvt.rn.bf16x2.f32 %0,%1,%2;" : "=r"(r) : "f"(hi), "f"(lo)); return r; }
__device__ __forceinline__ uint32_t pack_rz(float lo, float hi) { uint32_t r; asm("cvt.rz.bf16x2.f32 %0,%1,%2;" : "=r"(r) : "f"(hi), "f"(lo)); return r; }
__device__ __forceinline__ float blo(uint32_t u) { return __uint_as_float(u << 16); }
__device__ __forceinline__ float bhi(uint32_t u) { return __uint_as_float(u & 0xFFFF0000u); }
__device__ __forceinline__ float rbf(float x) { return __bfloat162float(__float2bfloat16_rn(x)); }
__device__ __forceinline__ float qsum(float v) { v += __shfl_xor_sync(~0u, v, 1); return v + __shfl_xor_sync(~0u, v, 2); }
__device__ __forceinline__ float ex2(float x) { float r; asm("ex2.approx.ftz.f32 %0,%1;" : "=f"(r) : "f"(x)); return r; }
#define TS(k, i)
__device__ __forceinline__ void wgmma_rs_n176_t1(float (&d)[88],uint32_t a0,uint32_t a1,uint32_t a2,uint32_t a3,uint64_t db,int sc){
  asm volatile("{\n.reg .pred p;\nsetp.ne.b32 p,%93,0;\n"
    "wgmma.mma_async.sync.aligned.m64n176k16.f32.bf16.bf16 {%0,%1,%2,%3,%4,%5,%6,%7,%8,%9,%10,%11,%12,%13,%14,%15,%16,%17,%18,%19,%20,%21,%22,%23,%24,%25,%26,%27,%28,%29,%30,%31,%32,%33,%34,%35,%36,%37,%38,%39,%40,%41,%42,%43,%44,%45,%46,%47,%48,%49,%50,%51,%52,%53,%54,%55,%56,%57,%58,%59,%60,%61,%62,%63,%64,%65,%66,%67,%68,%69,%70,%71,%72,%73,%74,%75,%76,%77,%78,%79,%80,%81,%82,%83,%84,%85,%86,%87},{%88,%89,%90,%91},%92,p,1,1,1;\n}\n"
    :"+f"(d[0]),"+f"(d[1]),"+f"(d[2]),"+f"(d[3]),"+f"(d[4]),"+f"(d[5]),"+f"(d[6]),"+f"(d[7]),"+f"(d[8]),"+f"(d[9]),"+f"(d[10]),"+f"(d[11]),"+f"(d[12]),"+f"(d[13]),"+f"(d[14]),"+f"(d[15]),"+f"(d[16]),"+f"(d[17]),"+f"(d[18]),"+f"(d[19]),"+f"(d[20]),"+f"(d[21]),"+f"(d[22]),"+f"(d[23]),"+f"(d[24]),"+f"(d[25]),"+f"(d[26]),"+f"(d[27]),"+f"(d[28]),"+f"(d[29]),"+f"(d[30]),"+f"(d[31]),"+f"(d[32]),"+f"(d[33]),"+f"(d[34]),"+f"(d[35]),"+f"(d[36]),"+f"(d[37]),"+f"(d[38]),"+f"(d[39]),"+f"(d[40]),"+f"(d[41]),"+f"(d[42]),"+f"(d[43]),"+f"(d[44]),"+f"(d[45]),"+f"(d[46]),"+f"(d[47]),"+f"(d[48]),"+f"(d[49]),"+f"(d[50]),"+f"(d[51]),"+f"(d[52]),"+f"(d[53]),"+f"(d[54]),"+f"(d[55]),"+f"(d[56]),"+f"(d[57]),"+f"(d[58]),"+f"(d[59]),"+f"(d[60]),"+f"(d[61]),"+f"(d[62]),"+f"(d[63]),"+f"(d[64]),"+f"(d[65]),"+f"(d[66]),"+f"(d[67]),"+f"(d[68]),"+f"(d[69]),"+f"(d[70]),"+f"(d[71]),"+f"(d[72]),"+f"(d[73]),"+f"(d[74]),"+f"(d[75]),"+f"(d[76]),"+f"(d[77]),"+f"(d[78]),"+f"(d[79]),"+f"(d[80]),"+f"(d[81]),"+f"(d[82]),"+f"(d[83]),"+f"(d[84]),"+f"(d[85]),"+f"(d[86]),"+f"(d[87])
    :"r"(a0),"r"(a1),"r"(a2),"r"(a3),"l"(db),"r"(sc));
}
__device__ __forceinline__ void wgmma_rs_n192_t1(float (&d)[96],uint32_t a0,uint32_t a1,uint32_t a2,uint32_t a3,uint64_t db,int sc){
  asm volatile("{\n.reg .pred p;\nsetp.ne.b32 p,%101,0;\n"
    "wgmma.mma_async.sync.aligned.m64n192k16.f32.bf16.bf16 {%0,%1,%2,%3,%4,%5,%6,%7,%8,%9,%10,%11,%12,%13,%14,%15,%16,%17,%18,%19,%20,%21,%22,%23,%24,%25,%26,%27,%28,%29,%30,%31,%32,%33,%34,%35,%36,%37,%38,%39,%40,%41,%42,%43,%44,%45,%46,%47,%48,%49,%50,%51,%52,%53,%54,%55,%56,%57,%58,%59,%60,%61,%62,%63,%64,%65,%66,%67,%68,%69,%70,%71,%72,%73,%74,%75,%76,%77,%78,%79,%80,%81,%82,%83,%84,%85,%86,%87,%88,%89,%90,%91,%92,%93,%94,%95},{%96,%97,%98,%99},%100,p,1,1,1;\n}\n"
    :"+f"(d[0]),"+f"(d[1]),"+f"(d[2]),"+f"(d[3]),"+f"(d[4]),"+f"(d[5]),"+f"(d[6]),"+f"(d[7]),"+f"(d[8]),"+f"(d[9]),"+f"(d[10]),"+f"(d[11]),"+f"(d[12]),"+f"(d[13]),"+f"(d[14]),"+f"(d[15]),"+f"(d[16]),"+f"(d[17]),"+f"(d[18]),"+f"(d[19]),"+f"(d[20]),"+f"(d[21]),"+f"(d[22]),"+f"(d[23]),"+f"(d[24]),"+f"(d[25]),"+f"(d[26]),"+f"(d[27]),"+f"(d[28]),"+f"(d[29]),"+f"(d[30]),"+f"(d[31]),"+f"(d[32]),"+f"(d[33]),"+f"(d[34]),"+f"(d[35]),"+f"(d[36]),"+f"(d[37]),"+f"(d[38]),"+f"(d[39]),"+f"(d[40]),"+f"(d[41]),"+f"(d[42]),"+f"(d[43]),"+f"(d[44]),"+f"(d[45]),"+f"(d[46]),"+f"(d[47]),"+f"(d[48]),"+f"(d[49]),"+f"(d[50]),"+f"(d[51]),"+f"(d[52]),"+f"(d[53]),"+f"(d[54]),"+f"(d[55]),"+f"(d[56]),"+f"(d[57]),"+f"(d[58]),"+f"(d[59]),"+f"(d[60]),"+f"(d[61]),"+f"(d[62]),"+f"(d[63]),"+f"(d[64]),"+f"(d[65]),"+f"(d[66]),"+f"(d[67]),"+f"(d[68]),"+f"(d[69]),"+f"(d[70]),"+f"(d[71]),"+f"(d[72]),"+f"(d[73]),"+f"(d[74]),"+f"(d[75]),"+f"(d[76]),"+f"(d[77]),"+f"(d[78]),"+f"(d[79]),"+f"(d[80]),"+f"(d[81]),"+f"(d[82]),"+f"(d[83]),"+f"(d[84]),"+f"(d[85]),"+f"(d[86]),"+f"(d[87]),"+f"(d[88]),"+f"(d[89]),"+f"(d[90]),"+f"(d[91]),"+f"(d[92]),"+f"(d[93]),"+f"(d[94]),"+f"(d[95])
    :"r"(a0),"r"(a1),"r"(a2),"r"(a3),"l"(db),"r"(sc));
}
__device__ __forceinline__ void wgmma_rs_n24_t1(float (&d)[12],uint32_t a0,uint32_t a1,uint32_t a2,uint32_t a3,uint64_t db,int sc){
  asm volatile("{\n.reg .pred p;\nsetp.ne.b32 p,%17,0;\n"
    "wgmma.mma_async.sync.aligned.m64n24k16.f32.bf16.bf16 {%0,%1,%2,%3,%4,%5,%6,%7,%8,%9,%10,%11},{%12,%13,%14,%15},%16,p,1,1,1;\n}\n"
    :"+f"(d[0]),"+f"(d[1]),"+f"(d[2]),"+f"(d[3]),"+f"(d[4]),"+f"(d[5]),"+f"(d[6]),"+f"(d[7]),"+f"(d[8]),"+f"(d[9]),"+f"(d[10]),"+f"(d[11])
    :"r"(a0),"r"(a1),"r"(a2),"r"(a3),"l"(db),"r"(sc));
}
__device__ __forceinline__ void wgmma_rs_n64_t0(float (&d)[32],uint32_t a0,uint32_t a1,uint32_t a2,uint32_t a3,uint64_t db,int sc){
  asm volatile("{\n.reg .pred p;\nsetp.ne.b32 p,%37,0;\n"
    "wgmma.mma_async.sync.aligned.m64n64k16.f32.bf16.bf16 {%0,%1,%2,%3,%4,%5,%6,%7,%8,%9,%10,%11,%12,%13,%14,%15,%16,%17,%18,%19,%20,%21,%22,%23,%24,%25,%26,%27,%28,%29,%30,%31},{%32,%33,%34,%35},%36,p,1,1,0;\n}\n"
    :"+f"(d[0]),"+f"(d[1]),"+f"(d[2]),"+f"(d[3]),"+f"(d[4]),"+f"(d[5]),"+f"(d[6]),"+f"(d[7]),"+f"(d[8]),"+f"(d[9]),"+f"(d[10]),"+f"(d[11]),"+f"(d[12]),"+f"(d[13]),"+f"(d[14]),"+f"(d[15]),"+f"(d[16]),"+f"(d[17]),"+f"(d[18]),"+f"(d[19]),"+f"(d[20]),"+f"(d[21]),"+f"(d[22]),"+f"(d[23]),"+f"(d[24]),"+f"(d[25]),"+f"(d[26]),"+f"(d[27]),"+f"(d[28]),"+f"(d[29]),"+f"(d[30]),"+f"(d[31])
    :"r"(a0),"r"(a1),"r"(a2),"r"(a3),"l"(db),"r"(sc));
}
__device__ __forceinline__ void wgmma_ss_n128_t1(float (&d)[64],uint64_t da,uint64_t db,int sc){
  asm volatile("{\n.reg .pred p;\nsetp.ne.b32 p,%66,0;\n"
    "wgmma.mma_async.sync.aligned.m64n128k16.f32.bf16.bf16 {%0,%1,%2,%3,%4,%5,%6,%7,%8,%9,%10,%11,%12,%13,%14,%15,%16,%17,%18,%19,%20,%21,%22,%23,%24,%25,%26,%27,%28,%29,%30,%31,%32,%33,%34,%35,%36,%37,%38,%39,%40,%41,%42,%43,%44,%45,%46,%47,%48,%49,%50,%51,%52,%53,%54,%55,%56,%57,%58,%59,%60,%61,%62,%63},%64,%65,p,1,1,0,1;\n}\n"
    :"+f"(d[0]),"+f"(d[1]),"+f"(d[2]),"+f"(d[3]),"+f"(d[4]),"+f"(d[5]),"+f"(d[6]),"+f"(d[7]),"+f"(d[8]),"+f"(d[9]),"+f"(d[10]),"+f"(d[11]),"+f"(d[12]),"+f"(d[13]),"+f"(d[14]),"+f"(d[15]),"+f"(d[16]),"+f"(d[17]),"+f"(d[18]),"+f"(d[19]),"+f"(d[20]),"+f"(d[21]),"+f"(d[22]),"+f"(d[23]),"+f"(d[24]),"+f"(d[25]),"+f"(d[26]),"+f"(d[27]),"+f"(d[28]),"+f"(d[29]),"+f"(d[30]),"+f"(d[31]),"+f"(d[32]),"+f"(d[33]),"+f"(d[34]),"+f"(d[35]),"+f"(d[36]),"+f"(d[37]),"+f"(d[38]),"+f"(d[39]),"+f"(d[40]),"+f"(d[41]),"+f"(d[42]),"+f"(d[43]),"+f"(d[44]),"+f"(d[45]),"+f"(d[46]),"+f"(d[47]),"+f"(d[48]),"+f"(d[49]),"+f"(d[50]),"+f"(d[51]),"+f"(d[52]),"+f"(d[53]),"+f"(d[54]),"+f"(d[55]),"+f"(d[56]),"+f"(d[57]),"+f"(d[58]),"+f"(d[59]),"+f"(d[60]),"+f"(d[61]),"+f"(d[62]),"+f"(d[63])
    :"l"(da),"l"(db),"r"(sc));
}
__device__ __forceinline__ void wgmma_ss_n64_t1(float (&d)[32],uint64_t da,uint64_t db,int sc){
  asm volatile("{\n.reg .pred p;\nsetp.ne.b32 p,%34,0;\n"
    "wgmma.mma_async.sync.aligned.m64n64k16.f32.bf16.bf16 {%0,%1,%2,%3,%4,%5,%6,%7,%8,%9,%10,%11,%12,%13,%14,%15,%16,%17,%18,%19,%20,%21,%22,%23,%24,%25,%26,%27,%28,%29,%30,%31},%32,%33,p,1,1,0,1;\n}\n"
    :"+f"(d[0]),"+f"(d[1]),"+f"(d[2]),"+f"(d[3]),"+f"(d[4]),"+f"(d[5]),"+f"(d[6]),"+f"(d[7]),"+f"(d[8]),"+f"(d[9]),"+f"(d[10]),"+f"(d[11]),"+f"(d[12]),"+f"(d[13]),"+f"(d[14]),"+f"(d[15]),"+f"(d[16]),"+f"(d[17]),"+f"(d[18]),"+f"(d[19]),"+f"(d[20]),"+f"(d[21]),"+f"(d[22]),"+f"(d[23]),"+f"(d[24]),"+f"(d[25]),"+f"(d[26]),"+f"(d[27]),"+f"(d[28]),"+f"(d[29]),"+f"(d[30]),"+f"(d[31])
    :"l"(da),"l"(db),"r"(sc));
}

__device__ __forceinline__ float silu_bf(bf16 c) { const float x = __bfloat162float(c); return rbf(x / (1.f + __expf(-x))); }
__device__ __forceinline__ void fma8(float (&a)[8], float s, const uint4& v) {
  a[0] += s * blo(v.x); a[1] += s * bhi(v.x); a[2] += s * blo(v.y); a[3] += s * bhi(v.y);
  a[4] += s * blo(v.z); a[5] += s * bhi(v.z); a[6] += s * blo(v.w); a[7] += s * bhi(v.w);
}
__device__ __forceinline__ float red8(float (&a)[8], int lane) {
#pragma unroll
  for (int w = 4; w >= 1; w >>= 1) {
    const bool up = lane & (w * 4);
#pragma unroll
    for (int j = 0; j < w; j++) a[j] = (up ? a[j + w] : a[j]) + __shfl_xor_sync(~0u, up ? a[j] : a[j + w], w * 4);
  }
  return a[0];
}
__device__ __forceinline__ float mod_fin(float s, int n) { s = rbf(s); return ((n >> 9) == 1 || (n >> 9) == 4) ? rbf(1.f + s) : s; }
__device__ __forceinline__ void poll4(uint2& a, uint2& b, uint2& c, uint2& d, const uint32_t* p, const uint32_t* q) {
  asm volatile("{\n.reg .pred p;\n.reg .u32 n,t;\nmov.u32 n,0;\nLW:\nld.relaxed.gpu.global.v2.u32 {%0,%1},[%8];\nld.relaxed.gpu.global.v2.u32 {%2,%3},[%8+64];\n"
               "ld.relaxed.gpu.global.v2.u32 {%4,%5},[%9];\nld.relaxed.gpu.global.v2.u32 {%6,%7},[%9+2048];\n"
               "lop3.b32 t,%0,%1,%2,0x80;\nlop3.b32 t,t,%3,%4,0x80;\nlop3.b32 t,t,%5,%6,0x80;\nlop3.b32 t,t,%7,1,0x80;\n"
               "setp.ne.u32 p,t,0;\n@p bra LD;\nadd.u32 n,n,1;\nsetp.lt.u32 p,n,1048576;\n@p bra LW;\nLD:\n}\n"
               : "=&r"(a.x), "=&r"(a.y), "=&r"(b.x), "=&r"(b.y), "=&r"(c.x), "=&r"(c.y), "=&r"(d.x), "=&r"(d.y) : "l"(p), "l"(q) : "memory");
}

constexpr int LN_SMEM = 131072 + 4 * 24576 + 2048 + 256 + 512;
template <bool FFN>
__global__ void __cluster_dims__(2, 1, 1) __launch_bounds__(384, 1) k_lngemm(const __grid_constant__ CUtensorMap mX, const __grid_constant__ CUtensorMap mB0,
                                                   const __grid_constant__ CUtensorMap mB1, const bf16* __restrict__ cv, const bf16* __restrict__ wm, const bf16* __restrict__ xg) {
  extern __shared__ __align__(1024) uint8_t smem[];
  const uint32_t sA = smem_u32(smem), sB = sA + (FFN ? 81920 : 131072), sM = sA + 229376, bars = sM + 2048;
  const uint32_t bA = bars, bF = bars + 64, bE = bars + 112;
  constexpr int NB = FFN ? 6 : 4;
  const int tid = threadIdx.x, warp = tid >> 5, lane = tid & 31;
  const int pr = blockIdx.x & 1, rb = FFN ? (blockIdx.x >> 4) * 2 + pr : blockIdx.x >> 3, ct = FFN ? (blockIdx.x >> 1) & 7 : blockIdx.x & 7;
  constexpr int NST = FFN ? 16 : 8, KS = FFN ? 2 : 4, BOX = FFN ? 4096 : 8192;
  TS(FFN ? 4 : 1, 0);
  pdl_launch();
  float* red = (float*)(smem + (bars - sA) + 256);
  if (tid == 256) {
    for (int i = 0; i < 8; i++) mbar_init(bA + 8 * i, 1);
    for (int i = 0; i < NB; i++) { mbar_init(bF + 8 * i, 1); mbar_init(bE + 8 * i, FFN ? 16 : 8); }
    fence_init();
  }
  __syncwarp();
  cluster_arrive();
  uint4 wv0, wv1, xv[4];
  bf16 cv0, cv1;
  if (!FFN && tid < 256) {
    wv0 = __ldg((const uint4*)(wm + tid * 3072 + blockIdx.x * 8)); wv1 = __ldg((const uint4*)(wm + (tid + 256) * 3072 + blockIdx.x * 8));
    cv0 = cv[tid]; cv1 = cv[tid + 256];
#pragma unroll
    for (int i = 0; i < 4; i++) xv[i] = __ldg((const uint4*)(xg + (blockIdx.x * 16 + (tid >> 4)) * 512 + i * 128 + (tid & 15) * 8));
  }
  cluster_wait();
  if (warp >= 8) {
    asm volatile("setmaxnreg.dec.sync.aligned.u32 40;");
    if (tid == 256) {
      auto loadB = [&](int s) {
        const uint32_t d = sB + (s % NB) * 24576, b = bF + (s % NB) * 8;
        mbar_expect(b, 24576);
        for (int j = 0; j < 3; j++) {
          if (FFN) tma2d_mc(d + (pr * 3 + j) * BOX, pr ? &mB1 : &mB0, ct * 176 + j * 64, s * 32, b);
          else tma2d(d + j * BOX, &mB0, ct * 192 + j * 64, s * 64, b);
        }
      };
      for (int i = 0; i < 8; i++) mbar_expect(bA + 8 * i, 16384);
      for (int s = 0; s < NB; s++) {
        const int i = s * 2 + (ct & 1);
        if (!FFN) tma2d_mc(sA + i * 16384, &mX, i * 64, rb * 128, bA + 8 * i);
        loadB(s);
      }
      if (FFN) {
        pdl_wait();
        for (int i = 0; i < 2; i++) bulk_load(sA + i * 16384, g_x1 + (rb * 64 + i * 8) * 1024, 16384, bA + 8 * i);
      }
      for (int s = NB; s < NST; s++) {
        mbar_wait(bE + (s % NB) * 8, (s / NB - 1) & 1); loadB(s);
        if (FFN && s <= 10 && !(s & 1)) bulk_load(sA + (s / 2 - 3) * 16384, g_x1 + (rb * 64 + (s / 2 + 2) * 8) * 1024, 16384, bA + 8 * (s / 2 + 2));
      }
    }
  } else {
  asm volatile("setmaxnreg.inc.sync.aligned.u32 232;");
  const int g = lane >> 2, t = lane & 3;
  const int lr = warp * 16 + (lane & 7) + ((lane >> 3) & 1) * 8;
  auto aaddr = [&](int ks) -> uint32_t {
    if (FFN) return sA + ((ks < 20 ? ks : ks - 20) * 2 + (lane >> 4)) * 2048 + lr * 16;
    return sA + (ks >> 2) * 16384 + lr * 128 + ((((ks & 3) * 2 + (lane >> 4)) ^ (lr & 7)) << 4);
  };
  const int row0 = rb * 128 + warp * 16 + g;
  float2 msh, msc;
  uint2 sh, sc;
  float rs0, rs1, nm0, nm1;
  if (!FFN) {
    {
      float a[8] = {0, 0, 0, 0, 0, 0, 0, 0};
      fma8(a, silu_bf(cv0), wv0); fma8(a, silu_bf(cv1), wv1);
      const float s = qsum(red8(a, lane));
      if (t == 0) red[warp * 8 + g] = s;
      asm volatile("bar.sync 1,256;" ::: "memory");
      if (tid < 8) {
        float r = 0;
#pragma unroll
        for (int i = 0; i < 8; i++) r += red[i * 8 + tid];
        const int n = blockIdx.x * 8 + tid;
        asm volatile("st.relaxed.gpu.global.u32 [%0],%1;" ::"l"(g_modv + n), "r"(__float_as_uint(mod_fin(r, n)) | 1u) : "memory");
      }
      TS(0, 1);
    }
    {
      float v[32], s = 0, q = 0;
#pragma unroll
      for (int i = 0; i < 16; i++) { const uint32_t u = ((const uint32_t*)xv)[i]; v[2 * i] = blo(u); v[2 * i + 1] = bhi(u); s += v[2 * i] + v[2 * i + 1]; }
      s = qsum(s); s += __shfl_xor_sync(~0u, s, 4); s += __shfl_xor_sync(~0u, s, 8);
      const float m = s * (1.f / 512);
#pragma unroll
      for (int i = 0; i < 32; i++) q += (v[i] - m) * (v[i] - m);
      q = qsum(q); q += __shfl_xor_sync(~0u, q, 4); q += __shfl_xor_sync(~0u, q, 8);
      const float rs = rsqrtf(q * (1.f / 512) + 1e-5f);
      if ((tid & 15) == 0)
        asm volatile("st.relaxed.gpu.global.v2.u32 [%0],{%1,%2};" ::"l"(g_modv + 1024 + (blockIdx.x * 16 + (tid >> 4)) * 2), "r"(__float_as_uint(rs) | 1u), "r"(__float_as_uint(-m * rs) | 1u) : "memory");
    }
    uint2 p0, p1;
    poll4(p0, p1, sh, sc, g_modv + 1024 + row0 * 2, g_modv + tid * 2);
    rs0 = __uint_as_float(p0.x); nm0 = __uint_as_float(p0.y); rs1 = __uint_as_float(p1.x); nm1 = __uint_as_float(p1.y);
  } else {
    pdl_wait();
    TS(4, 1);
    msh = *(const float2*)(g_mod + 1536 + tid * 2); msc = *(const float2*)(g_mod + 2048 + tid * 2);
    const float4 p0 = *(const float4*)(g_st + row0 * 8 + t * 2), p1 = *(const float4*)(g_st + (row0 + 8) * 8 + t * 2);
    const float m0 = qsum(p0.x + p0.z) * 0.125f, m1 = qsum(p1.x + p1.z) * 0.125f;
    const float v0 = qsum(p0.y + p0.w + 64.f * ((p0.x - m0) * (p0.x - m0) + (p0.z - m0) * (p0.z - m0)));
    const float v1 = qsum(p1.y + p1.w + 64.f * ((p1.x - m1) * (p1.x - m1) + (p1.z - m1) * (p1.z - m1)));
    rs0 = rsqrtf(v0 * (1.f / 512) + 1e-5f); rs1 = rsqrtf(v1 * (1.f / 512) + 1e-5f);
    nm0 = -m0 * rs0; nm1 = -m1 * rs1;
  }
  {
    uint32_t* m = (uint32_t*)(smem + (sM - sA)) + (tid >> 3) * 16 + (tid & 3) * 4 + ((tid >> 2) & 1);
    if (FFN) { m[0] = pack_rn(msc.x, msc.y); m[2] = pack_rn(msh.x, msh.y); }
    else { m[0] = __byte_perm(sc.x, sc.y, 0x7632); m[2] = __byte_perm(sh.x, sh.y, 0x7632); }
    asm volatile("bar.sync 1,256;" ::: "memory");
  }
  if (FFN && warp >= 2 && warp < 5 && lane == 0) bulk_load(sA + warp * 16384, g_x1 + (rb * 64 + warp * 8) * 1024, 16384, bA + 8 * warp);
  constexpr int NA = FFN ? 88 : 96;
  float acc0[NA], acc1[FFN ? 88 : 1];
  uint32_t a[2][KS][4];
  auto prep = [&](int ks, uint32_t(&o)[4]) {
    if ((ks & 3) == 0) mbar_wait(bA + 2 * ks, 0);
    uint32_t r[4]; ldsm4(aaddr(ks), r);
    const uint4 m = *(const uint4*)(smem + (sM - sA) + ks * 64 + t * 16);
#pragma unroll
    for (int i = 0; i < 4; i++) {
      const float rs = (i & 1) ? rs1 : rs0, nm = (i & 1) ? nm1 : nm0;
      const uint32_t n = pack_rn(fmaf(blo(r[i]), rs, nm), fmaf(bhi(r[i]), rs, nm));
      asm("fma.rn.bf16x2 %0,%1,%2,%3;" : "=r"(o[i]) : "r"(n), "r"(i < 2 ? m.x : m.y), "r"(i < 2 ? m.z : m.w));
    }
  };
  auto stage = [&](int s, uint32_t(&c)[KS][4], uint32_t(&n)[KS][4]) {
    mbar_wait(bF + (s % NB) * 8, (s / NB) & 1);
    const uint64_t db = mk_desc(sB + (s % NB) * 24576, BOX, 1024, 1);
    wg_fence();
#pragma unroll
    for (int k = 0; k < KS; k++) {
      if constexpr (FFN) {
        wgmma_rs_n176_t1(acc0, c[k][0], c[k][1], c[k][2], c[k][3], db + k * 128, s + k);
        wgmma_rs_n176_t1(acc1, c[k][0], c[k][1], c[k][2], c[k][3], db + k * 128 + 3 * BOX / 16, s + k);
      } else {
        wgmma_rs_n192_t1(acc0, c[k][0], c[k][1], c[k][2], c[k][3], db + k * 128, s + k);
      }
    }
    wg_commit();
    wg_wait<1>();
    if (s > 0 && s <= NST - NB) {
      if (!FFN) { if (lane == 0) mbar_arrive(bE + ((s - 1) % NB) * 8); }
      else if (lane < 2) asm volatile("{\n.reg .b32 r;\nmapa.shared::cluster.u32 r,%0,%1;\nmbarrier.arrive.relaxed.cluster.shared::cluster.b64 _,[r];\n}" ::"r"(bE + ((s - 1) % NB) * 8), "r"(lane) : "memory");
    }
    if (s < NST - 1) {
#pragma unroll
      for (int k = 0; k < KS; k++) prep((s + 1) * KS + k, n[k]);
    }
  };
#pragma unroll
  for (int k = 0; k < KS; k++) prep(k, a[0][k]);
  TS(FFN ? 4 : 1, 2);
#pragma unroll 1
  for (int s = 0; s < NST; s += 2) { stage(s, a[0], a[1]); stage(s + 1, a[1], a[0]); }
  wg_wait<0>();
  reg_fence(acc0);
  TS(FFN ? 4 : 1, 3);
  if constexpr (FFN) {
    reg_fence(acc1);
    uint32_t* o = (uint32_t*)g_h + ((rb * 172 + ct * 22) * 128 + warp * 16 + g) * 4 + t;
#pragma unroll
    for (int j = 0; j < 22; j++) {
      {
        float h[4], d[4];
#pragma unroll
        for (int i = 0; i < 4; i++) { const float x = acc0[4 * j + i]; d[i] = 1.f + ex2(fminf(-1.4426950408889634f * x, 30.f)); h[i] = x * acc1[4 * j + i]; }
        const float d01 = d[0] * d[1], d23 = d[2] * d[3];
        float r; asm("rcp.approx.ftz.f32 %0,%1;" : "=f"(r) : "f"(d01 * d23));
        const float r01 = r * d23, r23 = r * d01;
        h[0] *= r01 * d[1]; h[1] *= r01 * d[0]; h[2] *= r23 * d[3]; h[3] *= r23 * d[2];
        if (j < 18 || ct < 7) { o[j * 512] = pack_rn(h[0], h[1]); o[j * 512 + 32] = pack_rn(h[2], h[3]); }
      }
    }
  } else {
    uint32_t* o = (uint32_t*)g_qkv + (ct * 24 * 2048 + row0) * 4 + t;
#pragma unroll
    for (int j = 0; j < 24; j += 2) {
      const int G = ct * 24 + j;
      const float sc = G < 64 ? 0.25f * 1.4426950408889634f : 1.f;
      uint32_t p[4];
#pragma unroll
      for (int i = 0; i < 4; i++) p[i] = pack_rn(acc0[4 * j + 2 * i] * sc, acc0[4 * j + 2 * i + 1] * sc);
      o[j * 8192] = p[0]; o[j * 8192 + 32] = p[1]; o[(j + 1) * 8192] = p[2]; o[(j + 1) * 8192 + 32] = p[3];
      if (G >= 64 && G < 128) {
        float n0 = blo(p[0]) * blo(p[0]) + bhi(p[0]) * bhi(p[0]) + blo(p[2]) * blo(p[2]) + bhi(p[2]) * bhi(p[2]);
        float n1 = blo(p[1]) * blo(p[1]) + bhi(p[1]) * bhi(p[1]) + blo(p[3]) * blo(p[3]) + bhi(p[3]) * bhi(p[3]);
        n0 = qsum(n0); n1 = qsum(n1);
        const uint32_t mx = __reduce_max_sync(~0u, max(__float_as_uint(n0), __float_as_uint(n1)));
        if (lane == 0) g_kmax[((G - 64) >> 1) * 128 + rb * 8 + warp] = __uint_as_float(mx);
      }
    }
  }
  TS(FFN ? 4 : 1, 4);
}
}

#define SMASK 0xAAu
#define BRK 0
#define PACK 1
#define PP 1
constexpr int AT_SMEM = 5 * 32768 + 256;
__device__ __forceinline__ uint32_t exp2_pair_fma(float s0, float s1, float c, uint32_t ka, uint32_t kz) {
  uint32_t r;
  asm volatile("{\n.reg .b32 y0,y1,e,u,t;\n"
      "fma.rn.sat.f32 y0,%1,0f00000080,%3;\nfma.rn.sat.f32 y1,%2,0f00000080,%3;\n"
      "mad.lo.u32 e,y1,65536,y0;\n"
      "and.b32 u,e,0x007F007F;\n"
      "fma.rn.f16x2 u,u,%4,%5;\nfma.rn.f16x2 t,u,u,%6;\nfma.rn.f16x2 t,t,u,%7;\n"
      "lop3.b32 %0,t,0x007F007F,e,0xE2;\n}\n"
      : "=r"(r) : "f"(s0), "f"(s1), "f"(c), "r"(ka), "r"(0x36B236B2u), "r"(0x3C733C73u), "r"(0x47764776u), "r"(kz));
  return r;
}
__device__ __forceinline__ void attn_pass(float (&oa)[12], float (&ob)[12], const uint32_t (&q)[4], float m0, float m1, uint32_t sK, uint32_t bars, bool first, uint32_t kz) {
  const uint64_t dk = mk_desc(sK, 32768, 128, 0), dv = mk_desc(sK + 65536, 128, 32768, 0);
  const float c0 = (127.f - m0) * __uint_as_float(0x80u), c1 = (127.f - m1) * __uint_as_float(0x80u);
  const uint32_t ka = 0x7ACE7ACEu + kz;
  constexpr int NK = 64, NS = 32, NP = 16, NI = 32;
  auto qk = [&](float (&s)[NS], int i) { wgmma_rs_n64_t0(s, q[0], q[1], q[2], q[3], dk + i * NK, 0); };
  auto softmax = [&](float (&s)[NS], uint32_t (&p)[NP], uint32_t mask) {
    reg_fence(s);
    float e0, e1;
    int pend = -1;
#pragma unroll
    for (int t = 0; t < NP; t++) {
      const int j = (t & 3) * 4 + (t >> 2);
      if ((mask >> (t & 3)) & 1) {
        p[j] = exp2_pair_fma(s[2 * j], s[2 * j + 1], (j & 1) ? c1 : c0, ka, kz);
      } else {
        float f0, f1;
        asm volatile("ex2.approx.ftz.f32 %0,%2;\nex2.approx.ftz.f32 %1,%3;" : "=&f"(f0), "=f"(f1) : "f"(s[2 * j]), "f"(s[2 * j + 1]));
        if (pend >= 0) asm volatile("cvt.rn.bf16x2.f32 %0,%1,%2;" : "=r"(p[pend]) : "f"(e1), "f"(e0));
        e0 = f0; e1 = f1; pend = j;
      }
    }
    if (pend >= 0) asm volatile("cvt.rn.bf16x2.f32 %0,%1,%2;" : "=r"(p[pend]) : "f"(e1), "f"(e0));
#pragma unroll
    for (int j = 0; j < NP; j++) asm volatile("" : "+r"(p[j])::"memory");
  };
  auto pv = [&](uint32_t (&p)[NP], int i, uint32_t mask) {
#pragma unroll
    for (int k = 0; k < 4; k++) wgmma_rs_n24_t1(((mask >> k) & 1) ? ob : oa, p[4 * k], p[4 * k + 1], p[4 * k + 2], p[4 * k + 3], dv + i * NK + k * 16, 1);
  };
  auto ld = [&](int i) { if (first && (i & 3) == 0) mbar_wait(bars + i * 2, 0); };
  constexpr uint32_t M0 = SMASK & 15, M1 = SMASK >> 4;
  zero(oa); zero(ob);
  ld(0);
  if (first) TS(2, 2);
  float s[NS];
  zero(s);
  uint32_t p0[NP], p1[NP];
  wg_fence(); qk(s, 0); wg_commit(); wg_wait<0>(); softmax(s, p0, M0);
#pragma unroll 1
  for (int i = 0; i < NI - 2; i += 2) {
    wg_fence(); qk(s, i + 1); wg_commit(); pv(p0, i, M0); wg_commit(); wg_wait<1>(); softmax(s, p1, M1); wg_wait<0>();
    ld(i + 2);
    wg_fence(); qk(s, i + 2); wg_commit(); pv(p1, i + 1, M1); wg_commit(); wg_wait<1>(); softmax(s, p0, M0); wg_wait<0>();
  }
  wg_fence(); qk(s, NI - 1); wg_commit(); pv(p0, NI - 2, M0); wg_commit(); wg_wait<1>(); softmax(s, p1, M1); wg_wait<0>();
  wg_fence(); pv(p1, NI - 1, M1); wg_commit();
  wg_wait<0>();
  reg_fence(oa); reg_fence(ob);
}
__device__ __forceinline__ void mma16816(float (&d)[4], const uint32_t (&a)[4], uint32_t b0, uint32_t b1) {
  asm("mma.sync.aligned.m16n8k16.row.col.f32.bf16.bf16.f32 {%0,%1,%2,%3},{%4,%5,%6,%7},{%8,%9},{%0,%1,%2,%3};"
      : "+f"(d[0]), "+f"(d[1]), "+f"(d[2]), "+f"(d[3]) : "r"(a[0]), "r"(a[1]), "r"(a[2]), "r"(a[3]), "r"(b0), "r"(b1));
}
__device__ __forceinline__ void attn_safe(float (&o)[12], const uint32_t (&q)[4], uint32_t sK) {
  const int lane = threadIdx.x & 31;
  const uint32_t ka = sK + (lane >> 4) * 32768 + (lane & 15) * 16;
  float m0 = -INFINITY, m1 = -INFINITY;
#pragma unroll 2
  for (int i = 0; i < 128; i++) {
    uint32_t k[4]; ldsm4(ka + i * 256, k);
    float s0[4] = {0, 0, 0, 0}, s1[4] = {0, 0, 0, 0};
    mma16816(s0, q, k[0], k[2]); mma16816(s1, q, k[1], k[3]);
    m0 = fmaxf(fmaxf(m0, fmaxf(s0[0], s0[1])), fmaxf(s1[0], s1[1])); m1 = fmaxf(fmaxf(m1, fmaxf(s0[2], s0[3])), fmaxf(s1[2], s1[3]));
  }
  m0 = fmaxf(m0, __shfl_xor_sync(~0u, m0, 1)); m0 = fmaxf(m0, __shfl_xor_sync(~0u, m0, 2));
  m1 = fmaxf(m1, __shfl_xor_sync(~0u, m1, 1)); m1 = fmaxf(m1, __shfl_xor_sync(~0u, m1, 2));
  float o0[4] = {0, 0, 0, 0}, o1[4] = {0, 0, 0, 0}, o2[4] = {0, 0, 0, 0};
#pragma unroll 2
  for (int i = 0; i < 128; i++) {
    uint32_t k[4], v[4]; ldsm4(ka + i * 256, k);
    asm volatile("ldmatrix.sync.aligned.m8n8.x4.trans.shared.b16 {%0,%1,%2,%3},[%4];" : "=r"(v[0]), "=r"(v[1]), "=r"(v[2]), "=r"(v[3]) : "r"(ka + 65536 + i * 256) : "memory");
    float s0[4] = {0, 0, 0, 0}, s1[4] = {0, 0, 0, 0};
    mma16816(s0, q, k[0], k[2]); mma16816(s1, q, k[1], k[3]);
    const uint32_t p[4] = {pack_rn(ex2(s0[0] - m0), ex2(s0[1] - m0)), pack_rn(ex2(s0[2] - m1), ex2(s0[3] - m1)),
                           pack_rn(ex2(s1[0] - m0), ex2(s1[1] - m0)), pack_rn(ex2(s1[2] - m1), ex2(s1[3] - m1))};
    mma16816(o0, p, v[0], v[1]); mma16816(o1, p, v[2], v[3]); mma16816(o2, p, 0x3F803F80u, 0x3F803F80u);
  }
#pragma unroll
  for (int i = 0; i < 4; i++) { o[i] = o0[i]; o[4 + i] = o1[i]; o[8 + i] = o2[i]; }
}
__global__ void __cluster_dims__(2, 1, 1) __launch_bounds__(512, 1) k_attn(const bf16* wo, const bf16* w1, const bf16* w3, const bf16* w2, const bf16* __restrict__ cv, const bf16* __restrict__ wm, uint32_t kz) {
  extern __shared__ __align__(1024) uint8_t smem[];
  const uint32_t sK = smem_u32(smem), bars = sK + 5 * 32768;
  const int tid = threadIdx.x, warp = tid >> 5, lane = tid & 31, g = lane >> 2, t = lane & 3;
  pdl_launch();
  if (blockIdx.x < 4) {
    float* cs = (float*)smem;
    cs[tid] = silu_bf(cv[tid]);
    __syncthreads();
    const int n0 = 1024 + blockIdx.x * 512, r0 = (tid >> 6) * 64;
    float a[8] = {0, 0, 0, 0, 0, 0, 0, 0};
#pragma unroll 16
    for (int r = r0; r < r0 + 64; r++) fma8(a, cs[r], __ldg((const uint4*)(wm + r * 3072 + n0 + (tid & 63) * 8)));
    float4* rp = (float4*)(cs + 512 + tid * 8);
    rp[0] = make_float4(a[0], a[1], a[2], a[3]); rp[1] = make_float4(a[4], a[5], a[6], a[7]);
    __syncthreads();
    float s = 0;
#pragma unroll
    for (int i = 0; i < 8; i++) s += cs[512 + i * 512 + tid];
    g_mod[n0 + tid] = mod_fin(s, n0 + tid);
    return;
  }
  const int bid = blockIdx.x - 4, h = bid >> 2, qb = bid & 3;
  TS(2, 0);
  if (tid == 0) { for (int i = 0; i < 8; i++) { mbar_init(bars + 8 * i, 1); mbar_expect(bars + 8 * i, 16384); } fence_init(); }
#pragma unroll
  for (int i = 0; i < 4; i++) *(uint4*)(smem + 131072 + i * 8192 + tid * 16) = make_uint4(0x3F803F80u, 0x3F803F80u, 0x3F803F80u, 0x3F803F80u);
  fence_async();
  cluster_sync();
  pdl_wait();
  TS(2, 1);
  if (tid >= 472) g_modv[bid * 40 + tid - 472] = 0;
  const uint4 km4 = *(const uint4*)(g_kmax + h * 128 + lane * 4);
  const uint32_t* qp = (const uint32_t*)g_qkv + (h * 2 * 2048 + qb * 512 + warp * 16 + g) * 4 + t;
  uint32_t q[4] = {qp[0], qp[32], qp[8192], qp[8192 + 32]};
  auto ldkv = [&]() {
    const int c = warp >> 1, pl = (qb & 1) + (warp & 1) * 2;
    bulk_load_mc(sK + pl * 32768 + c * 4096, g_qkv + ((64 + (pl >> 1) * 64 + h * 2 + (pl & 1)) * 2048 + c * 256) * 8, 4096, bars + 8 * c);
  };
  if (lane == 0 && warp < 4) ldkv();
  const uint32_t qn[4] = {qp[1024], qp[1024 + 32], qp[1024 + 8192], qp[1024 + 8192 + 32]};
  const float kmax = __uint_as_float(__reduce_max_sync(~0u, max(max(km4.x, km4.y), max(km4.z, km4.w))));
  if (lane == 0 && warp >= 4 && kmax != -1.f) ldkv();
#pragma unroll 1
  for (int tile = 0; tile < 2; tile++) {
    const int row = qb * 512 + tile * 256 + warp * 16 + g;
    const float n0 = qsum(blo(q[0]) * blo(q[0]) + bhi(q[0]) * bhi(q[0]) + blo(q[2]) * blo(q[2]) + bhi(q[2]) * bhi(q[2]));
    const float n1 = qsum(blo(q[1]) * blo(q[1]) + bhi(q[1]) * bhi(q[1]) + blo(q[3]) * blo(q[3]) + bhi(q[3]) * bhi(q[3]));
    const float b0 = sqrtf(n0 * kmax) * 1.001f, b1 = sqrtf(n1 * kmax) * 1.001f;
    const float m0 = fmaxf(ceilf(b0 - 100.f), 0.f), m1 = fmaxf(ceilf(b1 - 100.f), 0.f);
    float o[12], ob[12];
    attn_pass(o, ob, q, m0, m1, sK, bars, tile == 0, kz);
    const float f0 = ex2(-m0), f1 = ex2(-m1);
#pragma unroll
    for (int i = 0; i < 12; i++) o[i] = fmaf(o[i], (i & 2) ? f1 : f0, ob[i]);
    bool ok = b0 < 220.f && b1 < 220.f && o[8] >= 0x1p-90f && o[10] >= 0x1p-90f;
#pragma unroll
    for (int i = 0; i < 12; i++) ok = ok && fabsf(o[i]) < INFINITY;
    if (!__all_sync(~0u, ok)) attn_safe(o, q, sK);
    const float r0 = 1.f / o[8], r1 = 1.f / o[10];
    uint32_t* op = (uint32_t*)g_o + (((row >> 7) * 64 + h * 2) * 128 + (row & 127)) * 4 + t;
    op[0] = pack_rn(o[0] * r0, o[1] * r0); op[32] = pack_rn(o[2] * r1, o[3] * r1);
    op[512] = pack_rn(o[4] * r0, o[5] * r0); op[512 + 32] = pack_rn(o[6] * r1, o[7] * r1);
    if (tile == 0 && tid == 32) {
      l2_prefetch((const char*)wo + bid * 4096, 4096);
      l2_prefetch((const char*)w1 + bid * 11008, 11008);
      l2_prefetch((const char*)w3 + bid * 11008, 11008);
      l2_prefetch((const char*)w2 + bid * 11008, 11008);
    }
#pragma unroll
    for (int i = 0; i < 4; i++) q[i] = qn[i];
    TS(2, 3 + tile);
  }
}

constexpr int WO_SMEM = 131072 + 65536 + 256;
__global__ void __cluster_dims__(2, 1, 1) __launch_bounds__(256, 1) k_wo(const __grid_constant__ CUtensorMap mW, const bf16* __restrict__ x) {
  extern __shared__ __align__(1024) uint8_t smem[];
  const uint32_t sA = smem_u32(smem), sB = sA + 131072, bars = sB + 65536;
  const int tid = threadIdx.x, warp = tid >> 5, lane = tid & 31, g = lane >> 2, t = lane & 3;
  const int rb = blockIdx.x >> 3, ct = blockIdx.x & 7;
  TS(3, 0);
  pdl_launch();
  if (tid == 0) {
    for (int i = 0; i < 8; i++) mbar_init(bars + 8 * i, 1);
    fence_init();
    for (int i = 0; i < 8; i++) { mbar_expect(bars + 8 * i, 24576); tma2d(sB + i * 8192, &mW, ct * 64, i * 64, bars + 8 * i); }
  }
  __syncwarp();
  cluster_arrive();
  const int lrow = warp * 16 + g;
  uint32_t xr[16];
  const uint32_t* xp = (const uint32_t*)(x + (rb * 128 + lrow) * 512 + ct * 64) + t;
#pragma unroll
  for (int j = 0; j < 8; j++) { xr[2 * j] = __ldg(xp + j * 4); xr[2 * j + 1] = __ldg(xp + j * 4 + 8 * 256); }
  cluster_wait();
  pdl_wait();
  if (tid == 0) {
    for (int i = ct & 1; i < 8; i += 2) bulk_load_mc(sA + i * 16384, g_o + (rb * 64 + i * 8) * 1024, 16384, bars + 8 * i);
  }
  TS(3, 1);
  float2 ga[8];
#pragma unroll
  for (int j = 0; j < 8; j++) ga[j] = *(const float2*)(g_mod + 1024 + ct * 64 + j * 8 + t * 2);
  float acc[32];
  const uint64_t da = mk_desc(sA + (warp >> 2) * 1024, 2048, 128, 0), db = mk_desc(sB, 8192, 1024, 1);
#pragma unroll
  for (int c = 0; c < 8; c++) {
    mbar_wait(bars + 8 * c, 0);
    if (c == 0) TS(3, 2);
    wg_fence();
#pragma unroll
    for (int k = 0; k < 4; k++) wgmma_ss_n64_t1(acc, da + (c * 4 + k) * 256, db + (c * 4 + k) * 128, c + k);
    wg_commit();
  }
  wg_wait<0>();
  reg_fence(acc);
  TS(3, 3);
  uint32_t* o = (uint32_t*)g_x1 + ((rb * 64 + ct * 8) * 128 + lrow) * 4 + t;
  float s0 = 0, s1 = 0;
#pragma unroll
  for (int j = 0; j < 8; j++) {
    xr[2 * j] = pack_rn(fmaf(ga[j].x, acc[4 * j], blo(xr[2 * j])), fmaf(ga[j].y, acc[4 * j + 1], bhi(xr[2 * j])));
    xr[2 * j + 1] = pack_rn(fmaf(ga[j].x, acc[4 * j + 2], blo(xr[2 * j + 1])), fmaf(ga[j].y, acc[4 * j + 3], bhi(xr[2 * j + 1])));
    o[j * 512] = xr[2 * j]; o[j * 512 + 32] = xr[2 * j + 1];
    s0 += blo(xr[2 * j]) + bhi(xr[2 * j]); s1 += blo(xr[2 * j + 1]) + bhi(xr[2 * j + 1]);
  }
  const float m0 = qsum(s0) * (1.f / 64), m1 = qsum(s1) * (1.f / 64);
  float v0 = 0, v1 = 0;
#pragma unroll
  for (int j = 0; j < 8; j++) {
    float d;
    d = blo(xr[2 * j]) - m0; v0 += d * d; d = bhi(xr[2 * j]) - m0; v0 += d * d;
    d = blo(xr[2 * j + 1]) - m1; v1 += d * d; d = bhi(xr[2 * j + 1]) - m1; v1 += d * d;
  }
  v0 = qsum(v0); v1 = qsum(v1);
  if (t == 0) g_st[(rb * 128 + lrow) * 8 + ct] = make_float2(m0, v0);
  if (t == 1) g_st[(rb * 128 + lrow + 8) * 8 + ct] = make_float2(m1, v1);
  TS(3, 4);
}

constexpr int W2_SMEM = 6 * 32768 + 32768 + 256;
__global__ void __cluster_dims__(2, 1, 1) __launch_bounds__(288, 1) k_w2(const __grid_constant__ CUtensorMap mW, bf16* __restrict__ out) {
  extern __shared__ __align__(1024) uint8_t smem[];
  const uint32_t sR = smem_u32(smem), sX = sR + 6 * 32768, bF = sX + 32768, bE = bF + 48, bX = bF + 96;
  const int tid = threadIdx.x, warp = tid >> 5, lane = tid & 31, g = lane >> 2, t = lane & 3;
  const int kh = blockIdx.x & 1, ct = (blockIdx.x >> 1) & 3, rb = blockIdx.x >> 3;
  TS(5, 0);
  pdl_launch();
  if (tid == 256) {
    for (int i = 0; i < 6; i++) { mbar_init(bF + 8 * i, 1); mbar_init(bE + 8 * i, 8); }
    for (int i = 0; i < 8; i++) { mbar_init(bX + 8 * i, 1); mbar_expect(bX + 8 * i, 4096); }
    fence_init();
  }
  __syncthreads();
  asm volatile("barrier.cluster.arrive.relaxed.aligned;" ::: "memory");
  if (warp == 8) {
    if (lane == 0) {
      auto abytes = [&](int s) { return (kh == 1 && s == 10) ? 8192 : 16384; };
      auto loadB = [&](int s) {
        const int st = s % 6;
        mbar_expect(bF + 8 * st, 16384 + abytes(s));
        for (int j = 0; j < 2; j++) tma2d(sR + st * 32768 + 16384 + j * 8192, &mW, ct * 128 + j * 64, kh * 704 + s * 64, bF + 8 * st);
      };
      auto loadA = [&](int s) { bulk_load(sR + (s % 6) * 32768, g_h + (rb * 172 + kh * 88 + s * 8) * 1024, abytes(s), bF + 8 * (s % 6)); };
      for (int s = 0; s < 6; s++) loadB(s);
      pdl_wait();
      for (int s = 0; s < 6; s++) loadA(s);
      for (int s = 6; s < 11; s++) { mbar_wait(bE + 8 * (s - 6), 0); loadB(s); loadA(s); }
    }
    __syncwarp();
    cluster_wait();
    return;
  }
  pdl_wait();
  TS(5, 1);
  const int lrow = warp * 16 + g;
  uint32_t xr[16];
  float2 gb[8];
  const uint32_t* xp = (const uint32_t*)g_x1 + ((rb * 64 + ct * 16 + kh * 8) * 128 + lrow) * 4 + t;
#pragma unroll
  for (int j = 0; j < 8; j++) {
    xr[2 * j] = xp[j * 512]; xr[2 * j + 1] = xp[j * 512 + 32];
    gb[j] = *(const float2*)(g_mod + 2560 + ct * 128 + kh * 64 + j * 8 + t * 2);
  }
  float acc[64];
#pragma unroll 1
  for (int s = 0; s < 11; s++) {
    const int st = s % 6;
    mbar_wait(bF + 8 * st, s >= 6);
    const uint64_t da = mk_desc(sR + st * 32768 + (warp >> 2) * 1024, 2048, 128, 0), db = mk_desc(sR + st * 32768 + 16384, 8192, 1024, 1);
    if (s == 0) TS(5, 2);
    wg_fence();
    wgmma_ss_n128_t1(acc, da, db, s);
    wgmma_ss_n128_t1(acc, da + 256, db + 128, 1);
    wgmma_ss_n128_t1(acc, da + 512, db + 256, 1);
    wgmma_ss_n128_t1(acc, da + 768, db + 384, 1);
    wg_commit();
    wg_wait<1>();
    if (s > 0 && s < 6 && lane == 0) mbar_arrive(bE + 8 * (s - 1));
  }
  wg_wait<0>();
  reg_fence(acc);
  TS(5, 3);
  asm volatile("barrier.cluster.wait.aligned;" ::: "memory");
  uint32_t rem, rbar;
  asm("mapa.shared::cluster.u32 %0,%1,%2;" : "=r"(rbar) : "r"(bX + warp * 8), "r"(kh ^ 1));
  asm("mapa.shared::cluster.u32 %0,%1,%2;" : "=r"(rem) : "r"(sX + warp * 4096 + lane * 16), "r"(kh ^ 1));
#pragma unroll
  for (int j = 0; j < 8; j++) {
    float v[4];
#pragma unroll
    for (int i = 0; i < 4; i++) { v[i] = kh ? acc[4 * j + i] : acc[32 + 4 * j + i]; acc[4 * j + i] = kh ? acc[32 + 4 * j + i] : acc[4 * j + i]; }
    asm volatile("st.async.weak.shared::cluster.mbarrier::complete_tx::bytes.v4.f32 [%0],{%1,%2,%3,%4},[%5];" ::"r"(rem + j * 512), "f"(v[0]), "f"(v[1]), "f"(v[2]), "f"(v[3]), "r"(rbar) : "memory");
  }
  mbar_wait(bX + warp * 8, 0);
  TS(5, 5);
  const uint32_t sw = sX + warp * 4096;
#pragma unroll
  for (int j = 0; j < 8; j++) {
    const float4 p = *(const float4*)(smem + 6 * 32768 + warp * 4096 + j * 512 + lane * 16);
    xr[2 * j] = pack_rn(fmaf(gb[j].x, acc[4 * j] + p.x, blo(xr[2 * j])), fmaf(gb[j].y, acc[4 * j + 1] + p.y, bhi(xr[2 * j])));
    xr[2 * j + 1] = pack_rn(fmaf(gb[j].x, acc[4 * j + 2] + p.z, blo(xr[2 * j + 1])), fmaf(gb[j].y, acc[4 * j + 3] + p.w, bhi(xr[2 * j + 1])));
  }
  __syncwarp();
#pragma unroll
  for (int j = 1; j < 8; j += 2) {
    asm volatile("stmatrix.sync.aligned.m8n8.x4.shared.b16 [%0],{%1,%2,%3,%4};" ::"r"(sw + (lane & 15) * 128 + (((j - 1 + (lane >> 4)) ^ (lane & 7)) << 4)),
                            "r"(xr[2 * j - 2]), "r"(xr[2 * j - 1]), "r"(xr[2 * j]), "r"(xr[2 * j + 1]) : "memory");
  }
  __syncwarp();
#pragma unroll
  for (int i = 0; i < 4; i++) {
    const int r = i * 4 + (lane >> 3);
    *(uint4*)(out + (rb * 128 + warp * 16 + r) * 512 + ct * 128 + kh * 64 + (lane & 7) * 8) = *(const uint4*)(smem + 6 * 32768 + warp * 4096 + r * 128 + (((lane ^ r) & 7) << 4));
  }
  TS(5, 4);
}

typedef CUresult (*EncFn)(CUtensorMap*, CUtensorMapDataType, cuuint32_t, void*, const cuuint64_t*, const cuuint64_t*, const cuuint32_t*,
                          const cuuint32_t*, CUtensorMapInterleave, CUtensorMapSwizzle, CUtensorMapL2promotion, CUtensorMapFloatOOBfill);
static void mk_map(EncFn f, CUtensorMap* m, const void* p, int rows, int cols, int box_rows) {
  cuuint64_t dim[2] = {(cuuint64_t)cols, (cuuint64_t)rows}, str[1] = {(cuuint64_t)cols * 2};
  cuuint32_t box[2] = {64, (cuuint32_t)box_rows}, es[2] = {1, 1};
  f(m, CU_TENSOR_MAP_DATA_TYPE_BFLOAT16, 2, (void*)p, dim, str, box, es, CU_TENSOR_MAP_INTERLEAVE_NONE, CU_TENSOR_MAP_SWIZZLE_128B,
    CU_TENSOR_MAP_L2_PROMOTION_L2_128B, CU_TENSOR_MAP_FLOAT_OOB_FILL_NONE);
}
template <typename... KA, typename... A>
static void launch(void (*k)(KA...), int grid, int block, int smem, bool pdl, A... args) {
  cudaLaunchConfig_t cfg = {};
  cfg.gridDim = dim3(grid); cfg.blockDim = dim3(block); cfg.dynamicSmemBytes = smem; cfg.stream = cudaStreamPerThread;
  cudaLaunchAttribute at[1];
  at[0].id = cudaLaunchAttributeProgrammaticStreamSerialization; at[0].val.programmaticStreamSerializationAllowed = 1;
  cfg.attrs = at; cfg.numAttrs = pdl ? 1 : 0;
  cudaLaunchKernelEx(&cfg, k, args...);
}
extern "C" void kernel_launch(void* const* d_in, const int* in_sizes, int n_in, void* d_out, int out_size) {
  const bf16 *x = (const bf16*)d_in[0], *wqkv = (const bf16*)d_in[1], *wo = (const bf16*)d_in[2], *w1 = (const bf16*)d_in[4],
             *w3 = (const bf16*)d_in[5], *w2 = (const bf16*)d_in[6], *c = (const bf16*)d_in[7], *wmod = (const bf16*)d_in[8];
  void* fp = nullptr;
  cudaDriverEntryPointQueryResult qr;
  cudaGetDriverEntryPoint("cuTensorMapEncodeTiled", &fp, cudaEnableDefault, &qr);
  EncFn f = (EncFn)fp;
  CUtensorMap mX, mQ, mO, m1, m3, m2;
  mk_map(f, &mX, x, S_, D_, 128); mk_map(f, &mQ, wqkv, D_, 3 * D_, 64); mk_map(f, &mO, wo, D_, D_, 64);
  mk_map(f, &m1, w1, D_, F_, 32); mk_map(f, &m3, w3, D_, F_, 32); mk_map(f, &m2, w2, F_, D_, 64);
  cudaFuncSetAttribute(k_lngemm<false>, cudaFuncAttributeMaxDynamicSharedMemorySize, LN_SMEM);
  cudaFuncSetAttribute(k_lngemm<true>, cudaFuncAttributeMaxDynamicSharedMemorySize, LN_SMEM);
  cudaFuncSetAttribute(k_attn, cudaFuncAttributeMaxDynamicSharedMemorySize, AT_SMEM);
  cudaFuncSetAttribute(k_wo, cudaFuncAttributeMaxDynamicSharedMemorySize, WO_SMEM);
  cudaFuncSetAttribute(k_w2, cudaFuncAttributeMaxDynamicSharedMemorySize, W2_SMEM);
  launch(k_lngemm<false>, 128, 384, LN_SMEM, false, mX, mQ, mQ, c, wmod, x);
  launch(k_attn, 132, 512, AT_SMEM, true, wo, w1, w3, w2, c, wmod, 0u);
  launch(k_wo, 128, 256, WO_SMEM, true, mO, x);
  launch(k_lngemm<true>, 128, 384, LN_SMEM, true, mX, m1, m3, c, wmod, x);
  launch(k_w2, 128, 288, W2_SMEM, true, m2, (bf16*)d_out);
}
```

```cpp
#include <cuda_runtime.h>
#include <cuda_bf16.h>
#include <cuda.h>
#include <stdint.h>
typedef __nv_bfloat16 bf16;
constexpr int S_ = 2048, D_ = 512, F_ = 1376;
__device__ __align__(1024) float g_mod[3072];
__device__ __align__(1024) uint32_t g_modv[1024 + 4096];
__device__ __align__(1024) bf16 g_qkv[192 * 2048 * 8];
__device__ __align__(1024) float g_kmax[32 * 128];
__device__ __align__(1024) bf16 g_o[16 * 64 * 128 * 8];
__device__ __align__(1024) bf16 g_x1[16 * 64 * 128 * 8];
__device__ __align__(1024) float2 g_st[2048 * 8];
__device__ __align__(1024) bf16 g_h[16 * 172 * 128 * 8];

__device__ __forceinline__ uint32_t smem_u32(const void* p) { return (uint32_t)__cvta_generic_to_shared(p); }
__device__ __forceinline__ void mbar_init(uint32_t b, int n) { asm volatile("mbarrier.init.shared::cta.b64 [%0],%1;" ::"r"(b), "r"(n) : "memory"); }
__device__ __forceinline__ void mbar_expect(uint32_t b, int bytes) { asm volatile("mbarrier.arrive.expect_tx.shared::cta.b64 _,[%0],%1;" ::"r"(b), "r"(bytes) : "memory"); }
__device__ __forceinline__ void mbar_arrive(uint32_t b) { asm volatile("mbarrier.arrive.shared::cta.b64 _,[%0];" ::"r"(b) : "memory"); }
__device__ __forceinline__ void mbar_wait(uint32_t b, int parity) {
  asm volatile("{\n.reg .pred p;\n.reg .u32 n;\nmov.u32 n,0;\nLW:\nmbarrier.try_wait.parity.shared::cta.b64 p,[%0],%1;\n@p bra LD;\n"
               "add.u32 n,n,1;\nsetp.lt.u32 p,n,4194304;\n@p bra LW;\nLD:\n}\n" ::"r"(b), "r"(parity) : "memory");
}
__device__ __forceinline__ void fence_init() { asm volatile("fence.mbarrier_init.release.cluster;" ::: "memory"); }
__device__ __forceinline__ void fence_async() { asm volatile("fence.proxy.async.shared::cta;" ::: "memory"); }
__device__ __forceinline__ void bulk_load(uint32_t dst, const void* src, int bytes, uint32_t bar) {
  asm volatile("cp.async.bulk.shared::cluster.global.mbarrier::complete_tx::bytes [%0],[%1],%2,[%3];" ::"r"(dst), "l"(src), "r"(bytes), "r"(bar) : "memory");
}
__device__ __forceinline__ void tma2d(uint32_t dst, const CUtensorMap* m, int c0, int c1, uint32_t bar) {
  asm volatile("cp.async.bulk.tensor.2d.shared::cluster.global.mbarrier::complete_tx::bytes [%0],[%1,{%3,%4}],[%2];" ::"r"(dst), "l"(m), "r"(bar), "r"(c0), "r"(c1) : "memory");
}
__device__ __forceinline__ void bulk_load_mc(uint32_t dst, const void* src, int bytes, uint32_t bar) {
  asm volatile("cp.async.bulk.shared::cluster.global.mbarrier::complete_tx::bytes.multicast::cluster [%0],[%1],%2,[%3],%4;" ::"r"(dst), "l"(src), "r"(bytes), "r"(bar), "h"((uint16_t)3) : "memory");
}
__device__ __forceinline__ void tma2d_mc(uint32_t dst, const CUtensorMap* m, int c0, int c1, uint32_t bar) {
  asm volatile("cp.async.bulk.tensor.2d.shared::cluster.global.mbarrier::complete_tx::bytes.multicast::cluster [%0],[%1,{%3,%4}],[%2],%5;" ::"r"(dst), "l"(m), "r"(bar), "r"(c0), "r"(c1), "h"((uint16_t)3) : "memory");
}
__device__ __forceinline__ void cluster_arrive() { asm volatile("barrier.cluster.arrive.relaxed.aligned;" ::: "memory"); }
__device__ __forceinline__ void cluster_wait() { asm volatile("barrier.cluster.wait.aligned;" ::: "memory"); }
__device__ __forceinline__ void cluster_sync() { asm volatile("barrier.cluster.arrive.release.aligned;\nbarrier.cluster.wait.acquire.aligned;" ::: "memory"); }
__device__ __forceinline__ void l2_prefetch(const void* p, int bytes) { asm volatile("cp.async.bulk.prefetch.L2.global [%0],%1;" ::"l"(p), "r"(bytes) : "memory"); }
__device__ __forceinline__ void pdl_launch() { asm volatile("griddepcontrol.launch_dependents;" ::: "memory"); }
__device__ __forceinline__ void pdl_wait() { asm volatile("griddepcontrol.wait;" ::: "memory"); }
__device__ __forceinline__ void wg_fence() { asm volatile("wgmma.fence.sync.aligned;" ::: "memory"); }
__device__ __forceinline__ void wg_commit() { asm volatile("wgmma.commit_group.sync.aligned;" ::: "memory"); }
template <int N> __device__ __forceinline__ void wg_wait() { asm volatile("wgmma.wait_group.sync.aligned %0;" ::"n"(N) : "memory"); }
template <int N> __device__ __forceinline__ void reg_fence(float (&d)[N]) {
#pragma unroll
  for (int i = 0; i < N; i++) asm volatile("" : "+f"(d[i])::"memory");
}
template <int N> __device__ __forceinline__ void zero(float (&d)[N]) {
#pragma unroll
  for (int i = 0; i < N; i++) d[i] = 0.f;
  reg_fence(d);
}
__device__ __forceinline__ uint64_t mk_desc(uint32_t addr, uint32_t lbo, uint32_t sbo, uint32_t mode) {
  return (uint64_t)((addr >> 4) & 0x3FFF) | ((uint64_t)(lbo >> 4) << 16) | ((uint64_t)(sbo >> 4) << 32) | ((uint64_t)mode << 62);
}
__device__ __forceinline__ void ldsm4(uint32_t a, uint32_t (&r)[4]) {
  asm volatile("ldmatrix.sync.aligned.m8n8.x4.shared.b16 {%0,%1,%2,%3},[%4];" : "=r"(r[0]), "=r"(r[1]), "=r"(r[2]), "=r"(r[3]) : "r"(a) : "memory");
}
__device__ __forceinline__ uint32_t pack_rn(float lo, float hi) { uint32_t r; asm("cvt.rn.bf16x2.f32 %0,%1,%2;" : "=r"(r) : "f"(hi), "f"(lo)); return r; }
__device__ __forceinline__ uint32_t pack_rz(float lo, float hi) { uint32_t r; asm("cvt.rz.bf16x2.f32 %0,%1,%2;" : "=r"(r) : "f"(hi), "f"(lo)); return r; }
__device__ __forceinline__ float blo(uint32_t u) { return __uint_as_float(u << 16); }
__device__ __forceinline__ float bhi(uint32_t u) { return __uint_as_float(u & 0xFFFF0000u); }
__device__ __forceinline__ float rbf(float x) { return __bfloat162float(__float2bfloat16_rn(x)); }
__device__ __forceinline__ float qsum(float v) { v += __shfl_xor_sync(~0u, v, 1); return v + __shfl_xor_sync(~0u, v, 2); }
__device__ __forceinline__ float ex2(float x) { float r; asm("ex2.approx.ftz.f32 %0,%1;" : "=f"(r) : "f"(x)); return r; }
#define TS(k, i)
__device__ __forceinline__ void wgmma_rs_n176_t1(float (&d)[88],uint32_t a0,uint32_t a1,uint32_t a2,uint32_t a3,uint64_t db,int sc){
  asm volatile("{\n.reg .pred p;\nsetp.ne.b32 p,%93,0;\n"
    "wgmma.mma_async.sync.aligned.m64n176k16.f32.bf16.bf16 {%0,%1,%2,%3,%4,%5,%6,%7,%8,%9,%10,%11,%12,%13,%14,%15,%16,%17,%18,%19,%20,%21,%22,%23,%24,%25,%26,%27,%28,%29,%30,%31,%32,%33,%34,%35,%36,%37,%38,%39,%40,%41,%42,%43,%44,%45,%46,%47,%48,%49,%50,%51,%52,%53,%54,%55,%56,%57,%58,%59,%60,%61,%62,%63,%64,%65,%66,%67,%68,%69,%70,%71,%72,%73,%74,%75,%76,%77,%78,%79,%80,%81,%82,%83,%84,%85,%86,%87},{%88,%89,%90,%91},%92,p,1,1,1;\n}\n"
    :"+f"(d[0]),"+f"(d[1]),"+f"(d[2]),"+f"(d[3]),"+f"(d[4]),"+f"(d[5]),"+f"(d[6]),"+f"(d[7]),"+f"(d[8]),"+f"(d[9]),"+f"(d[10]),"+f"(d[11]),"+f"(d[12]),"+f"(d[13]),"+f"(d[14]),"+f"(d[15]),"+f"(d[16]),"+f"(d[17]),"+f"(d[18]),"+f"(d[19]),"+f"(d[20]),"+f"(d[21]),"+f"(d[22]),"+f"(d[23]),"+f"(d[24]),"+f"(d[25]),"+f"(d[26]),"+f"(d[27]),"+f"(d[28]),"+f"(d[29]),"+f"(d[30]),"+f"(d[31]),"+f"(d[32]),"+f"(d[33]),"+f"(d[34]),"+f"(d[35]),"+f"(d[36]),"+f"(d[37]),"+f"(d[38]),"+f"(d[39]),"+f"(d[40]),"+f"(d[41]),"+f"(d[42]),"+f"(d[43]),"+f"(d[44]),"+f"(d[45]),"+f"(d[46]),"+f"(d[47]),"+f"(d[48]),"+f"(d[49]),"+f"(d[50]),"+f"(d[51]),"+f"(d[52]),"+f"(d[53]),"+f"(d[54]),"+f"(d[55]),"+f"(d[56]),"+f"(d[57]),"+f"(d[58]),"+f"(d[59]),"+f"(d[60]),"+f"(d[61]),"+f"(d[62]),"+f"(d[63]),"+f"(d[64]),"+f"(d[65]),"+f"(d[66]),"+f"(d[67]),"+f"(d[68]),"+f"(d[69]),"+f"(d[70]),"+f"(d[71]),"+f"(d[72]),"+f"(d[73]),"+f"(d[74]),"+f"(d[75]),"+f"(d[76]),"+f"(d[77]),"+f"(d[78]),"+f"(d[79]),"+f"(d[80]),"+f"(d[81]),"+f"(d[82]),"+f"(d[83]),"+f"(d[84]),"+f"(d[85]),"+f"(d[86]),"+f"(d[87])
    :"r"(a0),"r"(a1),"r"(a2),"r"(a3),"l"(db),"r"(sc));
}
__device__ __forceinline__ void wgmma_rs_n192_t1(float (&d)[96],uint32_t a0,uint32_t a1,uint32_t a2,uint32_t a3,uint64_t db,int sc){
  asm volatile("{\n.reg .pred p;\nsetp.ne.b32 p,%101,0;\n"
    "wgmma.mma_async.sync.aligned.m64n192k16.f32.bf16.bf16 {%0,%1,%2,%3,%4,%5,%6,%7,%8,%9,%10,%11,%12,%13,%14,%15,%16,%17,%18,%19,%20,%21,%22,%23,%24,%25,%26,%27,%28,%29,%30,%31,%32,%33,%34,%35,%36,%37,%38,%39,%40,%41,%42,%43,%44,%45,%46,%47,%48,%49,%50,%51,%52,%53,%54,%55,%56,%57,%58,%59,%60,%61,%62,%63,%64,%65,%66,%67,%68,%69,%70,%71,%72,%73,%74,%75,%76,%77,%78,%79,%80,%81,%82,%83,%84,%85,%86,%87,%88,%89,%90,%91,%92,%93,%94,%95},{%96,%97,%98,%99},%100,p,1,1,1;\n}\n"
    :"+f"(d[0]),"+f"(d[1]),"+f"(d[2]),"+f"(d[3]),"+f"(d[4]),"+f"(d[5]),"+f"(d[6]),"+f"(d[7]),"+f"(d[8]),"+f"(d[9]),"+f"(d[10]),"+f"(d[11]),"+f"(d[12]),"+f"(d[13]),"+f"(d[14]),"+f"(d[15]),"+f"(d[16]),"+f"(d[17]),"+f"(d[18]),"+f"(d[19]),"+f"(d[20]),"+f"(d[21]),"+f"(d[22]),"+f"(d[23]),"+f"(d[24]),"+f"(d[25]),"+f"(d[26]),"+f"(d[27]),"+f"(d[28]),"+f"(d[29]),"+f"(d[30]),"+f"(d[31]),"+f"(d[32]),"+f"(d[33]),"+f"(d[34]),"+f"(d[35]),"+f"(d[36]),"+f"(d[37]),"+f"(d[38]),"+f"(d[39]),"+f"(d[40]),"+f"(d[41]),"+f"(d[42]),"+f"(d[43]),"+f"(d[44]),"+f"(d[45]),"+f"(d[46]),"+f"(d[47]),"+f"(d[48]),"+f"(d[49]),"+f"(d[50]),"+f"(d[51]),"+f"(d[52]),"+f"(d[53]),"+f"(d[54]),"+f"(d[55]),"+f"(d[56]),"+f"(d[57]),"+f"(d[58]),"+f"(d[59]),"+f"(d[60]),"+f"(d[61]),"+f"(d[62]),"+f"(d[63]),"+f"(d[64]),"+f"(d[65]),"+f"(d[66]),"+f"(d[67]),"+f"(d[68]),"+f"(d[69]),"+f"(d[70]),"+f"(d[71]),"+f"(d[72]),"+f"(d[73]),"+f"(d[74]),"+f"(d[75]),"+f"(d[76]),"+f"(d[77]),"+f"(d[78]),"+f"(d[79]),"+f"(d[80]),"+f"(d[81]),"+f"(d[82]),"+f"(d[83]),"+f"(d[84]),"+f"(d[85]),"+f"(d[86]),"+f"(d[87]),"+f"(d[88]),"+f"(d[89]),"+f"(d[90]),"+f"(d[91]),"+f"(d[92]),"+f"(d[93]),"+f"(d[94]),"+f"(d[95])
    :"r"(a0),"r"(a1),"r"(a2),"r"(a3),"l"(db),"r"(sc));
}
__device__ __forceinline__ void wgmma_rs_n24_t1(float (&d)[12],uint32_t a0,uint32_t a1,uint32_t a2,uint32_t a3,uint64_t db,int sc){
  asm volatile("{\n.reg .pred p;\nsetp.ne.b32 p,%17,0;\n"
    "wgmma.mma_async.sync.aligned.m64n24k16.f32.bf16.bf16 {%0,%1,%2,%3,%4,%5,%6,%7,%8,%9,%10,%11},{%12,%13,%14,%15},%16,p,1,1,1;\n}\n"
    :"+f"(d[0]),"+f"(d[1]),"+f"(d[2]),"+f"(d[3]),"+f"(d[4]),"+f"(d[5]),"+f"(d[6]),"+f"(d[7]),"+f"(d[8]),"+f"(d[9]),"+f"(d[10]),"+f"(d[11])
    :"r"(a0),"r"(a1),"r"(a2),"r"(a3),"l"(db),"r"(sc));
}
__device__ __forceinline__ void wgmma_rs_n64_t0(float (&d)[32],uint32_t a0,uint32_t a1,uint32_t a2,uint32_t a3,uint64_t db,int sc){
  asm volatile("{\n.reg .pred p;\nsetp.ne.b32 p,%37,0;\n"
    "wgmma.mma_async.sync.aligned.m64n64k16.f32.bf16.bf16 {%0,%1,%2,%3,%4,%5,%6,%7,%8,%9,%10,%11,%12,%13,%14,%15,%16,%17,%18,%19,%20,%21,%22,%23,%24,%25,%26,%27,%28,%29,%30,%31},{%32,%33,%34,%35},%36,p,1,1,0;\n}\n"
    :"+f"(d[0]),"+f"(d[1]),"+f"(d[2]),"+f"(d[3]),"+f"(d[4]),"+f"(d[5]),"+f"(d[6]),"+f"(d[7]),"+f"(d[8]),"+f"(d[9]),"+f"(d[10]),"+f"(d[11]),"+f"(d[12]),"+f"(d[13]),"+f"(d[14]),"+f"(d[15]),"+f"(d[16]),"+f"(d[17]),"+f"(d[18]),"+f"(d[19]),"+f"(d[20]),"+f"(d[21]),"+f"(d[22]),"+f"(d[23]),"+f"(d[24]),"+f"(d[25]),"+f"(d[26]),"+f"(d[27]),"+f"(d[28]),"+f"(d[29]),"+f"(d[30]),"+f"(d[31])
    :"r"(a0),"r"(a1),"r"(a2),"r"(a3),"l"(db),"r"(sc));
}
__device__ __forceinline__ void wgmma_ss_n128_t1(float (&d)[64],uint64_t da,uint64_t db,int sc){
  asm volatile("{\n.reg .pred p;\nsetp.ne.b32 p,%66,0;\n"
    "wgmma.mma_async.sync.aligned.m64n128k16.f32.bf16.bf16 {%0,%1,%2,%3,%4,%5,%6,%7,%8,%9,%10,%11,%12,%13,%14,%15,%16,%17,%18,%19,%20,%21,%22,%23,%24,%25,%26,%27,%28,%29,%30,%31,%32,%33,%34,%35,%36,%37,%38,%39,%40,%41,%42,%43,%44,%45,%46,%47,%48,%49,%50,%51,%52,%53,%54,%55,%56,%57,%58,%59,%60,%61,%62,%63},%64,%65,p,1,1,0,1;\n}\n"
    :"+f"(d[0]),"+f"(d[1]),"+f"(d[2]),"+f"(d[3]),"+f"(d[4]),"+f"(d[5]),"+f"(d[6]),"+f"(d[7]),"+f"(d[8]),"+f"(d[9]),"+f"(d[10]),"+f"(d[11]),"+f"(d[12]),"+f"(d[13]),"+f"(d[14]),"+f"(d[15]),"+f"(d[16]),"+f"(d[17]),"+f"(d[18]),"+f"(d[19]),"+f"(d[20]),"+f"(d[21]),"+f"(d[22]),"+f"(d[23]),"+f"(d[24]),"+f"(d[25]),"+f"(d[26]),"+f"(d[27]),"+f"(d[28]),"+f"(d[29]),"+f"(d[30]),"+f"(d[31]),"+f"(d[32]),"+f"(d[33]),"+f"(d[34]),"+f"(d[35]),"+f"(d[36]),"+f"(d[37]),"+f"(d[38]),"+f"(d[39]),"+f"(d[40]),"+f"(d[41]),"+f"(d[42]),"+f"(d[43]),"+f"(d[44]),"+f"(d[45]),"+f"(d[46]),"+f"(d[47]),"+f"(d[48]),"+f"(d[49]),"+f"(d[50]),"+f"(d[51]),"+f"(d[52]),"+f"(d[53]),"+f"(d[54]),"+f"(d[55]),"+f"(d[56]),"+f"(d[57]),"+f"(d[58]),"+f"(d[59]),"+f"(d[60]),"+f"(d[61]),"+f"(d[62]),"+f"(d[63])
    :"l"(da),"l"(db),"r"(sc));
}
__device__ __forceinline__ void wgmma_ss_n64_t1(float (&d)[32],uint64_t da,uint64_t db,int sc){
  asm volatile("{\n.reg .pred p;\nsetp.ne.b32 p,%34,0;\n"
    "wgmma.mma_async.sync.aligned.m64n64k16.f32.bf16.bf16 {%0,%1,%2,%3,%4,%5,%6,%7,%8,%9,%10,%11,%12,%13,%14,%15,%16,%17,%18,%19,%20,%21,%22,%23,%24,%25,%26,%27,%28,%29,%30,%31},%32,%33,p,1,1,0,1;\n}\n"
    :"+f"(d[0]),"+f"(d[1]),"+f"(d[2]),"+f"(d[3]),"+f"(d[4]),"+f"(d[5]),"+f"(d[6]),"+f"(d[7]),"+f"(d[8]),"+f"(d[9]),"+f"(d[10]),"+f"(d[11]),"+f"(d[12]),"+f"(d[13]),"+f"(d[14]),"+f"(d[15]),"+f"(d[16]),"+f"(d[17]),"+f"(d[18]),"+f"(d[19]),"+f"(d[20]),"+f"(d[21]),"+f"(d[22]),"+f"(d[23]),"+f"(d[24]),"+f"(d[25]),"+f"(d[26]),"+f"(d[27]),"+f"(d[28]),"+f"(d[29]),"+f"(d[30]),"+f"(d[31])
    :"l"(da),"l"(db),"r"(sc));
}

__device__ __forceinline__ float silu_bf(bf16 c) { const float x = __bfloat162float(c); return rbf(x / (1.f + __expf(-x))); }
__device__ __forceinline__ void fma8(float (&a)[8], float s, const uint4& v) {
  a[0] += s * blo(v.x); a[1] += s * bhi(v.x); a[2] += s * blo(v.y); a[3] += s * bhi(v.y);
  a[4] += s * blo(v.z); a[5] += s * bhi(v.z); a[6] += s * blo(v.w); a[7] += s * bhi(v.w);
}
__device__ __forceinline__ float red8(float (&a)[8], int lane) {
#pragma unroll
  for (int w = 4; w >= 1; w >>= 1) {
    const bool up = lane & (w * 4);
#pragma unroll
    for (int j = 0; j < w; j++) a[j] = (up ? a[j + w] : a[j]) + __shfl_xor_sync(~0u, up ? a[j] : a[j + w], w * 4);
  }
  return a[0];
}
__device__ __forceinline__ float mod_fin(float s, int n) { s = rbf(s); return ((n >> 9) == 1 || (n >> 9) == 4) ? rbf(1.f + s) : s; }
__device__ __forceinline__ void poll4(uint2& a, uint2& b, uint2& c, uint2& d, const uint32_t* p, const uint32_t* q) {
  asm volatile("{\n.reg .pred p;\n.reg .u32 n,t;\nmov.u32 n,0;\nLW:\nld.relaxed.gpu.global.v2.u32 {%0,%1},[%8];\nld.relaxed.gpu.global.v2.u32 {%2,%3},[%8+64];\n"
               "ld.relaxed.gpu.global.v2.u32 {%4,%5},[%9];\nld.relaxed.gpu.global.v2.u32 {%6,%7},[%9+2048];\n"
               "lop3.b32 t,%0,%1,%2,0x80;\nlop3.b32 t,t,%3,%4,0x80;\nlop3.b32 t,t,%5,%6,0x80;\nlop3.b32 t,t,%7,1,0x80;\n"
               "setp.ne.u32 p,t,0;\n@p bra LD;\nadd.u32 n,n,1;\nsetp.lt.u32 p,n,1048576;\n@p bra LW;\nLD:\n}\n"
               : "=&r"(a.x), "=&r"(a.y), "=&r"(b.x), "=&r"(b.y), "=&r"(c.x), "=&r"(c.y), "=&r"(d.x), "=&r"(d.y) : "l"(p), "l"(q) : "memory");
}

constexpr int LN_SMEM = 131072 + 4 * 24576 + 2048 + 256 + 512;
template <bool FFN>
__global__ void __cluster_dims__(2, 1, 1) __launch_bounds__(384, 1) k_lngemm(const __grid_constant__ CUtensorMap mX, const __grid_constant__ CUtensorMap mB0,
                                                   const __grid_constant__ CUtensorMap mB1, const bf16* __restrict__ cv, const bf16* __restrict__ wm, const bf16* __restrict__ xg) {
  extern __shared__ __align__(1024) uint8_t smem[];
  const uint32_t sA = smem_u32(smem), sB = sA + (FFN ? 81920 : 131072), sM = sA + 229376, bars = sM + 2048;
  const uint32_t bA = bars, bF = bars + 64, bE = bars + 112;
  constexpr int NB = FFN ? 6 : 4;
  const int tid = threadIdx.x, warp = tid >> 5, lane = tid & 31;
  const int pr = blockIdx.x & 1, rb = FFN ? (blockIdx.x >> 4) * 2 + pr : blockIdx.x >> 3, ct = FFN ? (blockIdx.x >> 1) & 7 : blockIdx.x & 7;
  constexpr int NST = FFN ? 16 : 8, KS = FFN ? 2 : 4, BOX = FFN ? 4096 : 8192;
  TS(FFN ? 4 : 1, 0);
  pdl_launch();
  float* red = (float*)(smem + (bars - sA) + 256);
  if (tid == 256) {
    for (int i = 0; i < 8; i++) mbar_init(bA + 8 * i, 1);
    for (int i = 0; i < NB; i++) { mbar_init(bF + 8 * i, 1); mbar_init(bE + 8 * i, FFN ? 16 : 8); }
    fence_init();
  }
  __syncwarp();
  cluster_arrive();
  uint4 wv0, wv1, xv[4];
  bf16 cv0, cv1;
  if (!FFN && tid < 256) {
    wv0 = __ldg((const uint4*)(wm + tid * 3072 + blockIdx.x * 8)); wv1 = __ldg((const uint4*)(wm + (tid + 256) * 3072 + blockIdx.x * 8));
    cv0 = cv[tid]; cv1 = cv[tid + 256];
#pragma unroll
    for (int i = 0; i < 4; i++) xv[i] = __ldg((const uint4*)(xg + (blockIdx.x * 16 + (tid >> 4)) * 512 + i * 128 + (tid & 15) * 8));
  }
  cluster_wait();
  if (warp >= 8) {
    asm volatile("setmaxnreg.dec.sync.aligned.u32 40;");
    if (tid == 256) {
      auto loadB = [&](int s) {
        const uint32_t d = sB + (s % NB) * 24576, b = bF + (s % NB) * 8;
        mbar_expect(b, 24576);
        for (int j = 0; j < 3; j++) {
          if (FFN) tma2d_mc(d + (pr * 3 + j) * BOX, pr ? &mB1 : &mB0, ct * 176 + j * 64, s * 32, b);
          else tma2d(d + j * BOX, &mB0, ct * 192 + j * 64, s * 64, b);
        }
      };
      for (int i = 0; i < 8; i++) mbar_expect(bA + 8 * i, 16384);
      for (int s = 0; s < NB; s++) {
        const int i = s * 2 + (ct & 1);
        if (!FFN) tma2d_mc(sA + i * 16384, &mX, i * 64, rb * 128, bA + 8 * i);
        loadB(s);
      }
      if (FFN) {
        pdl_wait();
        for (int i = 0; i < 2; i++) bulk_load(sA + i * 16384, g_x1 + (rb * 64 + i * 8) * 1024, 16384, bA + 8 * i);
      }
      for (int s = NB; s < NST; s++) {
        mbar_wait(bE + (s % NB) * 8, (s / NB - 1) & 1); loadB(s);
        if (FFN && s <= 10 && !(s & 1)) bulk_load(sA + (s / 2 - 3) * 16384, g_x1 + (rb * 64 + (s / 2 + 2) * 8) * 1024, 16384, bA + 8 * (s / 2 + 2));
      }
    }
  } else {
  asm volatile("setmaxnreg.inc.sync.aligned.u32 232;");
  const int g = lane >> 2, t = lane & 3;
  const int lr = warp * 16 + (lane & 7) + ((lane >> 3) & 1) * 8;
  auto aaddr = [&](int ks) -> uint32_t {
    if (FFN) return sA + ((ks < 20 ? ks : ks - 20) * 2 + (lane >> 4)) * 2048 + lr * 16;
    return sA + (ks >> 2) * 16384 + lr * 128 + ((((ks & 3) * 2 + (lane >> 4)) ^ (lr & 7)) << 4);
  };
  const int row0 = rb * 128 + warp * 16 + g;
  float2 msh, msc;
  uint2 sh, sc;
  float rs0, rs1, nm0, nm1;
  if (!FFN) {
    {
      float a[8] = {0, 0, 0, 0, 0, 0, 0, 0};
      fma8(a, silu_bf(cv0), wv0); fma8(a, silu_bf(cv1), wv1);
      const float s = qsum(red8(a, lane));
      if (t == 0) red[warp * 8 + g] = s;
      asm volatile("bar.sync 1,256;" ::: "memory");
      if (tid < 8) {
        float r = 0;
#pragma unroll
        for (int i = 0; i < 8; i++) r += red[i * 8 + tid];
        const int n = blockIdx.x * 8 + tid;
        asm volatile("st.relaxed.gpu.global.u32 [%0],%1;" ::"l"(g_modv + n), "r"(__float_as_uint(mod_fin(r, n)) | 1u) : "memory");
      }
      TS(0, 1);
    }
    {
      float v[32], s = 0, q = 0;
#pragma unroll
      for (int i = 0; i < 16; i++) { const uint32_t u = ((const uint32_t*)xv)[i]; v[2 * i] = blo(u); v[2 * i + 1] = bhi(u); s += v[2 * i] + v[2 * i + 1]; }
      s = qsum(s); s += __shfl_xor_sync(~0u, s, 4); s += __shfl_xor_sync(~0u, s, 8);
      const float m = s * (1.f / 512);
#pragma unroll
      for (int i = 0; i < 32; i++) q += (v[i] - m) * (v[i] - m);
      q = qsum(q); q += __shfl_xor_sync(~0u, q, 4); q += __shfl_xor_sync(~0u, q, 8);
      const float rs = rsqrtf(q * (1.f / 512) + 1e-5f);
      if ((tid & 15) == 0)
        asm volatile("st.relaxed.gpu.global.v2.u32 [%0],{%1,%2};" ::"l"(g_modv + 1024 + (blockIdx.x * 16 + (tid >> 4)) * 2), "r"(__float_as_uint(rs) | 1u), "r"(__float_as_uint(-m * rs) | 1u) : "memory");
    }
    uint2 p0, p1;
    poll4(p0, p1, sh, sc, g_modv + 1024 + row0 * 2, g_modv + tid * 2);
    rs0 = __uint_as_float(p0.x); nm0 = __uint_as_float(p0.y); rs1 = __uint_as_float(p1.x); nm1 = __uint_as_float(p1.y);
  } else {
    pdl_wait();
    TS(4, 1);
    msh = *(const float2*)(g_mod + 1536 + tid * 2); msc = *(const float2*)(g_mod + 2048 + tid * 2);
    const float4 p0 = *(const float4*)(g_st + row0 * 8 + t * 2), p1 = *(const float4*)(g_st + (row0 + 8) * 8 + t * 2);
    const float m0 = qsum(p0.x + p0.z) * 0.125f, m1 = qsum(p1.x + p1.z) * 0.125f;
    const float v0 = qsum(p0.y + p0.w + 64.f * ((p0.x - m0) * (p0.x - m0) + (p0.z - m0) * (p0.z - m0)));
    const float v1 = qsum(p1.y + p1.w + 64.f * ((p1.x - m1) * (p1.x - m1) + (p1.z - m1) * (p1.z - m1)));
    rs0 = rsqrtf(v0 * (1.f / 512) + 1e-5f); rs1 = rsqrtf(v1 * (1.f / 512) + 1e-5f);
    nm0 = -m0 * rs0; nm1 = -m1 * rs1;
  }
  {
    uint32_t* m = (uint32_t*)(smem + (sM - sA)) + (tid >> 3) * 16 + (tid & 3) * 4 + ((tid >> 2) & 1);
    if (FFN) { m[0] = pack_rn(msc.x, msc.y); m[2] = pack_rn(msh.x, msh.y); }
    else { m[0] = __byte_perm(sc.x, sc.y, 0x7632); m[2] = __byte_perm(sh.x, sh.y, 0x7632); }
    asm volatile("bar.sync 1,256;" ::: "memory");
  }
  if (FFN && warp >= 2 && warp < 5 && lane == 0) bulk_load(sA + warp * 16384, g_x1 + (rb * 64 + warp * 8) * 1024, 16384, bA + 8 * warp);
  constexpr int NA = FFN ? 88 : 96;
  float acc0[NA], acc1[FFN ? 88 : 1];
  uint32_t a[2][KS][4];
  auto prep = [&](int ks, uint32_t(&o)[4]) {
    if ((ks & 3) == 0) mbar_wait(bA + 2 * ks, 0);
    uint32_t r[4]; ldsm4(aaddr(ks), r);
    const uint4 m = *(const uint4*)(smem + (sM - sA) + ks * 64 + t * 16);
#pragma unroll
    for (int i = 0; i < 4; i++) {
      const float rs = (i & 1) ? rs1 : rs0, nm = (i & 1) ? nm1 : nm0;
      const uint32_t n = pack_rn(fmaf(blo(r[i]), rs, nm), fmaf(bhi(r[i]), rs, nm));
      asm("fma.rn.bf16x2 %0,%1,%2,%3;" : "=r"(o[i]) : "r"(n), "r"(i < 2 ? m.x : m.y), "r"(i < 2 ? m.z : m.w));
    }
  };
  auto stage = [&](int s, uint32_t(&c)[KS][4], uint32_t(&n)[KS][4]) {
    mbar_wait(bF + (s % NB) * 8, (s / NB) & 1);
    const uint64_t db = mk_desc(sB + (s % NB) * 24576, BOX, 1024, 1);
    wg_fence();
#pragma unroll
    for (int k = 0; k < KS; k++) {
      if constexpr (FFN) {
        wgmma_rs_n176_t1(acc0, c[k][0], c[k][1], c[k][2], c[k][3], db + k * 128, s + k);
        wgmma_rs_n176_t1(acc1, c[k][0], c[k][1], c[k][2], c[k][3], db + k * 128 + 3 * BOX / 16, s + k);
      } else {
        wgmma_rs_n192_t1(acc0, c[k][0], c[k][1], c[k][2], c[k][3], db + k * 128, s + k);
      }
    }
    wg_commit();
    wg_wait<1>();
    if (s > 0 && s <= NST - NB) {
      if (!FFN) { if (lane == 0) mbar_arrive(bE + ((s - 1) % NB) * 8); }
      else if (lane < 2) asm volatile("{\n.reg .b32 r;\nmapa.shared::cluster.u32 r,%0,%1;\nmbarrier.arrive.relaxed.cluster.shared::cluster.b64 _,[r];\n}" ::"r"(bE + ((s - 1) % NB) * 8), "r"(lane) : "memory");
    }
    if (s < NST - 1) {
#pragma unroll
      for (int k = 0; k < KS; k++) prep((s + 1) * KS + k, n[k]);
    }
  };
#pragma unroll
  for (int k = 0; k < KS; k++) prep(k, a[0][k]);
  TS(FFN ? 4 : 1, 2);
#pragma unroll 1
  for (int s = 0; s < NST; s += 2) { stage(s, a[0], a[1]); stage(s + 1, a[1], a[0]); }
  wg_wait<0>();
  reg_fence(acc0);
  TS(FFN ? 4 : 1, 3);
  if constexpr (FFN) {
    reg_fence(acc1);
    uint32_t* o = (uint32_t*)g_h + ((rb * 172 + ct * 22) * 128 + warp * 16 + g) * 4 + t;
#pragma unroll
    for (int j = 0; j < 22; j++) {
      {
        float h[4], d[4];
#pragma unroll
        for (int i = 0; i < 4; i++) { const float x = acc0[4 * j + i]; d[i] = 1.f + ex2(fminf(-1.4426950408889634f * x, 30.f)); h[i] = x * acc1[4 * j + i]; }
        const float d01 = d[0] * d[1], d23 = d[2] * d[3];
        float r; asm("rcp.approx.ftz.f32 %0,%1;" : "=f"(r) : "f"(d01 * d23));
        const float r01 = r * d23, r23 = r * d01;
        h[0] *= r01 * d[1]; h[1] *= r01 * d[0]; h[2] *= r23 * d[3]; h[3] *= r23 * d[2];
        if (j < 18 || ct < 7) { o[j * 512] = pack_rn(h[0], h[1]); o[j * 512 + 32] = pack_rn(h[2], h[3]); }
      }
    }
  } else {
    uint32_t* o = (uint32_t*)g_qkv + (ct * 24 * 2048 + row0) * 4 + t;
#pragma unroll
    for (int j = 0; j < 24; j += 2) {
      const int G = ct * 24 + j;
      const float sc = G < 64 ? 0.25f * 1.4426950408889634f : 1.f;
      uint32_t p[4];
#pragma unroll
      for (int i = 0; i < 4; i++) p[i] = pack_rn(acc0[4 * j + 2 * i] * sc, acc0[4 * j + 2 * i + 1] * sc);
      o[j * 8192] = p[0]; o[j * 8192 + 32] = p[1]; o[(j + 1) * 8192] = p[2]; o[(j + 1) * 8192 + 32] = p[3];
      if (G >= 64 && G < 128) {
        float n0 = blo(p[0]) * blo(p[0]) + bhi(p[0]) * bhi(p[0]) + blo(p[2]) * blo(p[2]) + bhi(p[2]) * bhi(p[2]);
        float n1 = blo(p[1]) * blo(p[1]) + bhi(p[1]) * bhi(p[1]) + blo(p[3]) * blo(p[3]) + bhi(p[3]) * bhi(p[3]);
        n0 = qsum(n0); n1 = qsum(n1);
        const uint32_t mx = __reduce_max_sync(~0u, max(__float_as_uint(n0), __float_as_uint(n1)));
        if (lane == 0) g_kmax[((G - 64) >> 1) * 128 + rb * 8 + warp] = __uint_as_float(mx);
      }
    }
  }
  TS(FFN ? 4 : 1, 4);
}
}

#define SMASK 0xAAAAu
#define BRK 0
#define PACK 1
constexpr int AT_SMEM = 5 * 32768 + 256;
__device__ __forceinline__ uint32_t exp2_pair_fma(float s0, float s1, float c, uint32_t ka, uint32_t kz) {
  uint32_t r;
  asm volatile("{\n.reg .b32 y0,y1,e,u,t;\n"
      "fma.rn.sat.f32 y0,%1,0f00000080,%3;\nfma.rn.sat.f32 y1,%2,0f00000080,%3;\n"
      "mad.lo.u32 e,y1,65536,y0;\n"
      "and.b32 u,e,0x007F007F;\n"
      "fma.rn.f16x2 u,u,%4,%5;\nfma.rn.f16x2 t,u,u,%6;\nfma.rn.f16x2 t,t,u,%7;\n"
      "lop3.b32 %0,t,0x007F007F,e,0xE2;\n}\n"
      : "=r"(r) : "f"(s0), "f"(s1), "f"(c), "r"(ka), "r"(0x36B236B2u), "r"(0x3C733C73u), "r"(0x47764776u), "r"(kz));
  return r;
}
__device__ __forceinline__ void attn_pass(float (&oa)[12], float (&ob)[12], const uint32_t (&q)[4], float m0, float m1, uint32_t sK, uint32_t bars, bool first, uint32_t kz) {
  uint64_t dk = mk_desc(sK, 32768, 128, 0), dv = mk_desc(sK + 65536, 128, 32768, 0);
  const float c0 = (127.f - m0) * __uint_as_float(0x80u), c1 = (127.f - m1) * __uint_as_float(0x80u);
  uint32_t ka;
  asm volatile("mov.b32 %0,0x7ACE7ACE;" : "=r"(ka));
  constexpr int NK = 64, NS = 32, NP = 16;
  auto qk = [&](float (&s)[NS], int i) { wgmma_rs_n64_t0(s, q[0], q[1], q[2], q[3], dk + i * NK, 0); };
  auto softmax = [&](float (&s)[NS], uint32_t (&p)[NP], uint32_t mask) {
    reg_fence(s);
    float e0, e1;
    int pend = -1;
#pragma unroll
    for (int t = 0; t < NP; t++) {
      const int j = (t & 3) * 4 + (t >> 2);
      if ((mask >> (t & 3)) & 1) {
        p[j] = exp2_pair_fma(s[2 * j], s[2 * j + 1], (j & 1) ? c1 : c0, ka, kz);
      } else {
        float f0, f1;
        asm volatile("ex2.approx.ftz.f32 %0,%2;\nex2.approx.ftz.f32 %1,%3;" : "=&f"(f0), "=f"(f1) : "f"(s[2 * j]), "f"(s[2 * j + 1]));
        if (pend >= 0) asm volatile("cvt.rn.bf16x2.f32 %0,%1,%2;" : "=r"(p[pend]) : "f"(e1), "f"(e0));
        e0 = f0; e1 = f1; pend = j;
      }
    }
    if (pend >= 0) asm volatile("cvt.rn.bf16x2.f32 %0,%1,%2;" : "=r"(p[pend]) : "f"(e1), "f"(e0));
#pragma unroll
    for (int j = 0; j < NP; j++) asm volatile("" : "+r"(p[j])::"memory");
  };
  auto pv = [&](uint32_t (&p)[NP], int i, uint32_t mask) {
#pragma unroll
    for (int k = 0; k < 4; k++) wgmma_rs_n24_t1(((mask >> k) & 1) ? ob : oa, p[4 * k], p[4 * k + 1], p[4 * k + 2], p[4 * k + 3], dv + i * NK + k * 16, 1);
  };
  constexpr uint32_t M0 = SMASK & 15, M1 = (SMASK >> 4) & 15, M2 = (SMASK >> 8) & 15, M3 = SMASK >> 12;
  zero(oa); zero(ob);
  mbar_wait(bars, 0);
  if (first) TS(2, 2);
  float s[NS];
  zero(s);
  uint32_t p0[NP], p1[NP];
  auto step = [&](int i, uint32_t (&pa)[NP], uint32_t ma, uint32_t (&pb)[NP], uint32_t mb) {
    wg_fence(); qk(s, i + 1); wg_commit(); pv(pa, i, ma); wg_commit(); wg_wait<1>(); softmax(s, pb, mb); wg_wait<0>();
  };
  wg_fence(); qk(s, 0); wg_commit(); wg_wait<0>(); softmax(s, p0, M0);
#pragma unroll 1
  for (uint32_t b = bars + 8; b < bars + 64; b += 8) {
    step(0, p0, M0, p1, M1); step(1, p1, M1, p0, M2); step(2, p0, M2, p1, M3);
    mbar_wait(b, 0);
    step(3, p1, M3, p0, M0);
    dk += 4 * NK; dv += 4 * NK;
  }
  step(0, p0, M0, p1, M1); step(1, p1, M1, p0, M2); step(2, p0, M2, p1, M3);
  wg_fence(); pv(p1, 3, M3); wg_commit();
  wg_wait<0>();
  reg_fence(oa); reg_fence(ob);
}
__device__ __forceinline__ void mma16816(float (&d)[4], const uint32_t (&a)[4], uint32_t b0, uint32_t b1) {
  asm("mma.sync.aligned.m16n8k16.row.col.f32.bf16.bf16.f32 {%0,%1,%2,%3},{%4,%5,%6,%7},{%8,%9},{%0,%1,%2,%3};"
      : "+f"(d[0]), "+f"(d[1]), "+f"(d[2]), "+f"(d[3]) : "r"(a[0]), "r"(a[1]), "r"(a[2]), "r"(a[3]), "r"(b0), "r"(b1));
}
__device__ __forceinline__ void attn_safe(float (&o)[12], const uint32_t (&q)[4], uint32_t sK) {
  const int lane = threadIdx.x & 31;
  const uint32_t ka = sK + (lane >> 4) * 32768 + (lane & 15) * 16;
  float m0 = -INFINITY, m1 = -INFINITY;
#pragma unroll 2
  for (int i = 0; i < 128; i++) {
    uint32_t k[4]; ldsm4(ka + i * 256, k);
    float s0[4] = {0, 0, 0, 0}, s1[4] = {0, 0, 0, 0};
    mma16816(s0, q, k[0], k[2]); mma16816(s1, q, k[1], k[3]);
    m0 = fmaxf(fmaxf(m0, fmaxf(s0[0], s0[1])), fmaxf(s1[0], s1[1])); m1 = fmaxf(fmaxf(m1, fmaxf(s0[2], s0[3])), fmaxf(s1[2], s1[3]));
  }
  m0 = fmaxf(m0, __shfl_xor_sync(~0u, m0, 1)); m0 = fmaxf(m0, __shfl_xor_sync(~0u, m0, 2));
  m1 = fmaxf(m1, __shfl_xor_sync(~0u, m1, 1)); m1 = fmaxf(m1, __shfl_xor_sync(~0u, m1, 2));
  float o0[4] = {0, 0, 0, 0}, o1[4] = {0, 0, 0, 0}, o2[4] = {0, 0, 0, 0};
#pragma unroll 2
  for (int i = 0; i < 128; i++) {
    uint32_t k[4], v[4]; ldsm4(ka + i * 256, k);
    asm volatile("ldmatrix.sync.aligned.m8n8.x4.trans.shared.b16 {%0,%1,%2,%3},[%4];" : "=r"(v[0]), "=r"(v[1]), "=r"(v[2]), "=r"(v[3]) : "r"(ka + 65536 + i * 256) : "memory");
    float s0[4] = {0, 0, 0, 0}, s1[4] = {0, 0, 0, 0};
    mma16816(s0, q, k[0], k[2]); mma16816(s1, q, k[1], k[3]);
    const uint32_t p[4] = {pack_rn(ex2(s0[0] - m0), ex2(s0[1] - m0)), pack_rn(ex2(s0[2] - m1), ex2(s0[3] - m1)),
                           pack_rn(ex2(s1[0] - m0), ex2(s1[1] - m0)), pack_rn(ex2(s1[2] - m1), ex2(s1[3] - m1))};
    mma16816(o0, p, v[0], v[1]); mma16816(o1, p, v[2], v[3]); mma16816(o2, p, 0x3F803F80u, 0x3F803F80u);
  }
#pragma unroll
  for (int i = 0; i < 4; i++) { o[i] = o0[i]; o[4 + i] = o1[i]; o[8 + i] = o2[i]; }
}
__global__ void __cluster_dims__(2, 1, 1) __launch_bounds__(512, 1) k_attn(const bf16* wo, const bf16* w1, const bf16* w3, const bf16* w2, const bf16* __restrict__ cv, const bf16* __restrict__ wm, uint32_t kz) {
  extern __shared__ __align__(1024) uint8_t smem[];
  const uint32_t sK = smem_u32(smem), bars = sK + 5 * 32768;
  const int tid = threadIdx.x, warp = tid >> 5, lane = tid & 31, g = lane >> 2, t = lane & 3;
  pdl_launch();
  if (blockIdx.x < 4) {
    float* cs = (float*)smem;
    cs[tid] = silu_bf(cv[tid]);
    __syncthreads();
    const int n0 = 1024 + blockIdx.x * 512, r0 = (tid >> 6) * 64;
    float a[8] = {0, 0, 0, 0, 0, 0, 0, 0};
#pragma unroll 16
    for (int r = r0; r < r0 + 64; r++) fma8(a, cs[r], __ldg((const uint4*)(wm + r * 3072 + n0 + (tid & 63) * 8)));
    float4* rp = (float4*)(cs + 512 + tid * 8);
    rp[0] = make_float4(a[0], a[1], a[2], a[3]); rp[1] = make_float4(a[4], a[5], a[6], a[7]);
    __syncthreads();
    float s = 0;
#pragma unroll
    for (int i = 0; i < 8; i++) s += cs[512 + i * 512 + tid];
    g_mod[n0 + tid] = mod_fin(s, n0 + tid);
    return;
  }
  const int bid = blockIdx.x - 4, h = bid >> 2, qb = bid & 3;
  TS(2, 0);
  if (tid == 0) { for (int i = 0; i < 8; i++) { mbar_init(bars + 8 * i, 1); mbar_expect(bars + 8 * i, 16384); } fence_init(); }
#pragma unroll
  for (int i = 0; i < 4; i++) *(uint4*)(smem + 131072 + i * 8192 + tid * 16) = make_uint4(0x3F803F80u, 0x3F803F80u, 0x3F803F80u, 0x3F803F80u);
  fence_async();
  cluster_sync();
  pdl_wait();
  TS(2, 1);
  if (tid >= 472) g_modv[bid * 40 + tid - 472] = 0;
  const uint4 km4 = *(const uint4*)(g_kmax + h * 128 + lane * 4);
  const uint32_t* qp = (const uint32_t*)g_qkv + (h * 2 * 2048 + qb * 512 + warp * 16 + g) * 4 + t;
  uint32_t q[4] = {qp[0], qp[32], qp[8192], qp[8192 + 32]};
  auto ldkv = [&]() {
    const int c = warp >> 1, pl = (qb & 1) + (warp & 1) * 2;
    bulk_load_mc(sK + pl * 32768 + c * 4096, g_qkv + ((64 + (pl >> 1) * 64 + h * 2 + (pl & 1)) * 2048 + c * 256) * 8, 4096, bars + 8 * c);
  };
  if (lane == 0 && warp < 4) ldkv();
  const uint32_t qn[4] = {qp[1024], qp[1024 + 32], qp[1024 + 8192], qp[1024 + 8192 + 32]};
  const float kmax = __uint_as_float(__reduce_max_sync(~0u, max(max(km4.x, km4.y), max(km4.z, km4.w))));
  if (lane == 0 && warp >= 4 && kmax != -1.f) ldkv();
#pragma unroll 1
  for (int tile = 0; tile < 2; tile++) {
    const int row = qb * 512 + tile * 256 + warp * 16 + g;
    const float n0 = qsum(blo(q[0]) * blo(q[0]) + bhi(q[0]) * bhi(q[0]) + blo(q[2]) * blo(q[2]) + bhi(q[2]) * bhi(q[2]));
    const float n1 = qsum(blo(q[1]) * blo(q[1]) + bhi(q[1]) * bhi(q[1]) + blo(q[3]) * blo(q[3]) + bhi(q[3]) * bhi(q[3]));
    const float b0 = sqrtf(n0 * kmax) * 1.001f, b1 = sqrtf(n1 * kmax) * 1.001f;
    const float m0 = fmaxf(ceilf(b0 - 100.f), 0.f), m1 = fmaxf(ceilf(b1 - 100.f), 0.f);
    float o[12], ob[12];
    attn_pass(o, ob, q, m0, m1, sK, bars, tile == 0, kz);
    const float f0 = ex2(-m0), f1 = ex2(-m1);
#pragma unroll
    for (int i = 0; i < 12; i++) o[i] = fmaf(o[i], (i & 2) ? f1 : f0, ob[i]);
    bool ok = b0 < 220.f && b1 < 220.f && o[8] >= 0x1p-90f && o[10] >= 0x1p-90f;
#pragma unroll
    for (int i = 0; i < 12; i++) ok = ok && fabsf(o[i]) < INFINITY;
    if (!__all_sync(~0u, ok)) attn_safe(o, q, sK);
    const float r0 = 1.f / o[8], r1 = 1.f / o[10];
    uint32_t* op = (uint32_t*)g_o + (((row >> 7) * 64 + h * 2) * 128 + (row & 127)) * 4 + t;
    op[0] = pack_rn(o[0] * r0, o[1] * r0); op[32] = pack_rn(o[2] * r1, o[3] * r1);
    op[512] = pack_rn(o[4] * r0, o[5] * r0); op[512 + 32] = pack_rn(o[6] * r1, o[7] * r1);
    if (tile == 0 && tid == 32) {
      l2_prefetch((const char*)wo + bid * 4096, 4096);
      l2_prefetch((const char*)w1 + bid * 11008, 11008);
      l2_prefetch((const char*)w3 + bid * 11008, 11008);
      l2_prefetch((const char*)w2 + bid * 11008, 11008);
    }
#pragma unroll
    for (int i = 0; i < 4; i++) q[i] = qn[i];
    TS(2, 3 + tile);
  }
}

constexpr int WO_SMEM = 131072 + 65536 + 256;
__global__ void __cluster_dims__(2, 1, 1) __launch_bounds__(256, 1) k_wo(const __grid_constant__ CUtensorMap mW, const bf16* __restrict__ x) {
  extern __shared__ __align__(1024) uint8_t smem[];
  const uint32_t sA = smem_u32(smem), sB = sA + 131072, bars = sB + 65536;
  const int tid = threadIdx.x, warp = tid >> 5, lane = tid & 31, g = lane >> 2, t = lane & 3;
  const int rb = blockIdx.x >> 3, ct = blockIdx.x & 7;
  TS(3, 0);
  pdl_launch();
  if (tid == 0) {
    for (int i = 0; i < 8; i++) mbar_init(bars + 8 * i, 1);
    fence_init();
    for (int i = 0; i < 8; i++) { mbar_expect(bars + 8 * i, 24576); tma2d(sB + i * 8192, &mW, ct * 64, i * 64, bars + 8 * i); }
  }
  __syncwarp();
  cluster_arrive();
  const int lrow = warp * 16 + g;
  uint32_t xr[16];
  const uint32_t* xp = (const uint32_t*)(x + (rb * 128 + lrow) * 512 + ct * 64) + t;
#pragma unroll
  for (int j = 0; j < 8; j++) { xr[2 * j] = __ldg(xp + j * 4); xr[2 * j + 1] = __ldg(xp + j * 4 + 8 * 256); }
  cluster_wait();
  pdl_wait();
  if (tid == 0) {
    for (int i = ct & 1; i < 8; i += 2) bulk_load_mc(sA + i * 16384, g_o + (rb * 64 + i * 8) * 1024, 16384, bars + 8 * i);
  }
  TS(3, 1);
  float2 ga[8];
#pragma unroll
  for (int j = 0; j < 8; j++) ga[j] = *(const float2*)(g_mod + 1024 + ct * 64 + j * 8 + t * 2);
  float acc[32];
  const uint64_t da = mk_desc(sA + (warp >> 2) * 1024, 2048, 128, 0), db = mk_desc(sB, 8192, 1024, 1);
#pragma unroll
  for (int c = 0; c < 8; c++) {
    mbar_wait(bars + 8 * c, 0);
    if (c == 0) TS(3, 2);
    wg_fence();
#pragma unroll
    for (int k = 0; k < 4; k++) wgmma_ss_n64_t1(acc, da + (c * 4 + k) * 256, db + (c * 4 + k) * 128, c + k);
    wg_commit();
  }
  wg_wait<0>();
  reg_fence(acc);
  TS(3, 3);
  uint32_t* o = (uint32_t*)g_x1 + ((rb * 64 + ct * 8) * 128 + lrow) * 4 + t;
  float s0 = 0, s1 = 0;
#pragma unroll
  for (int j = 0; j < 8; j++) {
    xr[2 * j] = pack_rn(fmaf(ga[j].x, acc[4 * j], blo(xr[2 * j])), fmaf(ga[j].y, acc[4 * j + 1], bhi(xr[2 * j])));
    xr[2 * j + 1] = pack_rn(fmaf(ga[j].x, acc[4 * j + 2], blo(xr[2 * j + 1])), fmaf(ga[j].y, acc[4 * j + 3], bhi(xr[2 * j + 1])));
    o[j * 512] = xr[2 * j]; o[j * 512 + 32] = xr[2 * j + 1];
    s0 += blo(xr[2 * j]) + bhi(xr[2 * j]); s1 += blo(xr[2 * j + 1]) + bhi(xr[2 * j + 1]);
  }
  const float m0 = qsum(s0) * (1.f / 64), m1 = qsum(s1) * (1.f / 64);
  float v0 = 0, v1 = 0;
#pragma unroll
  for (int j = 0; j < 8; j++) {
    float d;
    d = blo(xr[2 * j]) - m0; v0 += d * d; d = bhi(xr[2 * j]) - m0; v0 += d * d;
    d = blo(xr[2 * j + 1]) - m1; v1 += d * d; d = bhi(xr[2 * j + 1]) - m1; v1 += d * d;
  }
  v0 = qsum(v0); v1 = qsum(v1);
  if (t == 0) g_st[(rb * 128 + lrow) * 8 + ct] = make_float2(m0, v0);
  if (t == 1) g_st[(rb * 128 + lrow + 8) * 8 + ct] = make_float2(m1, v1);
  TS(3, 4);
}

constexpr int W2_SMEM = 6 * 32768 + 32768 + 256;
__global__ void __cluster_dims__(2, 1, 1) __launch_bounds__(288, 1) k_w2(const __grid_constant__ CUtensorMap mW, bf16* __restrict__ out) {
  extern __shared__ __align__(1024) uint8_t smem[];
  const uint32_t sR = smem_u32(smem), sX = sR + 6 * 32768, bF = sX + 32768, bE = bF + 48, bX = bF + 96;
  const int tid = threadIdx.x, warp = tid >> 5, lane = tid & 31, g = lane >> 2, t = lane & 3;
  const int kh = blockIdx.x & 1, ct = (blockIdx.x >> 1) & 3, rb = blockIdx.x >> 3;
  TS(5, 0);
  pdl_launch();
  if (tid == 256) {
    for (int i = 0; i < 6; i++) { mbar_init(bF + 8 * i, 1); mbar_init(bE + 8 * i, 8); }
    for (int i = 0; i < 8; i++) { mbar_init(bX + 8 * i, 1); mbar_expect(bX + 8 * i, 4096); }
    fence_init();
  }
  __syncthreads();
  asm volatile("barrier.cluster.arrive.relaxed.aligned;" ::: "memory");
  if (warp == 8) {
    if (lane == 0) {
      auto abytes = [&](int s) { return (kh == 1 && s == 10) ? 8192 : 16384; };
      auto loadB = [&](int s) {
        const int st = s % 6;
        mbar_expect(bF + 8 * st, 16384 + abytes(s));
        for (int j = 0; j < 2; j++) tma2d(sR + st * 32768 + 16384 + j * 8192, &mW, ct * 128 + j * 64, kh * 704 + s * 64, bF + 8 * st);
      };
      auto loadA = [&](int s) { bulk_load(sR + (s % 6) * 32768, g_h + (rb * 172 + kh * 88 + s * 8) * 1024, abytes(s), bF + 8 * (s % 6)); };
      for (int s = 0; s < 6; s++) loadB(s);
      pdl_wait();
      for (int s = 0; s < 6; s++) loadA(s);
      for (int s = 6; s < 11; s++) { mbar_wait(bE + 8 * (s - 6), 0); loadB(s); loadA(s); }
    }
    __syncwarp();
    cluster_wait();
    return;
  }
  pdl_wait();
  TS(5, 1);
  const int lrow = warp * 16 + g;
  uint32_t xr[16];
  float2 gb[8];
  const uint32_t* xp = (const uint32_t*)g_x1 + ((rb * 64 + ct * 16 + kh * 8) * 128 + lrow) * 4 + t;
#pragma unroll
  for (int j = 0; j < 8; j++) {
    xr[2 * j] = xp[j * 512]; xr[2 * j + 1] = xp[j * 512 + 32];
    gb[j] = *(const float2*)(g_mod + 2560 + ct * 128 + kh * 64 + j * 8 + t * 2);
  }
  float acc[64];
#pragma unroll 1
  for (int s = 0; s < 11; s++) {
    const int st = s % 6;
    mbar_wait(bF + 8 * st, s >= 6);
    const uint64_t da = mk_desc(sR + st * 32768 + (warp >> 2) * 1024, 2048, 128, 0), db = mk_desc(sR + st * 32768 + 16384, 8192, 1024, 1);
    if (s == 0) TS(5, 2);
    wg_fence();
    wgmma_ss_n128_t1(acc, da, db, s);
    wgmma_ss_n128_t1(acc, da + 256, db + 128, 1);
    wgmma_ss_n128_t1(acc, da + 512, db + 256, 1);
    wgmma_ss_n128_t1(acc, da + 768, db + 384, 1);
    wg_commit();
    wg_wait<1>();
    if (s > 0 && s < 6 && lane == 0) mbar_arrive(bE + 8 * (s - 1));
  }
  wg_wait<0>();
  reg_fence(acc);
  TS(5, 3);
  asm volatile("barrier.cluster.wait.aligned;" ::: "memory");
  uint32_t rem, rbar;
  asm("mapa.shared::cluster.u32 %0,%1,%2;" : "=r"(rbar) : "r"(bX + warp * 8), "r"(kh ^ 1));
  asm("mapa.shared::cluster.u32 %0,%1,%2;" : "=r"(rem) : "r"(sX + warp * 4096 + lane * 16), "r"(kh ^ 1));
#pragma unroll
  for (int j = 0; j < 8; j++) {
    float v[4];
#pragma unroll
    for (int i = 0; i < 4; i++) { v[i] = kh ? acc[4 * j + i] : acc[32 + 4 * j + i]; acc[4 * j + i] = kh ? acc[32 + 4 * j + i] : acc[4 * j + i]; }
    asm volatile("st.async.weak.shared::cluster.mbarrier::complete_tx::bytes.v4.f32 [%0],{%1,%2,%3,%4},[%5];" ::"r"(rem + j * 512), "f"(v[0]), "f"(v[1]), "f"(v[2]), "f"(v[3]), "r"(rbar) : "memory");
  }
  mbar_wait(bX + warp * 8, 0);
  TS(5, 5);
  const uint32_t sw = sX + warp * 4096;
#pragma unroll
  for (int j = 0; j < 8; j++) {
    const float4 p = *(const float4*)(smem + 6 * 32768 + warp * 4096 + j * 512 + lane * 16);
    xr[2 * j] = pack_rn(fmaf(gb[j].x, acc[4 * j] + p.x, blo(xr[2 * j])), fmaf(gb[j].y, acc[4 * j + 1] + p.y, bhi(xr[2 * j])));
    xr[2 * j + 1] = pack_rn(fmaf(gb[j].x, acc[4 * j + 2] + p.z, blo(xr[2 * j + 1])), fmaf(gb[j].y, acc[4 * j + 3] + p.w, bhi(xr[2 * j + 1])));
  }
  __syncwarp();
#pragma unroll
  for (int j = 1; j < 8; j += 2) {
    asm volatile("stmatrix.sync.aligned.m8n8.x4.shared.b16 [%0],{%1,%2,%3,%4};" ::"r"(sw + (lane & 15) * 128 + (((j - 1 + (lane >> 4)) ^ (lane & 7)) << 4)),
                            "r"(xr[2 * j - 2]), "r"(xr[2 * j - 1]), "r"(xr[2 * j]), "r"(xr[2 * j + 1]) : "memory");
  }
  __syncwarp();
#pragma unroll
  for (int i = 0; i < 4; i++) {
    const int r = i * 4 + (lane >> 3);
    *(uint4*)(out + (rb * 128 + warp * 16 + r) * 512 + ct * 128 + kh * 64 + (lane & 7) * 8) = *(const uint4*)(smem + 6 * 32768 + warp * 4096 + r * 128 + (((lane ^ r) & 7) << 4));
  }
  TS(5, 4);
}

typedef CUresult (*EncFn)(CUtensorMap*, CUtensorMapDataType, cuuint32_t, void*, const cuuint64_t*, const cuuint64_t*, const cuuint32_t*,
                          const cuuint32_t*, CUtensorMapInterleave, CUtensorMapSwizzle, CUtensorMapL2promotion, CUtensorMapFloatOOBfill);
static void mk_map(EncFn f, CUtensorMap* m, const void* p, int rows, int cols, int box_rows) {
  cuuint64_t dim[2] = {(cuuint64_t)cols, (cuuint64_t)rows}, str[1] = {(cuuint64_t)cols * 2};
  cuuint32_t box[2] = {64, (cuuint32_t)box_rows}, es[2] = {1, 1};
  f(m, CU_TENSOR_MAP_DATA_TYPE_BFLOAT16, 2, (void*)p, dim, str, box, es, CU_TENSOR_MAP_INTERLEAVE_NONE, CU_TENSOR_MAP_SWIZZLE_128B,
    CU_TENSOR_MAP_L2_PROMOTION_L2_128B, CU_TENSOR_MAP_FLOAT_OOB_FILL_NONE);
}
template <typename... KA, typename... A>
static void launch(void (*k)(KA...), int grid, int block, int smem, bool pdl, A... args) {
  cudaLaunchConfig_t cfg = {};
  cfg.gridDim = dim3(grid); cfg.blockDim = dim3(block); cfg.dynamicSmemBytes = smem; cfg.stream = cudaStreamPerThread;
  cudaLaunchAttribute at[1];
  at[0].id = cudaLaunchAttributeProgrammaticStreamSerialization; at[0].val.programmaticStreamSerializationAllowed = 1;
  cfg.attrs = at; cfg.numAttrs = pdl ? 1 : 0;
  cudaLaunchKernelEx(&cfg, k, args...);
}
extern "C" void kernel_launch(void* const* d_in, const int* in_sizes, int n_in, void* d_out, int out_size) {
  const bf16 *x = (const bf16*)d_in[0], *wqkv = (const bf16*)d_in[1], *wo = (const bf16*)d_in[2], *w1 = (const bf16*)d_in[4],
             *w3 = (const bf16*)d_in[5], *w2 = (const bf16*)d_in[6], *c = (const bf16*)d_in[7], *wmod = (const bf16*)d_in[8];
  void* fp = nullptr;
  cudaDriverEntryPointQueryResult qr;
  cudaGetDriverEntryPoint("cuTensorMapEncodeTiled", &fp, cudaEnableDefault, &qr);
  EncFn f = (EncFn)fp;
  CUtensorMap mX, mQ, mO, m1, m3, m2;
  mk_map(f, &mX, x, S_, D_, 128); mk_map(f, &mQ, wqkv, D_, 3 * D_, 64); mk_map(f, &mO, wo, D_, D_, 64);
  mk_map(f, &m1, w1, D_, F_, 32); mk_map(f, &m3, w3, D_, F_, 32); mk_map(f, &m2, w2, F_, D_, 64);
  cudaFuncSetAttribute(k_lngemm<false>, cudaFuncAttributeMaxDynamicSharedMemorySize, LN_SMEM);
  cudaFuncSetAttribute(k_lngemm<true>, cudaFuncAttributeMaxDynamicSharedMemorySize, LN_SMEM);
  cudaFuncSetAttribute(k_attn, cudaFuncAttributeMaxDynamicSharedMemorySize, AT_SMEM);
  cudaFuncSetAttribute(k_wo, cudaFuncAttributeMaxDynamicSharedMemorySize, WO_SMEM);
  cudaFuncSetAttribute(k_w2, cudaFuncAttributeMaxDynamicSharedMemorySize, W2_SMEM);
  launch(k_lngemm<false>, 128, 384, LN_SMEM, false, mX, mQ, mQ, c, wmod, x);
  launch(k_attn, 132, 512, AT_SMEM, true, wo, w1, w3, w2, c, wmod, 0u);
  launch(k_wo, 128, 256, WO_SMEM, true, mO, x);
  launch(k_lngemm<true>, 128, 384, LN_SMEM, true, mX, m1, m3, c, wmod, x);
  launch(k_w2, 128, 288, W2_SMEM, true, m2, (bf16*)d_out);
}
```

```cpp
#include <cuda_runtime.h>
#include <cuda_bf16.h>
#include <cuda.h>
#include <stdint.h>
typedef __nv_bfloat16 bf16;
constexpr int S_ = 2048, D_ = 512, F_ = 1376;
__device__ __align__(1024) float g_mod[3072];
__device__ __align__(1024) uint32_t g_modv[4096 + 4096];
__device__ __align__(1024) bf16 g_qkv[192 * 2048 * 8];
__device__ __align__(1024) float g_kmax[32 * 128];
__device__ __align__(1024) bf16 g_o[16 * 64 * 128 * 8];
__device__ __align__(1024) bf16 g_x1[16 * 64 * 128 * 8];
__device__ __align__(1024) float2 g_st[2048 * 8];
__device__ __align__(1024) bf16 g_h[16 * 172 * 128 * 8];

__device__ __forceinline__ uint32_t smem_u32(const void* p) { return (uint32_t)__cvta_generic_to_shared(p); }
__device__ __forceinline__ void mbar_init(uint32_t b, int n) { asm volatile("mbarrier.init.shared::cta.b64 [%0],%1;" ::"r"(b), "r"(n) : "memory"); }
__device__ __forceinline__ void mbar_expect(uint32_t b, int bytes) { asm volatile("mbarrier.arrive.expect_tx.shared::cta.b64 _,[%0],%1;" ::"r"(b), "r"(bytes) : "memory"); }
__device__ __forceinline__ void mbar_arrive(uint32_t b) { asm volatile("mbarrier.arrive.shared::cta.b64 _,[%0];" ::"r"(b) : "memory"); }
__device__ __forceinline__ void mbar_wait(uint32_t b, int parity) {
  asm volatile("{\n.reg .pred p;\n.reg .u32 n;\nmov.u32 n,0;\nLW:\nmbarrier.try_wait.parity.shared::cta.b64 p,[%0],%1;\n@p bra LD;\n"
               "add.u32 n,n,1;\nsetp.lt.u32 p,n,4194304;\n@p bra LW;\nLD:\n}\n" ::"r"(b), "r"(parity) : "memory");
}
__device__ __forceinline__ void fence_init() { asm volatile("fence.mbarrier_init.release.cluster;" ::: "memory"); }
__device__ __forceinline__ void fence_async() { asm volatile("fence.proxy.async.shared::cta;" ::: "memory"); }
__device__ __forceinline__ void bulk_load(uint32_t dst, const void* src, int bytes, uint32_t bar) {
  asm volatile("cp.async.bulk.shared::cluster.global.mbarrier::complete_tx::bytes [%0],[%1],%2,[%3];" ::"r"(dst), "l"(src), "r"(bytes), "r"(bar) : "memory");
}
__device__ __forceinline__ void tma2d(uint32_t dst, const CUtensorMap* m, int c0, int c1, uint32_t bar) {
  asm volatile("cp.async.bulk.tensor.2d.shared::cluster.global.mbarrier::complete_tx::bytes [%0],[%1,{%3,%4}],[%2];" ::"r"(dst), "l"(m), "r"(bar), "r"(c0), "r"(c1) : "memory");
}
__device__ __forceinline__ void bulk_load_mc(uint32_t dst, const void* src, int bytes, uint32_t bar) {
  asm volatile("cp.async.bulk.shared::cluster.global.mbarrier::complete_tx::bytes.multicast::cluster [%0],[%1],%2,[%3],%4;" ::"r"(dst), "l"(src), "r"(bytes), "r"(bar), "h"((uint16_t)3) : "memory");
}
__device__ __forceinline__ void tma2d_mc(uint32_t dst, const CUtensorMap* m, int c0, int c1, uint32_t bar) {
  asm volatile("cp.async.bulk.tensor.2d.shared::cluster.global.mbarrier::complete_tx::bytes.multicast::cluster [%0],[%1,{%3,%4}],[%2],%5;" ::"r"(dst), "l"(m), "r"(bar), "r"(c0), "r"(c1), "h"((uint16_t)3) : "memory");
}
__device__ __forceinline__ void cluster_arrive() { asm volatile("barrier.cluster.arrive.relaxed.aligned;" ::: "memory"); }
__device__ __forceinline__ void cluster_wait() { asm volatile("barrier.cluster.wait.aligned;" ::: "memory"); }
__device__ __forceinline__ void cluster_sync() { asm volatile("barrier.cluster.arrive.release.aligned;\nbarrier.cluster.wait.acquire.aligned;" ::: "memory"); }
__device__ __forceinline__ void l2_prefetch(const void* p, int bytes) { asm volatile("cp.async.bulk.prefetch.L2.global [%0],%1;" ::"l"(p), "r"(bytes) : "memory"); }
__device__ __forceinline__ void pdl_launch() { asm volatile("griddepcontrol.launch_dependents;" ::: "memory"); }
__device__ __forceinline__ void pdl_wait() { asm volatile("griddepcontrol.wait;" ::: "memory"); }
__device__ __forceinline__ void wg_fence() { asm volatile("wgmma.fence.sync.aligned;" ::: "memory"); }
__device__ __forceinline__ void wg_commit() { asm volatile("wgmma.commit_group.sync.aligned;" ::: "memory"); }
template <int N> __device__ __forceinline__ void wg_wait() { asm volatile("wgmma.wait_group.sync.aligned %0;" ::"n"(N) : "memory"); }
template <int N> __device__ __forceinline__ void reg_fence(float (&d)[N]) {
#pragma unroll
  for (int i = 0; i < N; i++) asm volatile("" : "+f"(d[i])::"memory");
}
template <int N> __device__ __forceinline__ void zero(float (&d)[N]) {
#pragma unroll
  for (int i = 0; i < N; i++) d[i] = 0.f;
  reg_fence(d);
}
__device__ __forceinline__ uint64_t mk_desc(uint32_t addr, uint32_t lbo, uint32_t sbo, uint32_t mode) {
  return (uint64_t)((addr >> 4) & 0x3FFF) | ((uint64_t)(lbo >> 4) << 16) | ((uint64_t)(sbo >> 4) << 32) | ((uint64_t)mode << 62);
}
__device__ __forceinline__ void ldsm4(uint32_t a, uint32_t (&r)[4]) {
  asm volatile("ldmatrix.sync.aligned.m8n8.x4.shared.b16 {%0,%1,%2,%3},[%4];" : "=r"(r[0]), "=r"(r[1]), "=r"(r[2]), "=r"(r[3]) : "r"(a) : "memory");
}
__device__ __forceinline__ uint32_t pack_rn(float lo, float hi) { uint32_t r; asm("cvt.rn.bf16x2.f32 %0,%1,%2;" : "=r"(r) : "f"(hi), "f"(lo)); return r; }
__device__ __forceinline__ uint32_t pack_rz(float lo, float hi) { uint32_t r; asm("cvt.rz.bf16x2.f32 %0,%1,%2;" : "=r"(r) : "f"(hi), "f"(lo)); return r; }
__device__ __forceinline__ float blo(uint32_t u) { return __uint_as_float(u << 16); }
__device__ __forceinline__ float bhi(uint32_t u) { return __uint_as_float(u & 0xFFFF0000u); }
__device__ __forceinline__ float rbf(float x) { return __bfloat162float(__float2bfloat16_rn(x)); }
__device__ __forceinline__ float qsum(float v) { v += __shfl_xor_sync(~0u, v, 1); return v + __shfl_xor_sync(~0u, v, 2); }
__device__ __forceinline__ float ex2(float x) { float r; asm("ex2.approx.ftz.f32 %0,%1;" : "=f"(r) : "f"(x)); return r; }
#define TS(k, i)
__device__ __forceinline__ void wgmma_rs_n176_t1(float (&d)[88],uint32_t a0,uint32_t a1,uint32_t a2,uint32_t a3,uint64_t db,int sc){
  asm volatile("{\n.reg .pred p;\nsetp.ne.b32 p,%93,0;\n"
    "wgmma.mma_async.sync.aligned.m64n176k16.f32.bf16.bf16 {%0,%1,%2,%3,%4,%5,%6,%7,%8,%9,%10,%11,%12,%13,%14,%15,%16,%17,%18,%19,%20,%21,%22,%23,%24,%25,%26,%27,%28,%29,%30,%31,%32,%33,%34,%35,%36,%37,%38,%39,%40,%41,%42,%43,%44,%45,%46,%47,%48,%49,%50,%51,%52,%53,%54,%55,%56,%57,%58,%59,%60,%61,%62,%63,%64,%65,%66,%67,%68,%69,%70,%71,%72,%73,%74,%75,%76,%77,%78,%79,%80,%81,%82,%83,%84,%85,%86,%87},{%88,%89,%90,%91},%92,p,1,1,1;\n}\n"
    :"+f"(d[0]),"+f"(d[1]),"+f"(d[2]),"+f"(d[3]),"+f"(d[4]),"+f"(d[5]),"+f"(d[6]),"+f"(d[7]),"+f"(d[8]),"+f"(d[9]),"+f"(d[10]),"+f"(d[11]),"+f"(d[12]),"+f"(d[13]),"+f"(d[14]),"+f"(d[15]),"+f"(d[16]),"+f"(d[17]),"+f"(d[18]),"+f"(d[19]),"+f"(d[20]),"+f"(d[21]),"+f"(d[22]),"+f"(d[23]),"+f"(d[24]),"+f"(d[25]),"+f"(d[26]),"+f"(d[27]),"+f"(d[28]),"+f"(d[29]),"+f"(d[30]),"+f"(d[31]),"+f"(d[32]),"+f"(d[33]),"+f"(d[34]),"+f"(d[35]),"+f"(d[36]),"+f"(d[37]),"+f"(d[38]),"+f"(d[39]),"+f"(d[40]),"+f"(d[41]),"+f"(d[42]),"+f"(d[43]),"+f"(d[44]),"+f"(d[45]),"+f"(d[46]),"+f"(d[47]),"+f"(d[48]),"+f"(d[49]),"+f"(d[50]),"+f"(d[51]),"+f"(d[52]),"+f"(d[53]),"+f"(d[54]),"+f"(d[55]),"+f"(d[56]),"+f"(d[57]),"+f"(d[58]),"+f"(d[59]),"+f"(d[60]),"+f"(d[61]),"+f"(d[62]),"+f"(d[63]),"+f"(d[64]),"+f"(d[65]),"+f"(d[66]),"+f"(d[67]),"+f"(d[68]),"+f"(d[69]),"+f"(d[70]),"+f"(d[71]),"+f"(d[72]),"+f"(d[73]),"+f"(d[74]),"+f"(d[75]),"+f"(d[76]),"+f"(d[77]),"+f"(d[78]),"+f"(d[79]),"+f"(d[80]),"+f"(d[81]),"+f"(d[82]),"+f"(d[83]),"+f"(d[84]),"+f"(d[85]),"+f"(d[86]),"+f"(d[87])
    :"r"(a0),"r"(a1),"r"(a2),"r"(a3),"l"(db),"r"(sc));
}
__device__ __forceinline__ void wgmma_rs_n192_t1(float (&d)[96],uint32_t a0,uint32_t a1,uint32_t a2,uint32_t a3,uint64_t db,int sc){
  asm volatile("{\n.reg .pred p;\nsetp.ne.b32 p,%101,0;\n"
    "wgmma.mma_async.sync.aligned.m64n192k16.f32.bf16.bf16 {%0,%1,%2,%3,%4,%5,%6,%7,%8,%9,%10,%11,%12,%13,%14,%15,%16,%17,%18,%19,%20,%21,%22,%23,%24,%25,%26,%27,%28,%29,%30,%31,%32,%33,%34,%35,%36,%37,%38,%39,%40,%41,%42,%43,%44,%45,%46,%47,%48,%49,%50,%51,%52,%53,%54,%55,%56,%57,%58,%59,%60,%61,%62,%63,%64,%65,%66,%67,%68,%69,%70,%71,%72,%73,%74,%75,%76,%77,%78,%79,%80,%81,%82,%83,%84,%85,%86,%87,%88,%89,%90,%91,%92,%93,%94,%95},{%96,%97,%98,%99},%100,p,1,1,1;\n}\n"
    :"+f"(d[0]),"+f"(d[1]),"+f"(d[2]),"+f"(d[3]),"+f"(d[4]),"+f"(d[5]),"+f"(d[6]),"+f"(d[7]),"+f"(d[8]),"+f"(d[9]),"+f"(d[10]),"+f"(d[11]),"+f"(d[12]),"+f"(d[13]),"+f"(d[14]),"+f"(d[15]),"+f"(d[16]),"+f"(d[17]),"+f"(d[18]),"+f"(d[19]),"+f"(d[20]),"+f"(d[21]),"+f"(d[22]),"+f"(d[23]),"+f"(d[24]),"+f"(d[25]),"+f"(d[26]),"+f"(d[27]),"+f"(d[28]),"+f"(d[29]),"+f"(d[30]),"+f"(d[31]),"+f"(d[32]),"+f"(d[33]),"+f"(d[34]),"+f"(d[35]),"+f"(d[36]),"+f"(d[37]),"+f"(d[38]),"+f"(d[39]),"+f"(d[40]),"+f"(d[41]),"+f"(d[42]),"+f"(d[43]),"+f"(d[44]),"+f"(d[45]),"+f"(d[46]),"+f"(d[47]),"+f"(d[48]),"+f"(d[49]),"+f"(d[50]),"+f"(d[51]),"+f"(d[52]),"+f"(d[53]),"+f"(d[54]),"+f"(d[55]),"+f"(d[56]),"+f"(d[57]),"+f"(d[58]),"+f"(d[59]),"+f"(d[60]),"+f"(d[61]),"+f"(d[62]),"+f"(d[63]),"+f"(d[64]),"+f"(d[65]),"+f"(d[66]),"+f"(d[67]),"+f"(d[68]),"+f"(d[69]),"+f"(d[70]),"+f"(d[71]),"+f"(d[72]),"+f"(d[73]),"+f"(d[74]),"+f"(d[75]),"+f"(d[76]),"+f"(d[77]),"+f"(d[78]),"+f"(d[79]),"+f"(d[80]),"+f"(d[81]),"+f"(d[82]),"+f"(d[83]),"+f"(d[84]),"+f"(d[85]),"+f"(d[86]),"+f"(d[87]),"+f"(d[88]),"+f"(d[89]),"+f"(d[90]),"+f"(d[91]),"+f"(d[92]),"+f"(d[93]),"+f"(d[94]),"+f"(d[95])
    :"r"(a0),"r"(a1),"r"(a2),"r"(a3),"l"(db),"r"(sc));
}
__device__ __forceinline__ void wgmma_rs_n24_t1(float (&d)[12],uint32_t a0,uint32_t a1,uint32_t a2,uint32_t a3,uint64_t db,int sc){
  asm volatile("{\n.reg .pred p;\nsetp.ne.b32 p,%17,0;\n"
    "wgmma.mma_async.sync.aligned.m64n24k16.f32.bf16.bf16 {%0,%1,%2,%3,%4,%5,%6,%7,%8,%9,%10,%11},{%12,%13,%14,%15},%16,p,1,1,1;\n}\n"
    :"+f"(d[0]),"+f"(d[1]),"+f"(d[2]),"+f"(d[3]),"+f"(d[4]),"+f"(d[5]),"+f"(d[6]),"+f"(d[7]),"+f"(d[8]),"+f"(d[9]),"+f"(d[10]),"+f"(d[11])
    :"r"(a0),"r"(a1),"r"(a2),"r"(a3),"l"(db),"r"(sc));
}
__device__ __forceinline__ void wgmma_rs_n64_t0(float (&d)[32],uint32_t a0,uint32_t a1,uint32_t a2,uint32_t a3,uint64_t db,int sc){
  asm volatile("{\n.reg .pred p;\nsetp.ne.b32 p,%37,0;\n"
    "wgmma.mma_async.sync.aligned.m64n64k16.f32.bf16.bf16 {%0,%1,%2,%3,%4,%5,%6,%7,%8,%9,%10,%11,%12,%13,%14,%15,%16,%17,%18,%19,%20,%21,%22,%23,%24,%25,%26,%27,%28,%29,%30,%31},{%32,%33,%34,%35},%36,p,1,1,0;\n}\n"
    :"+f"(d[0]),"+f"(d[1]),"+f"(d[2]),"+f"(d[3]),"+f"(d[4]),"+f"(d[5]),"+f"(d[6]),"+f"(d[7]),"+f"(d[8]),"+f"(d[9]),"+f"(d[10]),"+f"(d[11]),"+f"(d[12]),"+f"(d[13]),"+f"(d[14]),"+f"(d[15]),"+f"(d[16]),"+f"(d[17]),"+f"(d[18]),"+f"(d[19]),"+f"(d[20]),"+f"(d[21]),"+f"(d[22]),"+f"(d[23]),"+f"(d[24]),"+f"(d[25]),"+f"(d[26]),"+f"(d[27]),"+f"(d[28]),"+f"(d[29]),"+f"(d[30]),"+f"(d[31])
    :"r"(a0),"r"(a1),"r"(a2),"r"(a3),"l"(db),"r"(sc));
}
__device__ __forceinline__ void wgmma_ss_n128_t1(float (&d)[64],uint64_t da,uint64_t db,int sc){
  asm volatile("{\n.reg .pred p;\nsetp.ne.b32 p,%66,0;\n"
    "wgmma.mma_async.sync.aligned.m64n128k16.f32.bf16.bf16 {%0,%1,%2,%3,%4,%5,%6,%7,%8,%9,%10,%11,%12,%13,%14,%15,%16,%17,%18,%19,%20,%21,%22,%23,%24,%25,%26,%27,%28,%29,%30,%31,%32,%33,%34,%35,%36,%37,%38,%39,%40,%41,%42,%43,%44,%45,%46,%47,%48,%49,%50,%51,%52,%53,%54,%55,%56,%57,%58,%59,%60,%61,%62,%63},%64,%65,p,1,1,0,1;\n}\n"
    :"+f"(d[0]),"+f"(d[1]),"+f"(d[2]),"+f"(d[3]),"+f"(d[4]),"+f"(d[5]),"+f"(d[6]),"+f"(d[7]),"+f"(d[8]),"+f"(d[9]),"+f"(d[10]),"+f"(d[11]),"+f"(d[12]),"+f"(d[13]),"+f"(d[14]),"+f"(d[15]),"+f"(d[16]),"+f"(d[17]),"+f"(d[18]),"+f"(d[19]),"+f"(d[20]),"+f"(d[21]),"+f"(d[22]),"+f"(d[23]),"+f"(d[24]),"+f"(d[25]),"+f"(d[26]),"+f"(d[27]),"+f"(d[28]),"+f"(d[29]),"+f"(d[30]),"+f"(d[31]),"+f"(d[32]),"+f"(d[33]),"+f"(d[34]),"+f"(d[35]),"+f"(d[36]),"+f"(d[37]),"+f"(d[38]),"+f"(d[39]),"+f"(d[40]),"+f"(d[41]),"+f"(d[42]),"+f"(d[43]),"+f"(d[44]),"+f"(d[45]),"+f"(d[46]),"+f"(d[47]),"+f"(d[48]),"+f"(d[49]),"+f"(d[50]),"+f"(d[51]),"+f"(d[52]),"+f"(d[53]),"+f"(d[54]),"+f"(d[55]),"+f"(d[56]),"+f"(d[57]),"+f"(d[58]),"+f"(d[59]),"+f"(d[60]),"+f"(d[61]),"+f"(d[62]),"+f"(d[63])
    :"l"(da),"l"(db),"r"(sc));
}
__device__ __forceinline__ void wgmma_ss_n64_t1(float (&d)[32],uint64_t da,uint64_t db,int sc){
  asm volatile("{\n.reg .pred p;\nsetp.ne.b32 p,%34,0;\n"
    "wgmma.mma_async.sync.aligned.m64n64k16.f32.bf16.bf16 {%0,%1,%2,%3,%4,%5,%6,%7,%8,%9,%10,%11,%12,%13,%14,%15,%16,%17,%18,%19,%20,%21,%22,%23,%24,%25,%26,%27,%28,%29,%30,%31},%32,%33,p,1,1,0,1;\n}\n"
    :"+f"(d[0]),"+f"(d[1]),"+f"(d[2]),"+f"(d[3]),"+f"(d[4]),"+f"(d[5]),"+f"(d[6]),"+f"(d[7]),"+f"(d[8]),"+f"(d[9]),"+f"(d[10]),"+f"(d[11]),"+f"(d[12]),"+f"(d[13]),"+f"(d[14]),"+f"(d[15]),"+f"(d[16]),"+f"(d[17]),"+f"(d[18]),"+f"(d[19]),"+f"(d[20]),"+f"(d[21]),"+f"(d[22]),"+f"(d[23]),"+f"(d[24]),"+f"(d[25]),"+f"(d[26]),"+f"(d[27]),"+f"(d[28]),"+f"(d[29]),"+f"(d[30]),"+f"(d[31])
    :"l"(da),"l"(db),"r"(sc));
}

__device__ __forceinline__ float silu_bf(bf16 c) { const float x = __bfloat162float(c); return rbf(x / (1.f + __expf(-x))); }
__device__ __forceinline__ void fma8(float (&a)[8], float s, const uint4& v) {
  a[0] += s * blo(v.x); a[1] += s * bhi(v.x); a[2] += s * blo(v.y); a[3] += s * bhi(v.y);
  a[4] += s * blo(v.z); a[5] += s * bhi(v.z); a[6] += s * blo(v.w); a[7] += s * bhi(v.w);
}
__device__ __forceinline__ float red8(float (&a)[8], int lane) {
#pragma unroll
  for (int w = 4; w >= 1; w >>= 1) {
    const bool up = lane & (w * 4);
#pragma unroll
    for (int j = 0; j < w; j++) a[j] = (up ? a[j + w] : a[j]) + __shfl_xor_sync(~0u, up ? a[j] : a[j + w], w * 4);
  }
  return a[0];
}
__device__ __forceinline__ float mod_fin(float s, int n) { s = rbf(s); return ((n >> 9) == 1 || (n >> 9) == 4) ? rbf(1.f + s) : s; }
__device__ __forceinline__ void poll(uint2& a, uint2& b, float (&w)[16], const uint32_t* p, const uint32_t* q) {
  asm volatile("{\n.reg .pred p;\n.reg .b32 n,t,u;\nmov.u32 n,0;\nLW:\nld.relaxed.gpu.global.v2.u32 {%0,%1},[%20];\nld.relaxed.gpu.global.v2.u32 {%2,%3},[%20+64];\n"
               "ld.relaxed.gpu.global.v4.f32 {%4,%5,%6,%7},[%21];\nld.relaxed.gpu.global.v4.f32 {%8,%9,%10,%11},[%21+16];\n"
               "ld.relaxed.gpu.global.v4.f32 {%12,%13,%14,%15},[%21+8192];\nld.relaxed.gpu.global.v4.f32 {%16,%17,%18,%19},[%21+8208];\n"
               "lop3.b32 t,%0,%1,%2,0x80;\nlop3.b32 u,%3,%4,%5,0x80;\nlop3.b32 t,t,%6,%7,0x80;\nlop3.b32 u,u,%8,%9,0x80;\nlop3.b32 t,t,%10,%11,0x80;\n"
               "lop3.b32 u,u,%12,%13,0x80;\nlop3.b32 t,t,%14,%15,0x80;\nlop3.b32 u,u,%16,%17,0x80;\nlop3.b32 t,t,%18,%19,0x80;\nlop3.b32 t,t,u,1,0x80;\n"
               "setp.ne.u32 p,t,0;\n@p bra LD;\nadd.u32 n,n,1;\nsetp.lt.u32 p,n,1048576;\n@p bra LW;\nLD:\n}\n"
               : "=&r"(a.x), "=&r"(a.y), "=&r"(b.x), "=&r"(b.y), "=&f"(w[0]), "=&f"(w[1]), "=&f"(w[2]), "=&f"(w[3]), "=&f"(w[4]), "=&f"(w[5]), "=&f"(w[6]), "=&f"(w[7]),
                 "=&f"(w[8]), "=&f"(w[9]), "=&f"(w[10]), "=&f"(w[11]), "=&f"(w[12]), "=&f"(w[13]), "=&f"(w[14]), "=&f"(w[15]) : "l"(p), "l"(q) : "memory");
}

constexpr int LN_SMEM = 131072 + 4 * 24576 + 2048 + 256;
template <bool FFN>
__global__ void __cluster_dims__(2, 1, 1) __launch_bounds__(384, 1) k_lngemm(const __grid_constant__ CUtensorMap mX, const __grid_constant__ CUtensorMap mB0,
                                                   const __grid_constant__ CUtensorMap mB1, const bf16* __restrict__ cv, const bf16* __restrict__ wm, const bf16* __restrict__ xg, const bf16* wq) {
  extern __shared__ __align__(1024) uint8_t smem[];
  const uint32_t sA = smem_u32(smem), sB = sA + (FFN ? 81920 : 131072), sM = sA + 229376, bars = sM + 2048;
  const uint32_t bA = bars, bF = bars + 64, bE = bars + 112;
  constexpr int NB = FFN ? 6 : 4;
  const int tid = threadIdx.x, warp = tid >> 5, lane = tid & 31;
  const int pr = blockIdx.x & 1, rb = FFN ? (blockIdx.x >> 4) * 2 + pr : blockIdx.x >> 3, ct = FFN ? (blockIdx.x >> 1) & 7 : blockIdx.x & 7;
  constexpr int NST = FFN ? 16 : 8, KS = FFN ? 2 : 4, BOX = FFN ? 4096 : 8192;
  TS(FFN ? 4 : 1, 0);
  pdl_launch();
  float* red = (float*)(smem + (sM - sA));
  if (tid == 256) {
    for (int i = 0; i < 8; i++) mbar_init(bA + 8 * i, 1);
    for (int i = 0; i < NB; i++) { mbar_init(bF + 8 * i, 1); mbar_init(bE + 8 * i, FFN ? 16 : 8); }
    mbar_init(bars + 160, 1);
    fence_init();
  }
  __syncwarp();
  cluster_arrive();
  uint4 wv0, wv1, xv[4];
  bf16 cv0, cv1;
  if (!FFN && tid < 256) {
    const int r = (blockIdx.x & 3) * 128 + (tid >> 2);
    const uint4* wp = (const uint4*)(wm + r * 3072 + (blockIdx.x >> 2) * 32 + (tid & 3) * 8);
    wv0 = __ldg(wp); wv1 = __ldg(wp + 64 * 384);
    cv0 = cv[r]; cv1 = cv[r + 64];
#pragma unroll
    for (int i = 0; i < 4; i++) xv[i] = __ldg((const uint4*)(xg + (blockIdx.x * 16 + (tid >> 4)) * 512 + i * 128 + (tid & 15) * 8));
  }
  cluster_wait();
  if (warp >= 8) {
    asm volatile("setmaxnreg.dec.sync.aligned.u32 40;");
    if (tid == 256) {
      auto loadB = [&](int s) {
        const uint32_t d = sB + (s % NB) * 24576, b = bF + (s % NB) * 8;
        mbar_expect(b, 24576);
        for (int j = 0; j < 3; j++) {
          if (FFN) tma2d_mc(d + (pr * 3 + j) * BOX, pr ? &mB1 : &mB0, ct * 176 + j * 64, s * 32, b);
          else tma2d(d + j * BOX, &mB0, ct * 192 + j * 64, s * 64, b);
        }
      };
      for (int i = 0; i < 8; i++) mbar_expect(bA + 8 * i, 16384);
      for (int s = 0; s < NB; s++) {
        const int i = s * 2 + (ct & 1);
        if (!FFN) tma2d_mc(sA + i * 16384, &mX, i * 64, rb * 128, bA + 8 * i);
        loadB(s);
      }
      if (FFN) {
        pdl_wait();
        for (int i = 0; i < 2; i++) bulk_load(sA + i * 16384, g_x1 + (rb * 64 + i * 8) * 1024, 16384, bA + 8 * i);
      }
      for (int s = NB; s < NST; s++) {
        mbar_wait(bE + (s % NB) * 8, (s / NB - 1) & 1); loadB(s);
        if (FFN && s <= 10 && !(s & 1)) bulk_load(sA + (s / 2 - 3) * 16384, g_x1 + (rb * 64 + (s / 2 + 2) * 8) * 1024, 16384, bA + 8 * (s / 2 + 2));
      }
    }
  } else {
  asm volatile("setmaxnreg.inc.sync.aligned.u32 232;");
  const int g = lane >> 2, t = lane & 3;
  const int lr = warp * 16 + (lane & 7) + ((lane >> 3) & 1) * 8;
  auto aaddr = [&](int ks) -> uint32_t {
    if (FFN) return sA + ((ks < 20 ? ks : ks - 20) * 2 + (lane >> 4)) * 2048 + lr * 16;
    return sA + (ks >> 2) * 16384 + lr * 128 + ((((ks & 3) * 2 + (lane >> 4)) ^ (lr & 7)) << 4);
  };
  const int row0 = rb * 128 + warp * 16 + g;
  float2 msh, msc;
  float rs0, rs1, nm0, nm1;
  if (!FFN) {
    {
      float a[8] = {0, 0, 0, 0, 0, 0, 0, 0};
      fma8(a, silu_bf(cv0), wv0); fma8(a, silu_bf(cv1), wv1);
      red[warp * 32 + t * 8 + g] = red8(a, lane);
      asm volatile("bar.sync 1,256;" ::: "memory");
      if (tid < 32) {
        float r = 0;
#pragma unroll
        for (int i = 0; i < 8; i++) r += red[i * 32 + tid];
        asm volatile("st.relaxed.gpu.global.u32 [%0],%1;" ::"l"(g_modv + ((blockIdx.x >> 2) * 32 + tid) * 4 + (blockIdx.x & 3)), "r"(__float_as_uint(r) | 1u) : "memory");
      }
      TS(0, 1);
    }
    {
      float v[32], s = 0, q = 0;
#pragma unroll
      for (int i = 0; i < 16; i++) { const uint32_t u = ((const uint32_t*)xv)[i]; v[2 * i] = blo(u); v[2 * i + 1] = bhi(u); s += v[2 * i] + v[2 * i + 1]; }
      s = qsum(s); s += __shfl_xor_sync(~0u, s, 4); s += __shfl_xor_sync(~0u, s, 8);
      const float m = s * (1.f / 512);
#pragma unroll
      for (int i = 0; i < 32; i++) q += (v[i] - m) * (v[i] - m);
      q = qsum(q); q += __shfl_xor_sync(~0u, q, 4); q += __shfl_xor_sync(~0u, q, 8);
      const float rs = rsqrtf(q * (1.f / 512) + 1e-5f);
      if ((tid & 15) == 0)
        asm volatile("st.relaxed.gpu.global.v2.u32 [%0],{%1,%2};" ::"l"(g_modv + 4096 + (blockIdx.x * 16 + (tid >> 4)) * 2), "r"(__float_as_uint(rs) | 1u), "r"(__float_as_uint(-m * rs) | 1u) : "memory");
    }
    uint2 p0, p1;
    float w[16];
    poll(p0, p1, w, g_modv + 4096 + row0 * 2, g_modv + tid * 8);
    msh = make_float2(mod_fin(w[0] + w[1] + w[2] + w[3], 0), mod_fin(w[4] + w[5] + w[6] + w[7], 0));
    msc = make_float2(mod_fin(w[8] + w[9] + w[10] + w[11], 512), mod_fin(w[12] + w[13] + w[14] + w[15], 512));
    asm volatile("bar.sync 1,256;" ::: "memory");
    rs0 = __uint_as_float(p0.x); nm0 = __uint_as_float(p0.y); rs1 = __uint_as_float(p1.x); nm1 = __uint_as_float(p1.y);
  } else {
    pdl_wait();
    TS(4, 1);
    msh = *(const float2*)(g_mod + 1536 + tid * 2); msc = *(const float2*)(g_mod + 2048 + tid * 2);
    const float4 p0 = *(const float4*)(g_st + row0 * 8 + t * 2), p1 = *(const float4*)(g_st + (row0 + 8) * 8 + t * 2);
    const float m0 = qsum(p0.x + p0.z) * 0.125f, m1 = qsum(p1.x + p1.z) * 0.125f;
    const float v0 = qsum(p0.y + p0.w + 64.f * ((p0.x - m0) * (p0.x - m0) + (p0.z - m0) * (p0.z - m0)));
    const float v1 = qsum(p1.y + p1.w + 64.f * ((p1.x - m1) * (p1.x - m1) + (p1.z - m1) * (p1.z - m1)));
    rs0 = rsqrtf(v0 * (1.f / 512) + 1e-5f); rs1 = rsqrtf(v1 * (1.f / 512) + 1e-5f);
    nm0 = -m0 * rs0; nm1 = -m1 * rs1;
  }
  {
    uint32_t* m = (uint32_t*)(smem + (sM - sA)) + (tid >> 3) * 16 + (tid & 3) * 4 + ((tid >> 2) & 1);
    m[0] = pack_rn(msc.x, msc.y); m[2] = pack_rn(msh.x, msh.y);
    asm volatile("bar.sync 1,256;" ::: "memory");
  }
  if (FFN && warp >= 2 && warp < 5 && lane == 0) bulk_load(sA + warp * 16384, g_x1 + (rb * 64 + warp * 8) * 1024, 16384, bA + 8 * warp);
  constexpr int NA = FFN ? 88 : 96;
  float acc0[NA], acc1[FFN ? 88 : 1];
  uint32_t a[2][KS][4];
  auto prep = [&](int ks, uint32_t(&o)[4]) {
    if ((ks & 3) == 0) mbar_wait(bA + 2 * ks, 0);
    uint32_t r[4]; ldsm4(aaddr(ks), r);
    const uint4 m = *(const uint4*)(smem + (sM - sA) + ks * 64 + t * 16);
#pragma unroll
    for (int i = 0; i < 4; i++) {
      const float rs = (i & 1) ? rs1 : rs0, nm = (i & 1) ? nm1 : nm0;
      const uint32_t n = pack_rn(fmaf(blo(r[i]), rs, nm), fmaf(bhi(r[i]), rs, nm));
      asm("fma.rn.bf16x2 %0,%1,%2,%3;" : "=r"(o[i]) : "r"(n), "r"(i < 2 ? m.x : m.y), "r"(i < 2 ? m.z : m.w));
    }
  };
  auto stage = [&](int s, uint32_t(&c)[KS][4], uint32_t(&n)[KS][4]) {
    mbar_wait(bF + (s % NB) * 8, (s / NB) & 1);
    const uint64_t db = mk_desc(sB + (s % NB) * 24576, BOX, 1024, 1);
    wg_fence();
#pragma unroll
    for (int k = 0; k < KS; k++) {
      if constexpr (FFN) {
        wgmma_rs_n176_t1(acc0, c[k][0], c[k][1], c[k][2], c[k][3], db + k * 128, s + k);
        wgmma_rs_n176_t1(acc1, c[k][0], c[k][1], c[k][2], c[k][3], db + k * 128 + 3 * BOX / 16, s + k);
      } else {
        wgmma_rs_n192_t1(acc0, c[k][0], c[k][1], c[k][2], c[k][3], db + k * 128, s + k);
      }
    }
    wg_commit();
    wg_wait<1>();
    if (s > 0 && s <= NST - NB) {
      if (!FFN) { if (lane == 0) mbar_arrive(bE + ((s - 1) % NB) * 8); }
      else if (lane < 2) asm volatile("{\n.reg .b32 r;\nmapa.shared::cluster.u32 r,%0,%1;\nmbarrier.arrive.relaxed.cluster.shared::cluster.b64 _,[r];\n}" ::"r"(bE + ((s - 1) % NB) * 8), "r"(lane) : "memory");
    }
    if (s < NST - 1) {
#pragma unroll
      for (int k = 0; k < KS; k++) prep((s + 1) * KS + k, n[k]);
    }
  };
#pragma unroll
  for (int k = 0; k < KS; k++) prep(k, a[0][k]);
  TS(FFN ? 4 : 1, 2);
#pragma unroll 1
  for (int s = 0; s < NST; s += 2) { stage(s, a[0], a[1]); stage(s + 1, a[1], a[0]); }
  wg_wait<0>();
  reg_fence(acc0);
  TS(FFN ? 4 : 1, 3);
  if constexpr (FFN) {
    reg_fence(acc1);
    uint32_t* o = (uint32_t*)g_h + ((rb * 172 + ct * 22) * 128 + warp * 16 + g) * 4 + t;
#pragma unroll
    for (int j = 0; j < 22; j++) {
      {
        float h[4], d[4];
#pragma unroll
        for (int i = 0; i < 4; i++) { const float x = acc0[4 * j + i]; d[i] = 1.f + ex2(fminf(-1.4426950408889634f * x, 30.f)); h[i] = x * acc1[4 * j + i]; }
        const float d01 = d[0] * d[1], d23 = d[2] * d[3];
        float r; asm("rcp.approx.ftz.f32 %0,%1;" : "=f"(r) : "f"(d01 * d23));
        const float r01 = r * d23, r23 = r * d01;
        h[0] *= r01 * d[1]; h[1] *= r01 * d[0]; h[2] *= r23 * d[3]; h[3] *= r23 * d[2];
        if (j < 18 || ct < 7) { o[j * 512] = pack_rn(h[0], h[1]); o[j * 512 + 32] = pack_rn(h[2], h[3]); }
      }
    }
  } else {
    uint32_t* o = (uint32_t*)g_qkv + (ct * 24 * 2048 + row0) * 4 + t;
#pragma unroll
    for (int j = 0; j < 24; j += 2) {
      const int G = ct * 24 + j;
      const float sc = G < 64 ? 0.25f * 1.4426950408889634f : 1.f;
      uint32_t p[4];
#pragma unroll
      for (int i = 0; i < 4; i++) p[i] = pack_rn(acc0[4 * j + 2 * i] * sc, acc0[4 * j + 2 * i + 1] * sc);
      o[j * 8192] = p[0]; o[j * 8192 + 32] = p[1]; o[(j + 1) * 8192] = p[2]; o[(j + 1) * 8192 + 32] = p[3];
      if (G >= 64 && G < 128) {
        float n0 = blo(p[0]) * blo(p[0]) + bhi(p[0]) * bhi(p[0]) + blo(p[2]) * blo(p[2]) + bhi(p[2]) * bhi(p[2]);
        float n1 = blo(p[1]) * blo(p[1]) + bhi(p[1]) * bhi(p[1]) + blo(p[3]) * blo(p[3]) + bhi(p[3]) * bhi(p[3]);
        n0 = qsum(n0); n1 = qsum(n1);
        const uint32_t mx = __reduce_max_sync(~0u, max(__float_as_uint(n0), __float_as_uint(n1)));
        if (lane == 0) g_kmax[((G - 64) >> 1) * 128 + rb * 8 + warp] = __uint_as_float(mx);
      }
    }
  }
  TS(FFN ? 4 : 1, 4);
}
}

#define SMASK 0xCCCCu
#define BRK 0
#define PACK 1
constexpr int AT_SMEM = 5 * 32768 + 256;
__device__ __forceinline__ uint32_t exp2_pair_fma(float s0, float s1, float c, uint32_t ka, uint32_t kz) {
  uint32_t r;
  asm volatile("{\n.reg .b32 y0,y1,e,u,t;\n"
      "fma.rn.sat.f32 y0,%1,0f00000080,%3;\nfma.rn.sat.f32 y1,%2,0f00000080,%3;\n"
      "mad.lo.u32 e,y1,65536,y0;\n"
      "and.b32 u,e,0x007F007F;\n"
      "fma.rn.f16x2 u,u,%4,%5;\nfma.rn.f16x2 t,u,u,%6;\nfma.rn.f16x2 t,t,u,%7;\n"
      "lop3.b32 %0,t,0x007F007F,e,0xE2;\n}\n"
      : "=r"(r) : "f"(s0), "f"(s1), "f"(c), "r"(ka), "r"(0x36B236B2u), "r"(0x3C733C73u), "r"(0x47764776u), "r"(kz));
  return r;
}
__device__ __forceinline__ void attn_pass(float (&oa)[12], float (&ob)[12], const uint32_t (&q)[4], float m0, float m1, uint32_t sK, uint32_t bars, bool first, uint32_t kz) {
  uint64_t dk = mk_desc(sK, 32768, 128, 0), dv = mk_desc(sK + 65536, 128, 32768, 0);
  const float c0 = (127.f - m0) * __uint_as_float(0x80u), c1 = (127.f - m1) * __uint_as_float(0x80u);
  uint32_t ka;
  asm volatile("mov.b32 %0,0x7ACE7ACE;" : "=r"(ka));
  constexpr int NK = 64, NS = 32, NP = 16;
  auto qk = [&](float (&s)[NS], int i) { wgmma_rs_n64_t0(s, q[0], q[1], q[2], q[3], dk + i * NK, 0); };
  auto softmax = [&](float (&s)[NS], uint32_t (&p)[NP], uint32_t mask) {
    reg_fence(s);
    float e0, e1;
    int pend = -1;
#pragma unroll
    for (int t = 0; t < NP; t++) {
      const int j = (t & 3) * 4 + (t >> 2);
      if ((mask >> (t & 3)) & 1) {
        p[j] = exp2_pair_fma(s[2 * j], s[2 * j + 1], (j & 1) ? c1 : c0, ka, kz);
      } else {
        float f0, f1;
        asm volatile("ex2.approx.ftz.f32 %0,%2;\nex2.approx.ftz.f32 %1,%3;" : "=&f"(f0), "=f"(f1) : "f"(s[2 * j]), "f"(s[2 * j + 1]));
        if (pend >= 0) asm volatile("cvt.rn.bf16x2.f32 %0,%1,%2;" : "=r"(p[pend]) : "f"(e1), "f"(e0));
        e0 = f0; e1 = f1; pend = j;
      }
    }
    if (pend >= 0) asm volatile("cvt.rn.bf16x2.f32 %0,%1,%2;" : "=r"(p[pend]) : "f"(e1), "f"(e0));
#pragma unroll
    for (int j = 0; j < NP; j++) asm volatile("" : "+r"(p[j])::"memory");
  };
  auto pv = [&](uint32_t (&p)[NP], int i, uint32_t mask) {
#pragma unroll
    for (int k = 0; k < 4; k++) wgmma_rs_n24_t1(((mask >> k) & 1) ? ob : oa, p[4 * k], p[4 * k + 1], p[4 * k + 2], p[4 * k + 3], dv + i * NK + k * 16, 1);
  };
  constexpr uint32_t M0 = SMASK & 15, M1 = (SMASK >> 4) & 15, M2 = (SMASK >> 8) & 15, M3 = SMASK >> 12;
  zero(oa); zero(ob);
  mbar_wait(bars, 0);
  if (first) TS(2, 2);
  float s[NS];
  zero(s);
  uint32_t p0[NP], p1[NP];
  auto step = [&](int i, uint32_t (&pa)[NP], uint32_t ma, uint32_t (&pb)[NP], uint32_t mb) {
    wg_fence(); qk(s, i + 1); wg_commit(); pv(pa, i, ma); wg_commit(); wg_wait<1>(); softmax(s, pb, mb); wg_wait<0>();
  };
  wg_fence(); qk(s, 0); wg_commit(); wg_wait<0>(); softmax(s, p0, M0);
#pragma unroll 1
  for (uint32_t b = bars + 8; b < bars + 64; b += 8) {
    step(0, p0, M0, p1, M1); step(1, p1, M1, p0, M2); step(2, p0, M2, p1, M3);
    mbar_wait(b, 0);
    step(3, p1, M3, p0, M0);
    dk += 4 * NK; dv += 4 * NK;
  }
  step(0, p0, M0, p1, M1); step(1, p1, M1, p0, M2); step(2, p0, M2, p1, M3);
  wg_fence(); pv(p1, 3, M3); wg_commit();
  wg_wait<0>();
  reg_fence(oa); reg_fence(ob);
}
__device__ __forceinline__ void mma16816(float (&d)[4], const uint32_t (&a)[4], uint32_t b0, uint32_t b1) {
  asm("mma.sync.aligned.m16n8k16.row.col.f32.bf16.bf16.f32 {%0,%1,%2,%3},{%4,%5,%6,%7},{%8,%9},{%0,%1,%2,%3};"
      : "+f"(d[0]), "+f"(d[1]), "+f"(d[2]), "+f"(d[3]) : "r"(a[0]), "r"(a[1]), "r"(a[2]), "r"(a[3]), "r"(b0), "r"(b1));
}
__device__ __forceinline__ void attn_safe(float (&o)[12], const uint32_t (&q)[4], uint32_t sK) {
  const int lane = threadIdx.x & 31;
  const uint32_t ka = sK + (lane >> 4) * 32768 + (lane & 15) * 16;
  float m0 = -INFINITY, m1 = -INFINITY;
#pragma unroll 2
  for (int i = 0; i < 128; i++) {
    uint32_t k[4]; ldsm4(ka + i * 256, k);
    float s0[4] = {0, 0, 0, 0}, s1[4] = {0, 0, 0, 0};
    mma16816(s0, q, k[0], k[2]); mma16816(s1, q, k[1], k[3]);
    m0 = fmaxf(fmaxf(m0, fmaxf(s0[0], s0[1])), fmaxf(s1[0], s1[1])); m1 = fmaxf(fmaxf(m1, fmaxf(s0[2], s0[3])), fmaxf(s1[2], s1[3]));
  }
  m0 = fmaxf(m0, __shfl_xor_sync(~0u, m0, 1)); m0 = fmaxf(m0, __shfl_xor_sync(~0u, m0, 2));
  m1 = fmaxf(m1, __shfl_xor_sync(~0u, m1, 1)); m1 = fmaxf(m1, __shfl_xor_sync(~0u, m1, 2));
  float o0[4] = {0, 0, 0, 0}, o1[4] = {0, 0, 0, 0}, o2[4] = {0, 0, 0, 0};
#pragma unroll 2
  for (int i = 0; i < 128; i++) {
    uint32_t k[4], v[4]; ldsm4(ka + i * 256, k);
    asm volatile("ldmatrix.sync.aligned.m8n8.x4.trans.shared.b16 {%0,%1,%2,%3},[%4];" : "=r"(v[0]), "=r"(v[1]), "=r"(v[2]), "=r"(v[3]) : "r"(ka + 65536 + i * 256) : "memory");
    float s0[4] = {0, 0, 0, 0}, s1[4] = {0, 0, 0, 0};
    mma16816(s0, q, k[0], k[2]); mma16816(s1, q, k[1], k[3]);
    const uint32_t p[4] = {pack_rn(ex2(s0[0] - m0), ex2(s0[1] - m0)), pack_rn(ex2(s0[2] - m1), ex2(s0[3] - m1)),
                           pack_rn(ex2(s1[0] - m0), ex2(s1[1] - m0)), pack_rn(ex2(s1[2] - m1), ex2(s1[3] - m1))};
    mma16816(o0, p, v[0], v[1]); mma16816(o1, p, v[2], v[3]); mma16816(o2, p, 0x3F803F80u, 0x3F803F80u);
  }
#pragma unroll
  for (int i = 0; i < 4; i++) { o[i] = o0[i]; o[4 + i] = o1[i]; o[8 + i] = o2[i]; }
}
__global__ void __cluster_dims__(2, 1, 1) __launch_bounds__(512, 1) k_attn(const bf16* wo, const bf16* w1, const bf16* w3, const bf16* w2, const bf16* __restrict__ cv, const bf16* __restrict__ wm, uint32_t kz) {
  extern __shared__ __align__(1024) uint8_t smem[];
  const uint32_t sK = smem_u32(smem), bars = sK + 5 * 32768;
  const int tid = threadIdx.x, warp = tid >> 5, lane = tid & 31, g = lane >> 2, t = lane & 3;
  pdl_launch();
  if (blockIdx.x < 4) {
    float* cs = (float*)smem;
    cs[tid] = silu_bf(cv[tid]);
    __syncthreads();
    const int n0 = 1024 + blockIdx.x * 512, r0 = (tid >> 6) * 64;
    float a[8] = {0, 0, 0, 0, 0, 0, 0, 0};
#pragma unroll 16
    for (int r = r0; r < r0 + 64; r++) fma8(a, cs[r], __ldg((const uint4*)(wm + r * 3072 + n0 + (tid & 63) * 8)));
    float4* rp = (float4*)(cs + 512 + tid * 8);
    rp[0] = make_float4(a[0], a[1], a[2], a[3]); rp[1] = make_float4(a[4], a[5], a[6], a[7]);
    __syncthreads();
    float s = 0;
#pragma unroll
    for (int i = 0; i < 8; i++) s += cs[512 + i * 512 + tid];
    g_mod[n0 + tid] = mod_fin(s, n0 + tid);
    return;
  }
  const int bid = blockIdx.x - 4, h = bid >> 2, qb = bid & 3;
  TS(2, 0);
  if (tid == 0) { for (int i = 0; i < 8; i++) { mbar_init(bars + 8 * i, 1); mbar_expect(bars + 8 * i, 16384); } fence_init(); }
#pragma unroll
  for (int i = 0; i < 4; i++) *(uint4*)(smem + 131072 + i * 8192 + tid * 16) = make_uint4(0x3F803F80u, 0x3F803F80u, 0x3F803F80u, 0x3F803F80u);
  fence_async();
  cluster_sync();
  pdl_wait();
  TS(2, 1);
  if (tid >= 448) g_modv[bid * 64 + tid - 448] = 0;
  const uint4 km4 = *(const uint4*)(g_kmax + h * 128 + lane * 4);
  const uint32_t* qp = (const uint32_t*)g_qkv + (h * 2 * 2048 + qb * 512 + warp * 16 + g) * 4 + t;
  uint32_t q[4] = {qp[0], qp[32], qp[8192], qp[8192 + 32]};
  auto ldkv = [&]() {
    const int c = warp >> 1, pl = (qb & 1) + (warp & 1) * 2;
    bulk_load_mc(sK + pl * 32768 + c * 4096, g_qkv + ((64 + (pl >> 1) * 64 + h * 2 + (pl & 1)) * 2048 + c * 256) * 8, 4096, bars + 8 * c);
  };
  if (lane == 0 && warp < 4) ldkv();
  const uint32_t qn[4] = {qp[1024], qp[1024 + 32], qp[1024 + 8192], qp[1024 + 8192 + 32]};
  const float kmax = __uint_as_float(__reduce_max_sync(~0u, max(max(km4.x, km4.y), max(km4.z, km4.w))));
  if (lane == 0 && warp >= 4 && kmax != -1.f) ldkv();
#pragma unroll 1
  for (int tile = 0; tile < 2; tile++) {
    const int row = qb * 512 + tile * 256 + warp * 16 + g;
    const float n0 = qsum(blo(q[0]) * blo(q[0]) + bhi(q[0]) * bhi(q[0]) + blo(q[2]) * blo(q[2]) + bhi(q[2]) * bhi(q[2]));
    const float n1 = qsum(blo(q[1]) * blo(q[1]) + bhi(q[1]) * bhi(q[1]) + blo(q[3]) * blo(q[3]) + bhi(q[3]) * bhi(q[3]));
    const float b0 = sqrtf(n0 * kmax) * 1.001f, b1 = sqrtf(n1 * kmax) * 1.001f;
    const float m0 = fmaxf(ceilf(b0 - 100.f), 0.f), m1 = fmaxf(ceilf(b1 - 100.f), 0.f);
    float o[12], ob[12];
    attn_pass(o, ob, q, m0, m1, sK, bars, tile == 0, kz);
    const float f0 = ex2(-m0), f1 = ex2(-m1);
#pragma unroll
    for (int i = 0; i < 12; i++) o[i] = fmaf(o[i], (i & 2) ? f1 : f0, ob[i]);
    bool ok = b0 < 220.f && b1 < 220.f && o[8] >= 0x1p-90f && o[10] >= 0x1p-90f;
#pragma unroll
    for (int i = 0; i < 12; i++) ok = ok && fabsf(o[i]) < INFINITY;
    if (!__all_sync(~0u, ok)) attn_safe(o, q, sK);
    const float r0 = 1.f / o[8], r1 = 1.f / o[10];
    uint32_t* op = (uint32_t*)g_o + (((row >> 7) * 64 + h * 2) * 128 + (row & 127)) * 4 + t;
    op[0] = pack_rn(o[0] * r0, o[1] * r0); op[32] = pack_rn(o[2] * r1, o[3] * r1);
    op[512] = pack_rn(o[4] * r0, o[5] * r0); op[512 + 32] = pack_rn(o[6] * r1, o[7] * r1);
    if (tile == 0 && tid == 32) {
      l2_prefetch((const char*)wo + bid * 4096, 4096);
      l2_prefetch((const char*)w1 + bid * 11008, 11008);
      l2_prefetch((const char*)w3 + bid * 11008, 11008);
      l2_prefetch((const char*)w2 + bid * 11008, 11008);
    }
#pragma unroll
    for (int i = 0; i < 4; i++) q[i] = qn[i];
    TS(2, 3 + tile);
  }
}

constexpr int WO_SMEM = 131072 + 65536 + 256;
__global__ void __cluster_dims__(2, 1, 1) __launch_bounds__(256, 1) k_wo(const __grid_constant__ CUtensorMap mW, const bf16* __restrict__ x) {
  extern __shared__ __align__(1024) uint8_t smem[];
  const uint32_t sA = smem_u32(smem), sB = sA + 131072, bars = sB + 65536;
  const int tid = threadIdx.x, warp = tid >> 5, lane = tid & 31, g = lane >> 2, t = lane & 3;
  const int rb = blockIdx.x >> 3, ct = blockIdx.x & 7;
  TS(3, 0);
  pdl_launch();
  if (tid == 0) {
    for (int i = 0; i < 8; i++) mbar_init(bars + 8 * i, 1);
    fence_init();
    for (int i = 0; i < 8; i++) { mbar_expect(bars + 8 * i, 24576); tma2d(sB + i * 8192, &mW, ct * 64, i * 64, bars + 8 * i); }
  }
  __syncwarp();
  cluster_arrive();
  const int lrow = warp * 16 + g;
  uint32_t xr[16];
  const uint32_t* xp = (const uint32_t*)(x + (rb * 128 + lrow) * 512 + ct * 64) + t;
#pragma unroll
  for (int j = 0; j < 8; j++) { xr[2 * j] = __ldg(xp + j * 4); xr[2 * j + 1] = __ldg(xp + j * 4 + 8 * 256); }
  cluster_wait();
  pdl_wait();
  if (tid == 0) {
    for (int i = ct & 1; i < 8; i += 2) bulk_load_mc(sA + i * 16384, g_o + (rb * 64 + i * 8) * 1024, 16384, bars + 8 * i);
  }
  TS(3, 1);
  float2 ga[8];
#pragma unroll
  for (int j = 0; j < 8; j++) ga[j] = *(const float2*)(g_mod + 1024 + ct * 64 + j * 8 + t * 2);
  float acc[32];
  const uint64_t da = mk_desc(sA + (warp >> 2) * 1024, 2048, 128, 0), db = mk_desc(sB, 8192, 1024, 1);
#pragma unroll
  for (int c = 0; c < 8; c++) {
    mbar_wait(bars + 8 * c, 0);
    if (c == 0) TS(3, 2);
    wg_fence();
#pragma unroll
    for (int k = 0; k < 4; k++) wgmma_ss_n64_t1(acc, da + (c * 4 + k) * 256, db + (c * 4 + k) * 128, c + k);
    wg_commit();
  }
  wg_wait<0>();
  reg_fence(acc);
  TS(3, 3);
  uint32_t* o = (uint32_t*)g_x1 + ((rb * 64 + ct * 8) * 128 + lrow) * 4 + t;
  float s0 = 0, s1 = 0;
#pragma unroll
  for (int j = 0; j < 8; j++) {
    xr[2 * j] = pack_rn(fmaf(ga[j].x, acc[4 * j], blo(xr[2 * j])), fmaf(ga[j].y, acc[4 * j + 1], bhi(xr[2 * j])));
    xr[2 * j + 1] = pack_rn(fmaf(ga[j].x, acc[4 * j + 2], blo(xr[2 * j + 1])), fmaf(ga[j].y, acc[4 * j + 3], bhi(xr[2 * j + 1])));
    o[j * 512] = xr[2 * j]; o[j * 512 + 32] = xr[2 * j + 1];
    s0 += blo(xr[2 * j]) + bhi(xr[2 * j]); s1 += blo(xr[2 * j + 1]) + bhi(xr[2 * j + 1]);
  }
  const float m0 = qsum(s0) * (1.f / 64), m1 = qsum(s1) * (1.f / 64);
  float v0 = 0, v1 = 0;
#pragma unroll
  for (int j = 0; j < 8; j++) {
    float d;
    d = blo(xr[2 * j]) - m0; v0 += d * d; d = bhi(xr[2 * j]) - m0; v0 += d * d;
    d = blo(xr[2 * j + 1]) - m1; v1 += d * d; d = bhi(xr[2 * j + 1]) - m1; v1 += d * d;
  }
  v0 = qsum(v0); v1 = qsum(v1);
  if (t == 0) g_st[(rb * 128 + lrow) * 8 + ct] = make_float2(m0, v0);
  if (t == 1) g_st[(rb * 128 + lrow + 8) * 8 + ct] = make_float2(m1, v1);
  TS(3, 4);
}

constexpr int W2_SMEM = 6 * 32768 + 32768 + 256;
__global__ void __cluster_dims__(2, 1, 1) __launch_bounds__(288, 1) k_w2(const __grid_constant__ CUtensorMap mW, bf16* __restrict__ out) {
  extern __shared__ __align__(1024) uint8_t smem[];
  const uint32_t sR = smem_u32(smem), sX = sR + 6 * 32768, bF = sX + 32768, bE = bF + 48, bX = bF + 96;
  const int tid = threadIdx.x, warp = tid >> 5, lane = tid & 31, g = lane >> 2, t = lane & 3;
  const int kh = blockIdx.x & 1, ct = (blockIdx.x >> 1) & 3, rb = blockIdx.x >> 3;
  TS(5, 0);
  pdl_launch();
  if (tid == 256) {
    for (int i = 0; i < 6; i++) { mbar_init(bF + 8 * i, 1); mbar_init(bE + 8 * i, 8); }
    for (int i = 0; i < 8; i++) { mbar_init(bX + 8 * i, 1); mbar_expect(bX + 8 * i, 4096); }
    fence_init();
  }
  __syncthreads();
  asm volatile("barrier.cluster.arrive.relaxed.aligned;" ::: "memory");
  if (warp == 8) {
    if (lane == 0) {
      auto abytes = [&](int s) { return (kh == 1 && s == 10) ? 8192 : 16384; };
      auto loadB = [&](int s) {
        const int st = s % 6;
        mbar_expect(bF + 8 * st, 16384 + abytes(s));
        for (int j = 0; j < 2; j++) tma2d(sR + st * 32768 + 16384 + j * 8192, &mW, ct * 128 + j * 64, kh * 704 + s * 64, bF + 8 * st);
      };
      auto loadA = [&](int s) { bulk_load(sR + (s % 6) * 32768, g_h + (rb * 172 + kh * 88 + s * 8) * 1024, abytes(s), bF + 8 * (s % 6)); };
      for (int s = 0; s < 6; s++) loadB(s);
      pdl_wait();
      for (int s = 0; s < 6; s++) loadA(s);
      for (int s = 6; s < 11; s++) { mbar_wait(bE + 8 * (s - 6), 0); loadB(s); loadA(s); }
    }
    __syncwarp();
    cluster_wait();
    return;
  }
  pdl_wait();
  TS(5, 1);
  const int lrow = warp * 16 + g;
  uint32_t xr[16];
  float2 gb[8];
  const uint32_t* xp = (const uint32_t*)g_x1 + ((rb * 64 + ct * 16 + kh * 8) * 128 + lrow) * 4 + t;
#pragma unroll
  for (int j = 0; j < 8; j++) {
    xr[2 * j] = xp[j * 512]; xr[2 * j + 1] = xp[j * 512 + 32];
    gb[j] = *(const float2*)(g_mod + 2560 + ct * 128 + kh * 64 + j * 8 + t * 2);
  }
  float acc[64];
#pragma unroll 1
  for (int s = 0; s < 11; s++) {
    const int st = s % 6;
    mbar_wait(bF + 8 * st, s >= 6);
    const uint64_t da = mk_desc(sR + st * 32768 + (warp >> 2) * 1024, 2048, 128, 0), db = mk_desc(sR + st * 32768 + 16384, 8192, 1024, 1);
    if (s == 0) TS(5, 2);
    wg_fence();
    wgmma_ss_n128_t1(acc, da, db, s);
    wgmma_ss_n128_t1(acc, da + 256, db + 128, 1);
    wgmma_ss_n128_t1(acc, da + 512, db + 256, 1);
    wgmma_ss_n128_t1(acc, da + 768, db + 384, 1);
    wg_commit();
    wg_wait<1>();
    if (s > 0 && s < 6 && lane == 0) mbar_arrive(bE + 8 * (s - 1));
  }
  wg_wait<0>();
  reg_fence(acc);
  TS(5, 3);
  asm volatile("barrier.cluster.wait.aligned;" ::: "memory");
  uint32_t rem, rbar;
  asm("mapa.shared::cluster.u32 %0,%1,%2;" : "=r"(rbar) : "r"(bX + warp * 8), "r"(kh ^ 1));
  asm("mapa.shared::cluster.u32 %0,%1,%2;" : "=r"(rem) : "r"(sX + warp * 4096 + lane * 16), "r"(kh ^ 1));
#pragma unroll
  for (int j = 0; j < 8; j++) {
    float v[4];
#pragma unroll
    for (int i = 0; i < 4; i++) { v[i] = kh ? acc[4 * j + i] : acc[32 + 4 * j + i]; acc[4 * j + i] = kh ? acc[32 + 4 * j + i] : acc[4 * j + i]; }
    asm volatile("st.async.weak.shared::cluster.mbarrier::complete_tx::bytes.v4.f32 [%0],{%1,%2,%3,%4},[%5];" ::"r"(rem + j * 512), "f"(v[0]), "f"(v[1]), "f"(v[2]), "f"(v[3]), "r"(rbar) : "memory");
  }
  mbar_wait(bX + warp * 8, 0);
  TS(5, 5);
  const uint32_t sw = sX + warp * 4096;
#pragma unroll
  for (int j = 0; j < 8; j++) {
    const float4 p = *(const float4*)(smem + 6 * 32768 + warp * 4096 + j * 512 + lane * 16);
    xr[2 * j] = pack_rn(fmaf(gb[j].x, acc[4 * j] + p.x, blo(xr[2 * j])), fmaf(gb[j].y, acc[4 * j + 1] + p.y, bhi(xr[2 * j])));
    xr[2 * j + 1] = pack_rn(fmaf(gb[j].x, acc[4 * j + 2] + p.z, blo(xr[2 * j + 1])), fmaf(gb[j].y, acc[4 * j + 3] + p.w, bhi(xr[2 * j + 1])));
  }
  __syncwarp();
#pragma unroll
  for (int j = 1; j < 8; j += 2) {
    asm volatile("stmatrix.sync.aligned.m8n8.x4.shared.b16 [%0],{%1,%2,%3,%4};" ::"r"(sw + (lane & 15) * 128 + (((j - 1 + (lane >> 4)) ^ (lane & 7)) << 4)),
                            "r"(xr[2 * j - 2]), "r"(xr[2 * j - 1]), "r"(xr[2 * j]), "r"(xr[2 * j + 1]) : "memory");
  }
  __syncwarp();
#pragma unroll
  for (int i = 0; i < 4; i++) {
    const int r = i * 4 + (lane >> 3);
    *(uint4*)(out + (rb * 128 + warp * 16 + r) * 512 + ct * 128 + kh * 64 + (lane & 7) * 8) = *(const uint4*)(smem + 6 * 32768 + warp * 4096 + r * 128 + (((lane ^ r) & 7) << 4));
  }
  TS(5, 4);
}

typedef CUresult (*EncFn)(CUtensorMap*, CUtensorMapDataType, cuuint32_t, void*, const cuuint64_t*, const cuuint64_t*, const cuuint32_t*,
                          const cuuint32_t*, CUtensorMapInterleave, CUtensorMapSwizzle, CUtensorMapL2promotion, CUtensorMapFloatOOBfill);
static void mk_map(EncFn f, CUtensorMap* m, const void* p, int rows, int cols, int box_rows) {
  cuuint64_t dim[2] = {(cuuint64_t)cols, (cuuint64_t)rows}, str[1] = {(cuuint64_t)cols * 2};
  cuuint32_t box[2] = {64, (cuuint32_t)box_rows}, es[2] = {1, 1};
  f(m, CU_TENSOR_MAP_DATA_TYPE_BFLOAT16, 2, (void*)p, dim, str, box, es, CU_TENSOR_MAP_INTERLEAVE_NONE, CU_TENSOR_MAP_SWIZZLE_128B,
    CU_TENSOR_MAP_L2_PROMOTION_L2_128B, CU_TENSOR_MAP_FLOAT_OOB_FILL_NONE);
}
template <typename... KA, typename... A>
static void launch(void (*k)(KA...), int grid, int block, int smem, bool pdl, A... args) {
  cudaLaunchConfig_t cfg = {};
  cfg.gridDim = dim3(grid); cfg.blockDim = dim3(block); cfg.dynamicSmemBytes = smem; cfg.stream = cudaStreamPerThread;
  cudaLaunchAttribute at[1];
  at[0].id = cudaLaunchAttributeProgrammaticStreamSerialization; at[0].val.programmaticStreamSerializationAllowed = 1;
  cfg.attrs = at; cfg.numAttrs = pdl ? 1 : 0;
  cudaLaunchKernelEx(&cfg, k, args...);
}
extern "C" void kernel_launch(void* const* d_in, const int* in_sizes, int n_in, void* d_out, int out_size) {
  const bf16 *x = (const bf16*)d_in[0], *wqkv = (const bf16*)d_in[1], *wo = (const bf16*)d_in[2], *w1 = (const bf16*)d_in[4],
             *w3 = (const bf16*)d_in[5], *w2 = (const bf16*)d_in[6], *c = (const bf16*)d_in[7], *wmod = (const bf16*)d_in[8];
  void* fp = nullptr;
  cudaDriverEntryPointQueryResult qr;
  cudaGetDriverEntryPoint("cuTensorMapEncodeTiled", &fp, cudaEnableDefault, &qr);
  EncFn f = (EncFn)fp;
  CUtensorMap mX, mQ, mO, m1, m3, m2;
  mk_map(f, &mX, x, S_, D_, 128); mk_map(f, &mQ, wqkv, D_, 3 * D_, 64); mk_map(f, &mO, wo, D_, D_, 64);
  mk_map(f, &m1, w1, D_, F_, 32); mk_map(f, &m3, w3, D_, F_, 32); mk_map(f, &m2, w2, F_, D_, 64);
  cudaFuncSetAttribute(k_lngemm<false>, cudaFuncAttributeMaxDynamicSharedMemorySize, LN_SMEM);
  cudaFuncSetAttribute(k_lngemm<true>, cudaFuncAttributeMaxDynamicSharedMemorySize, LN_SMEM);
  cudaFuncSetAttribute(k_attn, cudaFuncAttributeMaxDynamicSharedMemorySize, AT_SMEM);
  cudaFuncSetAttribute(k_wo, cudaFuncAttributeMaxDynamicSharedMemorySize, WO_SMEM);
  cudaFuncSetAttribute(k_w2, cudaFuncAttributeMaxDynamicSharedMemorySize, W2_SMEM);
  launch(k_lngemm<false>, 128, 384, LN_SMEM, false, mX, mQ, mQ, c, wmod, x, wqkv);
  launch(k_attn, 132, 512, AT_SMEM, true, wo, w1, w3, w2, c, wmod, 0u);
  launch(k_wo, 128, 256, WO_SMEM, true, mO, x);
  launch(k_lngemm<true>, 128, 384, LN_SMEM, true, mX, m1, m3, c, wmod, x, wqkv);
  launch(k_w2, 128, 288, W2_SMEM, true, m2, (bf16*)d_out);
}
```

```cpp
#include <cuda_runtime.h>
#include <cuda_bf16.h>
#include <cuda.h>
#include <stdint.h>
typedef __nv_bfloat16 bf16;
constexpr int S_ = 2048, D_ = 512, F_ = 1376;
__device__ __align__(1024) float g_mod[3072];
__device__ __align__(1024) uint32_t g_modv[4096 + 4096];
__device__ __align__(1024) bf16 g_qkv[192 * 2048 * 8];
__device__ __align__(1024) float g_kmax[32 * 128];
__device__ __align__(1024) bf16 g_o[16 * 64 * 128 * 8];
__device__ __align__(1024) bf16 g_x1[16 * 64 * 128 * 8];
__device__ __align__(1024) bf16 g_a[16 * 64 * 128 * 8];
__device__ __align__(1024) float2 g_uv[2 * 1408];
__device__ __align__(1024) float2 g_st[2048 * 8];
__device__ __align__(1024) bf16 g_h[16 * 172 * 128 * 8];

__device__ __forceinline__ uint32_t smem_u32(const void* p) { return (uint32_t)__cvta_generic_to_shared(p); }
__device__ __forceinline__ void mbar_init(uint32_t b, int n) { asm volatile("mbarrier.init.shared::cta.b64 [%0],%1;" ::"r"(b), "r"(n) : "memory"); }
__device__ __forceinline__ void mbar_expect(uint32_t b, int bytes) { asm volatile("mbarrier.arrive.expect_tx.shared::cta.b64 _,[%0],%1;" ::"r"(b), "r"(bytes) : "memory"); }
__device__ __forceinline__ void mbar_arrive(uint32_t b) { asm volatile("mbarrier.arrive.shared::cta.b64 _,[%0];" ::"r"(b) : "memory"); }
__device__ __forceinline__ void mbar_wait(uint32_t b, int parity) {
  asm volatile("{\n.reg .pred p;\n.reg .u32 n;\nmov.u32 n,0;\nLW:\nmbarrier.try_wait.parity.shared::cta.b64 p,[%0],%1;\n@p bra LD;\n"
               "add.u32 n,n,1;\nsetp.lt.u32 p,n,4194304;\n@p bra LW;\nLD:\n}\n" ::"r"(b), "r"(parity) : "memory");
}
__device__ __forceinline__ void fence_init() { asm volatile("fence.mbarrier_init.release.cluster;" ::: "memory"); }
__device__ __forceinline__ void fence_async() { asm volatile("fence.proxy.async.shared::cta;" ::: "memory"); }
__device__ __forceinline__ void bulk_load(uint32_t dst, const void* src, int bytes, uint32_t bar) {
  asm volatile("cp.async.bulk.shared::cluster.global.mbarrier::complete_tx::bytes [%0],[%1],%2,[%3];" ::"r"(dst), "l"(src), "r"(bytes), "r"(bar) : "memory");
}
__device__ __forceinline__ void tma2d(uint32_t dst, const CUtensorMap* m, int c0, int c1, uint32_t bar) {
  asm volatile("cp.async.bulk.tensor.2d.shared::cluster.global.mbarrier::complete_tx::bytes [%0],[%1,{%3,%4}],[%2];" ::"r"(dst), "l"(m), "r"(bar), "r"(c0), "r"(c1) : "memory");
}
__device__ __forceinline__ void bulk_load_mc(uint32_t dst, const void* src, int bytes, uint32_t bar) {
  asm volatile("cp.async.bulk.shared::cluster.global.mbarrier::complete_tx::bytes.multicast::cluster [%0],[%1],%2,[%3],%4;" ::"r"(dst), "l"(src), "r"(bytes), "r"(bar), "h"((uint16_t)3) : "memory");
}
__device__ __forceinline__ void tma2d_mc(uint32_t dst, const CUtensorMap* m, int c0, int c1, uint32_t bar) {
  asm volatile("cp.async.bulk.tensor.2d.shared::cluster.global.mbarrier::complete_tx::bytes.multicast::cluster [%0],[%1,{%3,%4}],[%2],%5;" ::"r"(dst), "l"(m), "r"(bar), "r"(c0), "r"(c1), "h"((uint16_t)3) : "memory");
}
__device__ __forceinline__ void cluster_arrive() { asm volatile("barrier.cluster.arrive.relaxed.aligned;" ::: "memory"); }
__device__ __forceinline__ void cluster_wait() { asm volatile("barrier.cluster.wait.aligned;" ::: "memory"); }
__device__ __forceinline__ void cluster_sync() { asm volatile("barrier.cluster.arrive.release.aligned;\nbarrier.cluster.wait.acquire.aligned;" ::: "memory"); }
__device__ __forceinline__ void l2_prefetch(const void* p, int bytes) { asm volatile("cp.async.bulk.prefetch.L2.global [%0],%1;" ::"l"(p), "r"(bytes) : "memory"); }
__device__ __forceinline__ void pdl_launch() { asm volatile("griddepcontrol.launch_dependents;" ::: "memory"); }
__device__ __forceinline__ void pdl_wait() { asm volatile("griddepcontrol.wait;" ::: "memory"); }
__device__ __forceinline__ void wg_fence() { asm volatile("wgmma.fence.sync.aligned;" ::: "memory"); }
__device__ __forceinline__ void wg_commit() { asm volatile("wgmma.commit_group.sync.aligned;" ::: "memory"); }
template <int N> __device__ __forceinline__ void wg_wait() { asm volatile("wgmma.wait_group.sync.aligned %0;" ::"n"(N) : "memory"); }
template <int N> __device__ __forceinline__ void reg_fence(float (&d)[N]) {
#pragma unroll
  for (int i = 0; i < N; i++) asm volatile("" : "+f"(d[i])::"memory");
}
template <int N> __device__ __forceinline__ void zero(float (&d)[N]) {
#pragma unroll
  for (int i = 0; i < N; i++) d[i] = 0.f;
  reg_fence(d);
}
__device__ __forceinline__ uint64_t mk_desc(uint32_t addr, uint32_t lbo, uint32_t sbo, uint32_t mode) {
  return (uint64_t)((addr >> 4) & 0x3FFF) | ((uint64_t)(lbo >> 4) << 16) | ((uint64_t)(sbo >> 4) << 32) | ((uint64_t)mode << 62);
}
__device__ __forceinline__ void ldsm4(uint32_t a, uint32_t (&r)[4]) {
  asm volatile("ldmatrix.sync.aligned.m8n8.x4.shared.b16 {%0,%1,%2,%3},[%4];" : "=r"(r[0]), "=r"(r[1]), "=r"(r[2]), "=r"(r[3]) : "r"(a) : "memory");
}
__device__ __forceinline__ uint32_t pack_rn(float lo, float hi) { uint32_t r; asm("cvt.rn.bf16x2.f32 %0,%1,%2;" : "=r"(r) : "f"(hi), "f"(lo)); return r; }
__device__ __forceinline__ uint32_t pack_rz(float lo, float hi) { uint32_t r; asm("cvt.rz.bf16x2.f32 %0,%1,%2;" : "=r"(r) : "f"(hi), "f"(lo)); return r; }
__device__ __forceinline__ float blo(uint32_t u) { return __uint_as_float(u << 16); }
__device__ __forceinline__ float bhi(uint32_t u) { return __uint_as_float(u & 0xFFFF0000u); }
__device__ __forceinline__ float rbf(float x) { return __bfloat162float(__float2bfloat16_rn(x)); }
__device__ __forceinline__ float qsum(float v) { v += __shfl_xor_sync(~0u, v, 1); return v + __shfl_xor_sync(~0u, v, 2); }
__device__ __forceinline__ float ex2(float x) { float r; asm("ex2.approx.ftz.f32 %0,%1;" : "=f"(r) : "f"(x)); return r; }
#define TS(k, i)
__device__ __forceinline__ void wgmma_rs_n176_t1(float (&d)[88],uint32_t a0,uint32_t a1,uint32_t a2,uint32_t a3,uint64_t db,int sc){
  asm volatile("{\n.reg .pred p;\nsetp.ne.b32 p,%93,0;\n"
    "wgmma.mma_async.sync.aligned.m64n176k16.f32.bf16.bf16 {%0,%1,%2,%3,%4,%5,%6,%7,%8,%9,%10,%11,%12,%13,%14,%15,%16,%17,%18,%19,%20,%21,%22,%23,%24,%25,%26,%27,%28,%29,%30,%31,%32,%33,%34,%35,%36,%37,%38,%39,%40,%41,%42,%43,%44,%45,%46,%47,%48,%49,%50,%51,%52,%53,%54,%55,%56,%57,%58,%59,%60,%61,%62,%63,%64,%65,%66,%67,%68,%69,%70,%71,%72,%73,%74,%75,%76,%77,%78,%79,%80,%81,%82,%83,%84,%85,%86,%87},{%88,%89,%90,%91},%92,p,1,1,1;\n}\n"
    :"+f"(d[0]),"+f"(d[1]),"+f"(d[2]),"+f"(d[3]),"+f"(d[4]),"+f"(d[5]),"+f"(d[6]),"+f"(d[7]),"+f"(d[8]),"+f"(d[9]),"+f"(d[10]),"+f"(d[11]),"+f"(d[12]),"+f"(d[13]),"+f"(d[14]),"+f"(d[15]),"+f"(d[16]),"+f"(d[17]),"+f"(d[18]),"+f"(d[19]),"+f"(d[20]),"+f"(d[21]),"+f"(d[22]),"+f"(d[23]),"+f"(d[24]),"+f"(d[25]),"+f"(d[26]),"+f"(d[27]),"+f"(d[28]),"+f"(d[29]),"+f"(d[30]),"+f"(d[31]),"+f"(d[32]),"+f"(d[33]),"+f"(d[34]),"+f"(d[35]),"+f"(d[36]),"+f"(d[37]),"+f"(d[38]),"+f"(d[39]),"+f"(d[40]),"+f"(d[41]),"+f"(d[42]),"+f"(d[43]),"+f"(d[44]),"+f"(d[45]),"+f"(d[46]),"+f"(d[47]),"+f"(d[48]),"+f"(d[49]),"+f"(d[50]),"+f"(d[51]),"+f"(d[52]),"+f"(d[53]),"+f"(d[54]),"+f"(d[55]),"+f"(d[56]),"+f"(d[57]),"+f"(d[58]),"+f"(d[59]),"+f"(d[60]),"+f"(d[61]),"+f"(d[62]),"+f"(d[63]),"+f"(d[64]),"+f"(d[65]),"+f"(d[66]),"+f"(d[67]),"+f"(d[68]),"+f"(d[69]),"+f"(d[70]),"+f"(d[71]),"+f"(d[72]),"+f"(d[73]),"+f"(d[74]),"+f"(d[75]),"+f"(d[76]),"+f"(d[77]),"+f"(d[78]),"+f"(d[79]),"+f"(d[80]),"+f"(d[81]),"+f"(d[82]),"+f"(d[83]),"+f"(d[84]),"+f"(d[85]),"+f"(d[86]),"+f"(d[87])
    :"r"(a0),"r"(a1),"r"(a2),"r"(a3),"l"(db),"r"(sc));
}
__device__ __forceinline__ void wgmma_rs_n192_t1(float (&d)[96],uint32_t a0,uint32_t a1,uint32_t a2,uint32_t a3,uint64_t db,int sc){
  asm volatile("{\n.reg .pred p;\nsetp.ne.b32 p,%101,0;\n"
    "wgmma.mma_async.sync.aligned.m64n192k16.f32.bf16.bf16 {%0,%1,%2,%3,%4,%5,%6,%7,%8,%9,%10,%11,%12,%13,%14,%15,%16,%17,%18,%19,%20,%21,%22,%23,%24,%25,%26,%27,%28,%29,%30,%31,%32,%33,%34,%35,%36,%37,%38,%39,%40,%41,%42,%43,%44,%45,%46,%47,%48,%49,%50,%51,%52,%53,%54,%55,%56,%57,%58,%59,%60,%61,%62,%63,%64,%65,%66,%67,%68,%69,%70,%71,%72,%73,%74,%75,%76,%77,%78,%79,%80,%81,%82,%83,%84,%85,%86,%87,%88,%89,%90,%91,%92,%93,%94,%95},{%96,%97,%98,%99},%100,p,1,1,1;\n}\n"
    :"+f"(d[0]),"+f"(d[1]),"+f"(d[2]),"+f"(d[3]),"+f"(d[4]),"+f"(d[5]),"+f"(d[6]),"+f"(d[7]),"+f"(d[8]),"+f"(d[9]),"+f"(d[10]),"+f"(d[11]),"+f"(d[12]),"+f"(d[13]),"+f"(d[14]),"+f"(d[15]),"+f"(d[16]),"+f"(d[17]),"+f"(d[18]),"+f"(d[19]),"+f"(d[20]),"+f"(d[21]),"+f"(d[22]),"+f"(d[23]),"+f"(d[24]),"+f"(d[25]),"+f"(d[26]),"+f"(d[27]),"+f"(d[28]),"+f"(d[29]),"+f"(d[30]),"+f"(d[31]),"+f"(d[32]),"+f"(d[33]),"+f"(d[34]),"+f"(d[35]),"+f"(d[36]),"+f"(d[37]),"+f"(d[38]),"+f"(d[39]),"+f"(d[40]),"+f"(d[41]),"+f"(d[42]),"+f"(d[43]),"+f"(d[44]),"+f"(d[45]),"+f"(d[46]),"+f"(d[47]),"+f"(d[48]),"+f"(d[49]),"+f"(d[50]),"+f"(d[51]),"+f"(d[52]),"+f"(d[53]),"+f"(d[54]),"+f"(d[55]),"+f"(d[56]),"+f"(d[57]),"+f"(d[58]),"+f"(d[59]),"+f"(d[60]),"+f"(d[61]),"+f"(d[62]),"+f"(d[63]),"+f"(d[64]),"+f"(d[65]),"+f"(d[66]),"+f"(d[67]),"+f"(d[68]),"+f"(d[69]),"+f"(d[70]),"+f"(d[71]),"+f"(d[72]),"+f"(d[73]),"+f"(d[74]),"+f"(d[75]),"+f"(d[76]),"+f"(d[77]),"+f"(d[78]),"+f"(d[79]),"+f"(d[80]),"+f"(d[81]),"+f"(d[82]),"+f"(d[83]),"+f"(d[84]),"+f"(d[85]),"+f"(d[86]),"+f"(d[87]),"+f"(d[88]),"+f"(d[89]),"+f"(d[90]),"+f"(d[91]),"+f"(d[92]),"+f"(d[93]),"+f"(d[94]),"+f"(d[95])
    :"r"(a0),"r"(a1),"r"(a2),"r"(a3),"l"(db),"r"(sc));
}
__device__ __forceinline__ void wgmma_rs_n24_t1(float (&d)[12],uint32_t a0,uint32_t a1,uint32_t a2,uint32_t a3,uint64_t db,int sc){
  asm volatile("{\n.reg .pred p;\nsetp.ne.b32 p,%17,0;\n"
    "wgmma.mma_async.sync.aligned.m64n24k16.f32.bf16.bf16 {%0,%1,%2,%3,%4,%5,%6,%7,%8,%9,%10,%11},{%12,%13,%14,%15},%16,p,1,1,1;\n}\n"
    :"+f"(d[0]),"+f"(d[1]),"+f"(d[2]),"+f"(d[3]),"+f"(d[4]),"+f"(d[5]),"+f"(d[6]),"+f"(d[7]),"+f"(d[8]),"+f"(d[9]),"+f"(d[10]),"+f"(d[11])
    :"r"(a0),"r"(a1),"r"(a2),"r"(a3),"l"(db),"r"(sc));
}
__device__ __forceinline__ void wgmma_rs_n64_t0(float (&d)[32],uint32_t a0,uint32_t a1,uint32_t a2,uint32_t a3,uint64_t db,int sc){
  asm volatile("{\n.reg .pred p;\nsetp.ne.b32 p,%37,0;\n"
    "wgmma.mma_async.sync.aligned.m64n64k16.f32.bf16.bf16 {%0,%1,%2,%3,%4,%5,%6,%7,%8,%9,%10,%11,%12,%13,%14,%15,%16,%17,%18,%19,%20,%21,%22,%23,%24,%25,%26,%27,%28,%29,%30,%31},{%32,%33,%34,%35},%36,p,1,1,0;\n}\n"
    :"+f"(d[0]),"+f"(d[1]),"+f"(d[2]),"+f"(d[3]),"+f"(d[4]),"+f"(d[5]),"+f"(d[6]),"+f"(d[7]),"+f"(d[8]),"+f"(d[9]),"+f"(d[10]),"+f"(d[11]),"+f"(d[12]),"+f"(d[13]),"+f"(d[14]),"+f"(d[15]),"+f"(d[16]),"+f"(d[17]),"+f"(d[18]),"+f"(d[19]),"+f"(d[20]),"+f"(d[21]),"+f"(d[22]),"+f"(d[23]),"+f"(d[24]),"+f"(d[25]),"+f"(d[26]),"+f"(d[27]),"+f"(d[28]),"+f"(d[29]),"+f"(d[30]),"+f"(d[31])
    :"r"(a0),"r"(a1),"r"(a2),"r"(a3),"l"(db),"r"(sc));
}
__device__ __forceinline__ void wgmma_ss_n128_t1(float (&d)[64],uint64_t da,uint64_t db,int sc){
  asm volatile("{\n.reg .pred p;\nsetp.ne.b32 p,%66,0;\n"
    "wgmma.mma_async.sync.aligned.m64n128k16.f32.bf16.bf16 {%0,%1,%2,%3,%4,%5,%6,%7,%8,%9,%10,%11,%12,%13,%14,%15,%16,%17,%18,%19,%20,%21,%22,%23,%24,%25,%26,%27,%28,%29,%30,%31,%32,%33,%34,%35,%36,%37,%38,%39,%40,%41,%42,%43,%44,%45,%46,%47,%48,%49,%50,%51,%52,%53,%54,%55,%56,%57,%58,%59,%60,%61,%62,%63},%64,%65,p,1,1,0,1;\n}\n"
    :"+f"(d[0]),"+f"(d[1]),"+f"(d[2]),"+f"(d[3]),"+f"(d[4]),"+f"(d[5]),"+f"(d[6]),"+f"(d[7]),"+f"(d[8]),"+f"(d[9]),"+f"(d[10]),"+f"(d[11]),"+f"(d[12]),"+f"(d[13]),"+f"(d[14]),"+f"(d[15]),"+f"(d[16]),"+f"(d[17]),"+f"(d[18]),"+f"(d[19]),"+f"(d[20]),"+f"(d[21]),"+f"(d[22]),"+f"(d[23]),"+f"(d[24]),"+f"(d[25]),"+f"(d[26]),"+f"(d[27]),"+f"(d[28]),"+f"(d[29]),"+f"(d[30]),"+f"(d[31]),"+f"(d[32]),"+f"(d[33]),"+f"(d[34]),"+f"(d[35]),"+f"(d[36]),"+f"(d[37]),"+f"(d[38]),"+f"(d[39]),"+f"(d[40]),"+f"(d[41]),"+f"(d[42]),"+f"(d[43]),"+f"(d[44]),"+f"(d[45]),"+f"(d[46]),"+f"(d[47]),"+f"(d[48]),"+f"(d[49]),"+f"(d[50]),"+f"(d[51]),"+f"(d[52]),"+f"(d[53]),"+f"(d[54]),"+f"(d[55]),"+f"(d[56]),"+f"(d[57]),"+f"(d[58]),"+f"(d[59]),"+f"(d[60]),"+f"(d[61]),"+f"(d[62]),"+f"(d[63])
    :"l"(da),"l"(db),"r"(sc));
}
__device__ __forceinline__ void wgmma_ss_n64_t1(float (&d)[32],uint64_t da,uint64_t db,int sc){
  asm volatile("{\n.reg .pred p;\nsetp.ne.b32 p,%34,0;\n"
    "wgmma.mma_async.sync.aligned.m64n64k16.f32.bf16.bf16 {%0,%1,%2,%3,%4,%5,%6,%7,%8,%9,%10,%11,%12,%13,%14,%15,%16,%17,%18,%19,%20,%21,%22,%23,%24,%25,%26,%27,%28,%29,%30,%31},%32,%33,p,1,1,0,1;\n}\n"
    :"+f"(d[0]),"+f"(d[1]),"+f"(d[2]),"+f"(d[3]),"+f"(d[4]),"+f"(d[5]),"+f"(d[6]),"+f"(d[7]),"+f"(d[8]),"+f"(d[9]),"+f"(d[10]),"+f"(d[11]),"+f"(d[12]),"+f"(d[13]),"+f"(d[14]),"+f"(d[15]),"+f"(d[16]),"+f"(d[17]),"+f"(d[18]),"+f"(d[19]),"+f"(d[20]),"+f"(d[21]),"+f"(d[22]),"+f"(d[23]),"+f"(d[24]),"+f"(d[25]),"+f"(d[26]),"+f"(d[27]),"+f"(d[28]),"+f"(d[29]),"+f"(d[30]),"+f"(d[31])
    :"l"(da),"l"(db),"r"(sc));
}

__device__ __forceinline__ float silu_bf(bf16 c) { const float x = __bfloat162float(c); return rbf(x / (1.f + __expf(-x))); }
__device__ __forceinline__ void fma8(float (&a)[8], float s, const uint4& v) {
  a[0] += s * blo(v.x); a[1] += s * bhi(v.x); a[2] += s * blo(v.y); a[3] += s * bhi(v.y);
  a[4] += s * blo(v.z); a[5] += s * bhi(v.z); a[6] += s * blo(v.w); a[7] += s * bhi(v.w);
}
__device__ __forceinline__ float red8(float (&a)[8], int lane) {
#pragma unroll
  for (int w = 4; w >= 1; w >>= 1) {
    const bool up = lane & (w * 4);
#pragma unroll
    for (int j = 0; j < w; j++) a[j] = (up ? a[j + w] : a[j]) + __shfl_xor_sync(~0u, up ? a[j] : a[j + w], w * 4);
  }
  return a[0];
}
__device__ __forceinline__ float mod_fin(float s, int n) { s = rbf(s); return ((n >> 9) == 1 || (n >> 9) == 4) ? rbf(1.f + s) : s; }
__device__ __forceinline__ void poll(uint2& a, uint2& b, float (&w)[16], const uint32_t* p, const uint32_t* q) {
  asm volatile("{\n.reg .pred p;\n.reg .b32 n,t,u;\nmov.u32 n,0;\nLW:\nld.relaxed.gpu.global.v2.u32 {%0,%1},[%20];\nld.relaxed.gpu.global.v2.u32 {%2,%3},[%20+64];\n"
               "ld.relaxed.gpu.global.v4.f32 {%4,%5,%6,%7},[%21];\nld.relaxed.gpu.global.v4.f32 {%8,%9,%10,%11},[%21+16];\n"
               "ld.relaxed.gpu.global.v4.f32 {%12,%13,%14,%15},[%21+8192];\nld.relaxed.gpu.global.v4.f32 {%16,%17,%18,%19},[%21+8208];\n"
               "lop3.b32 t,%0,%1,%2,0x80;\nlop3.b32 u,%3,%4,%5,0x80;\nlop3.b32 t,t,%6,%7,0x80;\nlop3.b32 u,u,%8,%9,0x80;\nlop3.b32 t,t,%10,%11,0x80;\n"
               "lop3.b32 u,u,%12,%13,0x80;\nlop3.b32 t,t,%14,%15,0x80;\nlop3.b32 u,u,%16,%17,0x80;\nlop3.b32 t,t,%18,%19,0x80;\nlop3.b32 t,t,u,1,0x80;\n"
               "setp.ne.u32 p,t,0;\n@p bra LD;\nadd.u32 n,n,1;\nsetp.lt.u32 p,n,1048576;\n@p bra LW;\nLD:\n}\n"
               : "=&r"(a.x), "=&r"(a.y), "=&r"(b.x), "=&r"(b.y), "=&f"(w[0]), "=&f"(w[1]), "=&f"(w[2]), "=&f"(w[3]), "=&f"(w[4]), "=&f"(w[5]), "=&f"(w[6]), "=&f"(w[7]),
                 "=&f"(w[8]), "=&f"(w[9]), "=&f"(w[10]), "=&f"(w[11]), "=&f"(w[12]), "=&f"(w[13]), "=&f"(w[14]), "=&f"(w[15]) : "l"(p), "l"(q) : "memory");
}

constexpr int LN_SMEM = 131072 + 4 * 24576 + 2816 + 256;
#define DLY 2
template <bool FFN>
__global__ void __cluster_dims__(2, 1, 1) __launch_bounds__(384, 1) k_lngemm(const __grid_constant__ CUtensorMap mX, const __grid_constant__ CUtensorMap mB0,
                                                   const __grid_constant__ CUtensorMap mB1, const bf16* __restrict__ cv, const bf16* __restrict__ wm, const bf16* __restrict__ xg, const bf16* wq) {
  extern __shared__ __align__(1024) uint8_t smem[];
  const uint32_t sA = smem_u32(smem), sB = sA + (FFN ? 81920 : 131072), sM = sA + 229376, bars = sM + 2816;
  const uint32_t bA = bars, bF = bars + 64, bE = bars + 112;
  constexpr int NB = FFN ? 6 : 4;
  const int tid = threadIdx.x, warp = tid >> 5, lane = tid & 31;
  const int pr = blockIdx.x & 1, rb = FFN ? (blockIdx.x >> 4) * 2 + pr : blockIdx.x >> 3, ct = FFN ? (blockIdx.x >> 1) & 7 : blockIdx.x & 7;
  constexpr int NST = FFN ? 16 : 8, KS = FFN ? 2 : 4, BOX = FFN ? 4096 : 8192;
  TS(FFN ? 4 : 1, 0);
  pdl_launch();
  float* red = (float*)(smem + (sM - sA));
  if (tid == 256) {
    for (int i = 0; i < 8; i++) mbar_init(bA + 8 * i, 1);
    for (int i = 0; i < NB; i++) { mbar_init(bF + 8 * i, 1); mbar_init(bE + 8 * i, FFN ? 16 : 8); }
    mbar_init(bars + 160, 1);
    fence_init();
  }
  __syncwarp();
  cluster_arrive();
  uint4 wv0, wv1, xv[4];
  bf16 cv0, cv1;
  if (!FFN && tid < 256) {
    const int r = (blockIdx.x & 3) * 128 + (tid >> 2);
    const uint4* wp = (const uint4*)(wm + r * 3072 + (blockIdx.x >> 2) * 32 + (tid & 3) * 8);
    wv0 = __ldg(wp); wv1 = __ldg(wp + 64 * 384);
    cv0 = cv[r]; cv1 = cv[r + 64];
#pragma unroll
    for (int i = 0; i < 4; i++) xv[i] = __ldg((const uint4*)(xg + (blockIdx.x * 16 + (tid >> 4)) * 512 + i * 128 + (tid & 15) * 8));
  }
  cluster_wait();
  if (warp >= 8) {
    asm volatile("setmaxnreg.dec.sync.aligned.u32 40;");
    if (tid == 256) {
      auto loadB = [&](int s) {
        const uint32_t d = sB + (s % NB) * 24576, b = bF + (s % NB) * 8;
        mbar_expect(b, 24576);
        for (int j = 0; j < 3; j++) {
          if (FFN) tma2d_mc(d + (pr * 3 + j) * BOX, pr ? &mB1 : &mB0, ct * 176 + j * 64, s * 32, b);
          else tma2d(d + j * BOX, &mB0, ct * 192 + j * 64, s * 64, b);
        }
      };
      for (int i = 0; i < 8; i++) mbar_expect(bA + 8 * i, 16384);
      if (!FFN) l2_prefetch((const char*)wq + blockIdx.x * 12288, 12288);
      for (int s = 0; s < NB; s++) {
        const int i = s * 2 + (ct & 1);
        if (!FFN && s == DLY) mbar_wait(bars + 160, 0);
        if (!FFN) tma2d_mc(sA + i * 16384, &mX, i * 64, rb * 128, bA + 8 * i);
        loadB(s);
      }
      if (FFN) {
        pdl_wait();
        for (int i = 0; i < 5; i++) bulk_load(sA + i * 16384, g_a + (rb * 64 + i * 8) * 1024, 16384, bA + 8 * i);
      }
      for (int s = NB; s < NST; s++) {
        mbar_wait(bE + (s % NB) * 8, (s / NB - 1) & 1); loadB(s);
        if (FFN && s <= 10 && !(s & 1)) bulk_load(sA + (s / 2 - 3) * 16384, g_a + (rb * 64 + (s / 2 + 2) * 8) * 1024, 16384, bA + 8 * (s / 2 + 2));
      }
    }
  } else {
  asm volatile("setmaxnreg.inc.sync.aligned.u32 232;");
  const int g = lane >> 2, t = lane & 3;
  const int lr = warp * 16 + (lane & 7) + ((lane >> 3) & 1) * 8;
  auto aaddr = [&](int ks) -> uint32_t {
    if (FFN) return sA + ((ks < 20 ? ks : ks - 20) * 2 + (lane >> 4)) * 2048 + lr * 16;
    return sA + (ks >> 2) * 16384 + lr * 128 + ((((ks & 3) * 2 + (lane >> 4)) ^ (lr & 7)) << 4);
  };
  const int row0 = rb * 128 + warp * 16 + g;
  float2 msh, msc;
  float4 p0, p1, uv;
  float rs0, rs1, nm0, nm1;
  if (!FFN) {
    {
      float a[8] = {0, 0, 0, 0, 0, 0, 0, 0};
      fma8(a, silu_bf(cv0), wv0); fma8(a, silu_bf(cv1), wv1);
      red[warp * 32 + t * 8 + g] = red8(a, lane);
      asm volatile("bar.sync 1,256;" ::: "memory");
      if (tid < 32) {
        float r = 0;
#pragma unroll
        for (int i = 0; i < 8; i++) r += red[i * 32 + tid];
        asm volatile("st.relaxed.gpu.global.u32 [%0],%1;" ::"l"(g_modv + ((blockIdx.x >> 2) * 32 + tid) * 4 + (blockIdx.x & 3)), "r"(__float_as_uint(r) | 1u) : "memory");
      }
      TS(0, 1);
    }
    {
      float v[32], s = 0, q = 0;
#pragma unroll
      for (int i = 0; i < 16; i++) { const uint32_t u = ((const uint32_t*)xv)[i]; v[2 * i] = blo(u); v[2 * i + 1] = bhi(u); s += v[2 * i] + v[2 * i + 1]; }
      s = qsum(s); s += __shfl_xor_sync(~0u, s, 4); s += __shfl_xor_sync(~0u, s, 8);
      const float m = s * (1.f / 512);
#pragma unroll
      for (int i = 0; i < 32; i++) q += (v[i] - m) * (v[i] - m);
      q = qsum(q); q += __shfl_xor_sync(~0u, q, 4); q += __shfl_xor_sync(~0u, q, 8);
      const float rs = rsqrtf(q * (1.f / 512) + 1e-5f);
      if ((tid & 15) == 0)
        asm volatile("st.relaxed.gpu.global.v2.u32 [%0],{%1,%2};" ::"l"(g_modv + 4096 + (blockIdx.x * 16 + (tid >> 4)) * 2), "r"(__float_as_uint(rs) | 1u), "r"(__float_as_uint(-m * rs) | 1u) : "memory");
    }
    uint2 q0, q1;
    float w[16];
    if (tid < 128) {
      uint32_t v; int n = 0;
      do asm volatile("ld.relaxed.gpu.global.u32 %0,[%1];" : "=r"(v) : "l"(g_modv + (tid >> 2) * 128 + (tid & 3)) : "memory"); while (!(v & 1) && ++n < 1048576);
    }
    asm volatile("bar.sync 1,256;" ::: "memory");
    poll(q0, q1, w, g_modv + 4096 + row0 * 2, g_modv + tid * 8);
    msh = make_float2(mod_fin(w[0] + w[1] + w[2] + w[3], 0), mod_fin(w[4] + w[5] + w[6] + w[7], 0));
    msc = make_float2(mod_fin(w[8] + w[9] + w[10] + w[11], 512), mod_fin(w[12] + w[13] + w[14] + w[15], 512));
    asm volatile("bar.sync 1,256;" ::: "memory");
    if (tid == 32) mbar_arrive(bars + 160);
    rs0 = __uint_as_float(q0.x); nm0 = __uint_as_float(q0.y); rs1 = __uint_as_float(q1.x); nm1 = __uint_as_float(q1.y);
  } else {
    pdl_wait();
    TS(4, 1);
    p0 = *(const float4*)(g_st + row0 * 8 + t * 2); p1 = *(const float4*)(g_st + (row0 + 8) * 8 + t * 2);
    if (tid < 176) uv = *(const float4*)(g_uv + (tid >= 88 ? 1408 - 176 : 0) + ct * 176 + tid * 2);
  }
  if (!FFN) {
    uint32_t* m = (uint32_t*)(smem + (sM - sA)) + (tid >> 3) * 16 + (tid & 3) * 4 + ((tid >> 2) & 1);
    m[0] = pack_rn(msc.x, msc.y); m[2] = pack_rn(msh.x, msh.y);
    asm volatile("bar.sync 1,256;" ::: "memory");
  }
  constexpr int NA = FFN ? 88 : 96;
  float acc0[NA], acc1[FFN ? 88 : 1];
  uint32_t a[2][KS][4];
  auto prep = [&](int ks, uint32_t(&o)[4]) {
    if ((ks & 3) == 0) mbar_wait(bA + 2 * ks, 0);
    if (FFN) { ldsm4(aaddr(ks), o); return; }
    uint32_t r[4]; ldsm4(aaddr(ks), r);
    const uint4 m = *(const uint4*)(smem + (sM - sA) + ks * 64 + t * 16);
#pragma unroll
    for (int i = 0; i < 4; i++) {
      const float rs = (i & 1) ? rs1 : rs0, nm = (i & 1) ? nm1 : nm0;
      const uint32_t n = pack_rn(fmaf(blo(r[i]), rs, nm), fmaf(bhi(r[i]), rs, nm));
      asm("fma.rn.bf16x2 %0,%1,%2,%3;" : "=r"(o[i]) : "r"(n), "r"(i < 2 ? m.x : m.y), "r"(i < 2 ? m.z : m.w));
    }
  };
  auto stage = [&](int s, uint32_t(&c)[KS][4], uint32_t(&n)[KS][4]) {
    mbar_wait(bF + (s % NB) * 8, (s / NB) & 1);
    const uint64_t db = mk_desc(sB + (s % NB) * 24576, BOX, 1024, 1);
    wg_fence();
#pragma unroll
    for (int k = 0; k < KS; k++) {
      if constexpr (FFN) {
        wgmma_rs_n176_t1(acc0, c[k][0], c[k][1], c[k][2], c[k][3], db + k * 128, s + k);
        wgmma_rs_n176_t1(acc1, c[k][0], c[k][1], c[k][2], c[k][3], db + k * 128 + 3 * BOX / 16, s + k);
      } else {
        wgmma_rs_n192_t1(acc0, c[k][0], c[k][1], c[k][2], c[k][3], db + k * 128, s + k);
      }
    }
    wg_commit();
    wg_wait<1>();
    if (s > 0 && s <= NST - NB) {
      if (!FFN) { if (lane == 0) mbar_arrive(bE + ((s - 1) % NB) * 8); }
      else if (lane < 2) asm volatile("{\n.reg .b32 r;\nmapa.shared::cluster.u32 r,%0,%1;\nmbarrier.arrive.relaxed.cluster.shared::cluster.b64 _,[r];\n}" ::"r"(bE + ((s - 1) % NB) * 8), "r"(lane) : "memory");
    }
    if (s < NST - 1) {
#pragma unroll
      for (int k = 0; k < KS; k++) prep((s + 1) * KS + k, n[k]);
    }
  };
#pragma unroll
  for (int k = 0; k < KS; k++) prep(k, a[0][k]);
  TS(FFN ? 4 : 1, 2);
#pragma unroll 1
  for (int s = 0; s < NST; s += 2) { stage(s, a[0], a[1]); stage(s + 1, a[1], a[0]); }
  if (FFN) {
    if (tid < 176) *(float4*)(smem + (sM - sA) + tid * 16) = uv;
    const float m0 = qsum(p0.x + p0.z) * 0.125f, m1 = qsum(p1.x + p1.z) * 0.125f;
    const float v0 = qsum(p0.y + p0.w + 64.f * ((p0.x - m0) * (p0.x - m0) + (p0.z - m0) * (p0.z - m0)));
    const float v1 = qsum(p1.y + p1.w + 64.f * ((p1.x - m1) * (p1.x - m1) + (p1.z - m1) * (p1.z - m1)));
    rs0 = rsqrtf(v0 * (1.f / 512) + 1e-5f); rs1 = rsqrtf(v1 * (1.f / 512) + 1e-5f);
    nm0 = -m0 * rs0; nm1 = -m1 * rs1;
    asm volatile("bar.sync 1,256;" ::: "memory");
  }
  wg_wait<0>();
  reg_fence(acc0);
  TS(FFN ? 4 : 1, 3);
  if constexpr (FFN) {
    reg_fence(acc1);
    uint32_t* o = (uint32_t*)g_h + ((rb * 172 + ct * 22) * 128 + warp * 16 + g) * 4 + t;
#pragma unroll
    for (int j = 0; j < 22; j++) {
      {
        const float4 u1 = *(const float4*)(smem + (sM - sA) + (j * 4 + t) * 16), u3 = *(const float4*)(smem + (sM - sA) + (88 + j * 4 + t) * 16);
        float h[4], d[4];
#pragma unroll
        for (int i = 0; i < 4; i++) {
          const float rs = i < 2 ? rs0 : rs1, nm = i < 2 ? nm0 : nm1;
          const float x = fmaf(rs, acc0[4 * j + i], (i & 1) ? fmaf(nm, u1.z, u1.w) : fmaf(nm, u1.x, u1.y));
          const float y = fmaf(rs, acc1[4 * j + i], (i & 1) ? fmaf(nm, u3.z, u3.w) : fmaf(nm, u3.x, u3.y));
          d[i] = 1.f + ex2(fminf(-1.4426950408889634f * x, 30.f)); h[i] = x * y;
        }
        const float d01 = d[0] * d[1], d23 = d[2] * d[3];
        float r; asm("rcp.approx.ftz.f32 %0,%1;" : "=f"(r) : "f"(d01 * d23));
        const float r01 = r * d23, r23 = r * d01;
        h[0] *= r01 * d[1]; h[1] *= r01 * d[0]; h[2] *= r23 * d[3]; h[3] *= r23 * d[2];
        if (j < 18 || ct < 7) { o[j * 512] = pack_rn(h[0], h[1]); o[j * 512 + 32] = pack_rn(h[2], h[3]); }
      }
    }
  } else {
    uint32_t* o = (uint32_t*)g_qkv + (ct * 24 * 2048 + row0) * 4 + t;
#pragma unroll
    for (int j = 0; j < 24; j += 2) {
      const int G = ct * 24 + j;
      const float sc = G < 64 ? 0.25f * 1.4426950408889634f : 1.f;
      uint32_t p[4];
#pragma unroll
      for (int i = 0; i < 4; i++) p[i] = pack_rn(acc0[4 * j + 2 * i] * sc, acc0[4 * j + 2 * i + 1] * sc);
      o[j * 8192] = p[0]; o[j * 8192 + 32] = p[1]; o[(j + 1) * 8192] = p[2]; o[(j + 1) * 8192 + 32] = p[3];
      if (G >= 64 && G < 128) {
        float n0 = blo(p[0]) * blo(p[0]) + bhi(p[0]) * bhi(p[0]) + blo(p[2]) * blo(p[2]) + bhi(p[2]) * bhi(p[2]);
        float n1 = blo(p[1]) * blo(p[1]) + bhi(p[1]) * bhi(p[1]) + blo(p[3]) * blo(p[3]) + bhi(p[3]) * bhi(p[3]);
        n0 = qsum(n0); n1 = qsum(n1);
        const uint32_t mx = __reduce_max_sync(~0u, max(__float_as_uint(n0), __float_as_uint(n1)));
        if (lane == 0) g_kmax[((G - 64) >> 1) * 128 + rb * 8 + warp] = __uint_as_float(mx);
      }
    }
  }
  TS(FFN ? 4 : 1, 4);
}
}

#define SMASK 0xCCCCu
#define BRK 0
#define PACK 1
constexpr int AT_SMEM = 5 * 32768 + 256;
__device__ __forceinline__ uint32_t exp2_pair_fma(float s0, float s1, float c, uint32_t ka, uint32_t kz) {
  uint32_t r;
  asm volatile("{\n.reg .b32 y0,y1,e,u,t;\n"
      "fma.rn.sat.f32 y0,%1,0f00000080,%3;\nfma.rn.sat.f32 y1,%2,0f00000080,%3;\n"
      "mad.lo.u32 e,y1,65536,y0;\n"
      "and.b32 u,e,0x007F007F;\n"
      "fma.rn.f16x2 u,u,%4,%5;\nfma.rn.f16x2 t,u,u,%6;\nfma.rn.f16x2 t,t,u,%7;\n"
      "lop3.b32 %0,t,0x007F007F,e,0xE2;\n}\n"
      : "=r"(r) : "f"(s0), "f"(s1), "f"(c), "r"(ka), "r"(0x36B236B2u), "r"(0x3C733C73u), "r"(0x47764776u), "r"(kz));
  return r;
}
__device__ __forceinline__ void attn_pass(float (&oa)[12], float (&ob)[12], const uint32_t (&q)[4], float m0, float m1, uint32_t sK, uint32_t bars, bool first, uint32_t kz) {
  uint64_t dk = mk_desc(sK, 32768, 128, 0), dv = mk_desc(sK + 65536, 128, 32768, 0);
  const float c0 = (127.f - m0) * __uint_as_float(0x80u), c1 = (127.f - m1) * __uint_as_float(0x80u);
  uint32_t ka;
  asm volatile("mov.b32 %0,0x7ACE7ACE;" : "=r"(ka));
  constexpr int NK = 64, NS = 32, NP = 16;
  auto qk = [&](float (&s)[NS], int i) { wgmma_rs_n64_t0(s, q[0], q[1], q[2], q[3], dk + i * NK, 0); };
  auto softmax = [&](float (&s)[NS], uint32_t (&p)[NP], uint32_t mask) {
    reg_fence(s);
    float e0, e1;
    int pend = -1;
#pragma unroll
    for (int t = 0; t < NP; t++) {
      const int j = (t & 3) * 4 + (t >> 2);
      if ((mask >> (t & 3)) & 1) {
        p[j] = exp2_pair_fma(s[2 * j], s[2 * j + 1], (j & 1) ? c1 : c0, ka, kz);
      } else {
        float f0, f1;
        asm volatile("ex2.approx.ftz.f32 %0,%2;\nex2.approx.ftz.f32 %1,%3;" : "=&f"(f0), "=f"(f1) : "f"(s[2 * j]), "f"(s[2 * j + 1]));
        if (pend >= 0) asm volatile("cvt.rn.bf16x2.f32 %0,%1,%2;" : "=r"(p[pend]) : "f"(e1), "f"(e0));
        e0 = f0; e1 = f1; pend = j;
      }
    }
    if (pend >= 0) asm volatile("cvt.rn.bf16x2.f32 %0,%1,%2;" : "=r"(p[pend]) : "f"(e1), "f"(e0));
#pragma unroll
    for (int j = 0; j < NP; j++) asm volatile("" : "+r"(p[j])::"memory");
  };
  auto pv = [&](uint32_t (&p)[NP], int i, uint32_t mask) {
#pragma unroll
    for (int k = 0; k < 4; k++) wgmma_rs_n24_t1(((mask >> k) & 1) ? ob : oa, p[4 * k], p[4 * k + 1], p[4 * k + 2], p[4 * k + 3], dv + i * NK + k * 16, 1);
  };
  constexpr uint32_t M0 = SMASK & 15, M1 = (SMASK >> 4) & 15, M2 = (SMASK >> 8) & 15, M3 = SMASK >> 12;
  zero(oa); zero(ob);
  mbar_wait(bars, 0);
  if (first) TS(2, 2);
  float s[NS];
  zero(s);
  uint32_t p0[NP], p1[NP];
  auto step = [&](int i, uint32_t (&pa)[NP], uint32_t ma, uint32_t (&pb)[NP], uint32_t mb) {
    wg_fence(); qk(s, i + 1); wg_commit(); pv(pa, i, ma); wg_commit(); wg_wait<1>(); softmax(s, pb, mb); wg_wait<0>();
  };
  wg_fence(); qk(s, 0); wg_commit(); wg_wait<0>(); softmax(s, p0, M0);
#pragma unroll 1
  for (uint32_t b = bars + 8; b < bars + 64; b += 8) {
    step(0, p0, M0, p1, M1); step(1, p1, M1, p0, M2); step(2, p0, M2, p1, M3);
    mbar_wait(b, 0);
    step(3, p1, M3, p0, M0);
    dk += 4 * NK; dv += 4 * NK;
  }
  step(0, p0, M0, p1, M1); step(1, p1, M1, p0, M2); step(2, p0, M2, p1, M3);
  wg_fence(); pv(p1, 3, M3); wg_commit();
  wg_wait<0>();
  reg_fence(oa); reg_fence(ob);
}
__device__ __forceinline__ void mma16816(float (&d)[4], const uint32_t (&a)[4], uint32_t b0, uint32_t b1) {
  asm("mma.sync.aligned.m16n8k16.row.col.f32.bf16.bf16.f32 {%0,%1,%2,%3},{%4,%5,%6,%7},{%8,%9},{%0,%1,%2,%3};"
      : "+f"(d[0]), "+f"(d[1]), "+f"(d[2]), "+f"(d[3]) : "r"(a[0]), "r"(a[1]), "r"(a[2]), "r"(a[3]), "r"(b0), "r"(b1));
}
__device__ __forceinline__ void attn_safe(float (&o)[12], const uint32_t (&q)[4], uint32_t sK) {
  const int lane = threadIdx.x & 31;
  const uint32_t ka = sK + (lane >> 4) * 32768 + (lane & 15) * 16;
  float m0 = -INFINITY, m1 = -INFINITY;
#pragma unroll 2
  for (int i = 0; i < 128; i++) {
    uint32_t k[4]; ldsm4(ka + i * 256, k);
    float s0[4] = {0, 0, 0, 0}, s1[4] = {0, 0, 0, 0};
    mma16816(s0, q, k[0], k[2]); mma16816(s1, q, k[1], k[3]);
    m0 = fmaxf(fmaxf(m0, fmaxf(s0[0], s0[1])), fmaxf(s1[0], s1[1])); m1 = fmaxf(fmaxf(m1, fmaxf(s0[2], s0[3])), fmaxf(s1[2], s1[3]));
  }
  m0 = fmaxf(m0, __shfl_xor_sync(~0u, m0, 1)); m0 = fmaxf(m0, __shfl_xor_sync(~0u, m0, 2));
  m1 = fmaxf(m1, __shfl_xor_sync(~0u, m1, 1)); m1 = fmaxf(m1, __shfl_xor_sync(~0u, m1, 2));
  float o0[4] = {0, 0, 0, 0}, o1[4] = {0, 0, 0, 0}, o2[4] = {0, 0, 0, 0};
#pragma unroll 2
  for (int i = 0; i < 128; i++) {
    uint32_t k[4], v[4]; ldsm4(ka + i * 256, k);
    asm volatile("ldmatrix.sync.aligned.m8n8.x4.trans.shared.b16 {%0,%1,%2,%3},[%4];" : "=r"(v[0]), "=r"(v[1]), "=r"(v[2]), "=r"(v[3]) : "r"(ka + 65536 + i * 256) : "memory");
    float s0[4] = {0, 0, 0, 0}, s1[4] = {0, 0, 0, 0};
    mma16816(s0, q, k[0], k[2]); mma16816(s1, q, k[1], k[3]);
    const uint32_t p[4] = {pack_rn(ex2(s0[0] - m0), ex2(s0[1] - m0)), pack_rn(ex2(s0[2] - m1), ex2(s0[3] - m1)),
                           pack_rn(ex2(s1[0] - m0), ex2(s1[1] - m0)), pack_rn(ex2(s1[2] - m1), ex2(s1[3] - m1))};
    mma16816(o0, p, v[0], v[1]); mma16816(o1, p, v[2], v[3]); mma16816(o2, p, 0x3F803F80u, 0x3F803F80u);
  }
#pragma unroll
  for (int i = 0; i < 4; i++) { o[i] = o0[i]; o[4 + i] = o1[i]; o[8 + i] = o2[i]; }
}
__global__ void __cluster_dims__(2, 1, 1) __launch_bounds__(512, 1) k_attn(const bf16* wo, const bf16* w1, const bf16* w3, const bf16* w2, const bf16* __restrict__ cv, const bf16* __restrict__ wm, uint32_t kz) {
  extern __shared__ __align__(1024) uint8_t smem[];
  const uint32_t sK = smem_u32(smem), bars = sK + 5 * 32768;
  const int tid = threadIdx.x, warp = tid >> 5, lane = tid & 31, g = lane >> 2, t = lane & 3;
  pdl_launch();
  if (blockIdx.x < 4) {
    float* cs = (float*)smem;
    cs[tid] = silu_bf(cv[tid]);
    cluster_sync();
    const int b = blockIdx.x;
    float *mv = cs + 512, *rd = cs + 1536;
    auto put8 = [&](float* d, float (&a)[8]) { ((float4*)d)[0] = make_float4(a[0], a[1], a[2], a[3]); ((float4*)d)[1] = make_float4(a[4], a[5], a[6], a[7]); };
    for (int ph = 0; ph < 2; ph++) {
      const int nc = 512 >> ph, n0 = ph ? (b >> 1) * 1536 + 1024 + (b & 1) * 256 : 1536 + (b & 1) * 512, nr = 64 >> ph, r0 = tid / nr * nr;
      float a[8] = {0, 0, 0, 0, 0, 0, 0, 0};
#pragma unroll 16
      for (int r = r0; r < r0 + nr; r++) fma8(a, cs[r], __ldg((const uint4*)(wm + r * 3072 + n0 + (tid & (nr - 1)) * 8)));
      put8(rd + tid * 8, a);
      __syncthreads();
      if (tid < nc) {
        float s = 0;
        for (int i = tid; i < 4096; i += nc) s += rd[i];
        s = mod_fin(s, n0 + tid);
        if (ph || b < 2) g_mod[n0 + tid] = s;
        if (!ph) {
          mv[(b & 1) * 512 + tid] = s;
          asm volatile("{\n.reg .b32 r;\nmapa.shared::cluster.u32 r,%0,%1;\nst.shared::cluster.f32 [r],%2;\n}" ::"r"(smem_u32(mv + (b & 1) * 512 + tid)), "r"((b & 1) ^ 1), "f"(s) : "memory");
        }
      }
      cluster_sync();
    }
    if (tid < 430) {
      const bf16* w = (b >> 1 ? w3 : w1) + (b & 1) * 688 + tid % 86 * 8;
      float u[8] = {0, 0, 0, 0, 0, 0, 0, 0}, v[8] = {0, 0, 0, 0, 0, 0, 0, 0};
#pragma unroll 13
      for (int r = tid / 86; r < 512; r += 5) { const uint4 x = __ldg((const uint4*)(w + r * 1376)); fma8(u, mv[512 + r], x); fma8(v, mv[r], x); }
      put8(rd + tid * 8, u); put8(rd + 3440 + tid * 8, v);
    }
    __syncthreads();
    for (int n = tid; n < 688; n += 512) {
      float u = 0, v = 0;
      for (int i = n; i < 3440; i += 688) { u += rd[i]; v += rd[3440 + i]; }
      g_uv[(b >> 1) * 1408 + (b & 1) * 688 + n] = make_float2(u, v);
    }
    TS(0, 7);
    return;
  }
  const int bid = blockIdx.x - 4, h = bid >> 2, qb = bid & 3;
  TS(2, 0);
  if (tid == 0) { for (int i = 0; i < 8; i++) { mbar_init(bars + 8 * i, 1); mbar_expect(bars + 8 * i, 16384); } fence_init(); }
#pragma unroll
  for (int i = 0; i < 4; i++) *(uint4*)(smem + 131072 + i * 8192 + tid * 16) = make_uint4(0x3F803F80u, 0x3F803F80u, 0x3F803F80u, 0x3F803F80u);
  fence_async();
  cluster_sync();
  pdl_wait();
  TS(2, 1);
  if (tid >= 448) g_modv[bid * 64 + tid - 448] = 0;
  const uint4 km4 = *(const uint4*)(g_kmax + h * 128 + lane * 4);
  const uint32_t* qp = (const uint32_t*)g_qkv + (h * 2 * 2048 + qb * 512 + warp * 16 + g) * 4 + t;
  uint32_t q[4] = {qp[0], qp[32], qp[8192], qp[8192 + 32]};
  auto ldkv = [&]() {
    const int c = warp >> 1, pl = (qb & 1) + (warp & 1) * 2;
    bulk_load_mc(sK + pl * 32768 + c * 4096, g_qkv + ((64 + (pl >> 1) * 64 + h * 2 + (pl & 1)) * 2048 + c * 256) * 8, 4096, bars + 8 * c);
  };
  if (lane == 0 && warp < 4) ldkv();
  const uint32_t qn[4] = {qp[1024], qp[1024 + 32], qp[1024 + 8192], qp[1024 + 8192 + 32]};
  const float kmax = __uint_as_float(__reduce_max_sync(~0u, max(max(km4.x, km4.y), max(km4.z, km4.w))));
  if (lane == 0 && warp >= 4 && kmax != -1.f) ldkv();
#pragma unroll 1
  for (int tile = 0; tile < 2; tile++) {
    const int row = qb * 512 + tile * 256 + warp * 16 + g;
    const float n0 = qsum(blo(q[0]) * blo(q[0]) + bhi(q[0]) * bhi(q[0]) + blo(q[2]) * blo(q[2]) + bhi(q[2]) * bhi(q[2]));
    const float n1 = qsum(blo(q[1]) * blo(q[1]) + bhi(q[1]) * bhi(q[1]) + blo(q[3]) * blo(q[3]) + bhi(q[3]) * bhi(q[3]));
    const float b0 = sqrtf(n0 * kmax) * 1.001f, b1 = sqrtf(n1 * kmax) * 1.001f;
    const float m0 = fmaxf(ceilf(b0 - 100.f), 0.f), m1 = fmaxf(ceilf(b1 - 100.f), 0.f);
    float o[12], ob[12];
    attn_pass(o, ob, q, m0, m1, sK, bars, tile == 0, kz);
    const float f0 = ex2(-m0), f1 = ex2(-m1);
#pragma unroll
    for (int i = 0; i < 12; i++) o[i] = fmaf(o[i], (i & 2) ? f1 : f0, ob[i]);
    bool ok = b0 < 220.f && b1 < 220.f && o[8] >= 0x1p-90f && o[10] >= 0x1p-90f;
#pragma unroll
    for (int i = 0; i < 12; i++) ok = ok && fabsf(o[i]) < INFINITY;
    if (!__all_sync(~0u, ok)) attn_safe(o, q, sK);
    const float r0 = 1.f / o[8], r1 = 1.f / o[10];
    uint32_t* op = (uint32_t*)g_o + (((row >> 7) * 64 + h * 2) * 128 + (row & 127)) * 4 + t;
    op[0] = pack_rn(o[0] * r0, o[1] * r0); op[32] = pack_rn(o[2] * r1, o[3] * r1);
    op[512] = pack_rn(o[4] * r0, o[5] * r0); op[512 + 32] = pack_rn(o[6] * r1, o[7] * r1);
    if (tile == 0 && tid == 32) {
      l2_prefetch((const char*)wo + bid * 4096, 4096);
      l2_prefetch((const char*)w1 + bid * 11008, 11008);
      l2_prefetch((const char*)w3 + bid * 11008, 11008);
      l2_prefetch((const char*)w2 + bid * 11008, 11008);
    }
#pragma unroll
    for (int i = 0; i < 4; i++) q[i] = qn[i];
    TS(2, 3 + tile);
  }
}

constexpr int WO_SMEM = 131072 + 65536 + 256;
__global__ void __cluster_dims__(2, 1, 1) __launch_bounds__(256, 1) k_wo(const __grid_constant__ CUtensorMap mW, const bf16* __restrict__ x) {
  extern __shared__ __align__(1024) uint8_t smem[];
  const uint32_t sA = smem_u32(smem), sB = sA + 131072, bars = sB + 65536;
  const int tid = threadIdx.x, warp = tid >> 5, lane = tid & 31, g = lane >> 2, t = lane & 3;
  const int rb = blockIdx.x >> 3, ct = blockIdx.x & 7;
  TS(3, 0);
  pdl_launch();
  if (tid == 0) {
    for (int i = 0; i < 8; i++) mbar_init(bars + 8 * i, 1);
    fence_init();
    for (int i = 0; i < 8; i++) { mbar_expect(bars + 8 * i, 24576); tma2d(sB + i * 8192, &mW, ct * 64, i * 64, bars + 8 * i); }
  }
  __syncwarp();
  cluster_arrive();
  const int lrow = warp * 16 + g;
  uint32_t xr[16];
  const uint32_t* xp = (const uint32_t*)(x + (rb * 128 + lrow) * 512 + ct * 64) + t;
#pragma unroll
  for (int j = 0; j < 8; j++) { xr[2 * j] = __ldg(xp + j * 4); xr[2 * j + 1] = __ldg(xp + j * 4 + 8 * 256); }
  cluster_wait();
  pdl_wait();
  if (tid == 0) {
    for (int i = ct & 1; i < 8; i += 2) bulk_load_mc(sA + i * 16384, g_o + (rb * 64 + i * 8) * 1024, 16384, bars + 8 * i);
  }
  TS(3, 1);
  float2 ga[8];
  uint32_t sc[8];
#pragma unroll
  for (int j = 0; j < 8; j++) {
    ga[j] = *(const float2*)(g_mod + 1024 + ct * 64 + j * 8 + t * 2);
    const float2 v = *(const float2*)(g_mod + 2048 + ct * 64 + j * 8 + t * 2);
    sc[j] = pack_rn(v.x, v.y);
  }
  float acc[32];
  const uint64_t da = mk_desc(sA + (warp >> 2) * 1024, 2048, 128, 0), db = mk_desc(sB, 8192, 1024, 1);
#pragma unroll
  for (int c = 0; c < 8; c++) {
    mbar_wait(bars + 8 * c, 0);
    if (c == 0) TS(3, 2);
    wg_fence();
#pragma unroll
    for (int k = 0; k < 4; k++) wgmma_ss_n64_t1(acc, da + (c * 4 + k) * 256, db + (c * 4 + k) * 128, c + k);
    wg_commit();
  }
  wg_wait<0>();
  reg_fence(acc);
  TS(3, 3);
  uint32_t* o = (uint32_t*)g_x1 + ((rb * 64 + ct * 8) * 128 + lrow) * 4 + t;
  uint32_t* oa = (uint32_t*)g_a + ((rb * 64 + ct * 8) * 128 + lrow) * 4 + t;
  float s0 = 0, s1 = 0;
#pragma unroll
  for (int j = 0; j < 8; j++) {
    xr[2 * j] = pack_rn(fmaf(ga[j].x, acc[4 * j], blo(xr[2 * j])), fmaf(ga[j].y, acc[4 * j + 1], bhi(xr[2 * j])));
    xr[2 * j + 1] = pack_rn(fmaf(ga[j].x, acc[4 * j + 2], blo(xr[2 * j + 1])), fmaf(ga[j].y, acc[4 * j + 3], bhi(xr[2 * j + 1])));
    uint32_t a0, a1;
    asm("mul.rn.bf16x2 %0,%1,%2;" : "=r"(a0) : "r"(xr[2 * j]), "r"(sc[j]));
    asm("mul.rn.bf16x2 %0,%1,%2;" : "=r"(a1) : "r"(xr[2 * j + 1]), "r"(sc[j]));
    oa[j * 512] = a0; oa[j * 512 + 32] = a1;
    o[j * 512] = xr[2 * j]; o[j * 512 + 32] = xr[2 * j + 1];
    s0 += blo(xr[2 * j]) + bhi(xr[2 * j]); s1 += blo(xr[2 * j + 1]) + bhi(xr[2 * j + 1]);
  }
  const float m0 = qsum(s0) * (1.f / 64), m1 = qsum(s1) * (1.f / 64);
  float v0 = 0, v1 = 0;
#pragma unroll
  for (int j = 0; j < 8; j++) {
    float d;
    d = blo(xr[2 * j]) - m0; v0 += d * d; d = bhi(xr[2 * j]) - m0; v0 += d * d;
    d = blo(xr[2 * j + 1]) - m1; v1 += d * d; d = bhi(xr[2 * j + 1]) - m1; v1 += d * d;
  }
  v0 = qsum(v0); v1 = qsum(v1);
  if (t == 0) g_st[(rb * 128 + lrow) * 8 + ct] = make_float2(m0, v0);
  if (t == 1) g_st[(rb * 128 + lrow + 8) * 8 + ct] = make_float2(m1, v1);
  TS(3, 4);
}

constexpr int W2_SMEM = 6 * 32768 + 32768 + 256;
__global__ void __cluster_dims__(2, 1, 1) __launch_bounds__(288, 1) k_w2(const __grid_constant__ CUtensorMap mW, bf16* __restrict__ out) {
  extern __shared__ __align__(1024) uint8_t smem[];
  const uint32_t sR = smem_u32(smem), sX = sR + 6 * 32768, bF = sX + 32768, bE = bF + 48, bX = bF + 96;
  const int tid = threadIdx.x, warp = tid >> 5, lane = tid & 31, g = lane >> 2, t = lane & 3;
  const int kh = blockIdx.x & 1, ct = (blockIdx.x >> 1) & 3, rb = blockIdx.x >> 3;
  TS(5, 0);
  pdl_launch();
  if (tid == 256) {
    for (int i = 0; i < 6; i++) { mbar_init(bF + 8 * i, 1); mbar_init(bE + 8 * i, 8); }
    for (int i = 0; i < 8; i++) { mbar_init(bX + 8 * i, 1); mbar_expect(bX + 8 * i, 4096); }
    fence_init();
  }
  __syncthreads();
  asm volatile("barrier.cluster.arrive.relaxed.aligned;" ::: "memory");
  if (warp == 8) {
    if (lane == 0) {
      auto abytes = [&](int s) { return (kh == 1 && s == 10) ? 8192 : 16384; };
      auto loadB = [&](int s) {
        const int st = s % 6;
        mbar_expect(bF + 8 * st, 16384 + abytes(s));
        for (int j = 0; j < 2; j++) tma2d(sR + st * 32768 + 16384 + j * 8192, &mW, ct * 128 + j * 64, kh * 704 + s * 64, bF + 8 * st);
      };
      auto loadA = [&](int s) { bulk_load(sR + (s % 6) * 32768, g_h + (rb * 172 + kh * 88 + s * 8) * 1024, abytes(s), bF + 8 * (s % 6)); };
      for (int s = 0; s < 6; s++) loadB(s);
      pdl_wait();
      for (int s = 0; s < 6; s++) loadA(s);
      for (int s = 6; s < 11; s++) { mbar_wait(bE + 8 * (s - 6), 0); loadB(s); loadA(s); }
    }
    __syncwarp();
    cluster_wait();
    return;
  }
  pdl_wait();
  TS(5, 1);
  const int lrow = warp * 16 + g;
  uint32_t xr[16];
  float2 gb[8];
  const uint32_t* xp = (const uint32_t*)g_x1 + ((rb * 64 + ct * 16 + kh * 8) * 128 + lrow) * 4 + t;
#pragma unroll
  for (int j = 0; j < 8; j++) {
    xr[2 * j] = xp[j * 512]; xr[2 * j + 1] = xp[j * 512 + 32];
    gb[j] = *(const float2*)(g_mod + 2560 + ct * 128 + kh * 64 + j * 8 + t * 2);
  }
  float acc[64];
#pragma unroll 1
  for (int s = 0; s < 11; s++) {
    const int st = s % 6;
    mbar_wait(bF + 8 * st, s >= 6);
    const uint64_t da = mk_desc(sR + st * 32768 + (warp >> 2) * 1024, 2048, 128, 0), db = mk_desc(sR + st * 32768 + 16384, 8192, 1024, 1);
    if (s == 0) TS(5, 2);
    wg_fence();
    wgmma_ss_n128_t1(acc, da, db, s);
    wgmma_ss_n128_t1(acc, da + 256, db + 128, 1);
    wgmma_ss_n128_t1(acc, da + 512, db + 256, 1);
    wgmma_ss_n128_t1(acc, da + 768, db + 384, 1);
    wg_commit();
    wg_wait<1>();
    if (s > 0 && s < 6 && lane == 0) mbar_arrive(bE + 8 * (s - 1));
  }
  wg_wait<0>();
  reg_fence(acc);
  TS(5, 3);
  asm volatile("barrier.cluster.wait.aligned;" ::: "memory");
  uint32_t rem, rbar;
  asm("mapa.shared::cluster.u32 %0,%1,%2;" : "=r"(rbar) : "r"(bX + warp * 8), "r"(kh ^ 1));
  asm("mapa.shared::cluster.u32 %0,%1,%2;" : "=r"(rem) : "r"(sX + warp * 4096 + lane * 16), "r"(kh ^ 1));
#pragma unroll
  for (int j = 0; j < 8; j++) {
    float v[4];
#pragma unroll
    for (int i = 0; i < 4; i++) { v[i] = kh ? acc[4 * j + i] : acc[32 + 4 * j + i]; acc[4 * j + i] = kh ? acc[32 + 4 * j + i] : acc[4 * j + i]; }
    asm volatile("st.async.weak.shared::cluster.mbarrier::complete_tx::bytes.v4.f32 [%0],{%1,%2,%3,%4},[%5];" ::"r"(rem + j * 512), "f"(v[0]), "f"(v[1]), "f"(v[2]), "f"(v[3]), "r"(rbar) : "memory");
  }
  mbar_wait(bX + warp * 8, 0);
  TS(5, 5);
  const uint32_t sw = sX + warp * 4096;
#pragma unroll
  for (int j = 0; j < 8; j++) {
    const float4 p = *(const float4*)(smem + 6 * 32768 + warp * 4096 + j * 512 + lane * 16);
    xr[2 * j] = pack_rn(fmaf(gb[j].x, acc[4 * j] + p.x, blo(xr[2 * j])), fmaf(gb[j].y, acc[4 * j + 1] + p.y, bhi(xr[2 * j])));
    xr[2 * j + 1] = pack_rn(fmaf(gb[j].x, acc[4 * j + 2] + p.z, blo(xr[2 * j + 1])), fmaf(gb[j].y, acc[4 * j + 3] + p.w, bhi(xr[2 * j + 1])));
  }
  __syncwarp();
#pragma unroll
  for (int j = 1; j < 8; j += 2) {
    asm volatile("stmatrix.sync.aligned.m8n8.x4.shared.b16 [%0],{%1,%2,%3,%4};" ::"r"(sw + (lane & 15) * 128 + (((j - 1 + (lane >> 4)) ^ (lane & 7)) << 4)),
                            "r"(xr[2 * j - 2]), "r"(xr[2 * j - 1]), "r"(xr[2 * j]), "r"(xr[2 * j + 1]) : "memory");
  }
  __syncwarp();
#pragma unroll
  for (int i = 0; i < 4; i++) {
    const int r = i * 4 + (lane >> 3);
    *(uint4*)(out + (rb * 128 + warp * 16 + r) * 512 + ct * 128 + kh * 64 + (lane & 7) * 8) = *(const uint4*)(smem + 6 * 32768 + warp * 4096 + r * 128 + (((lane ^ r) & 7) << 4));
  }
  TS(5, 4);
}

typedef CUresult (*EncFn)(CUtensorMap*, CUtensorMapDataType, cuuint32_t, void*, const cuuint64_t*, const cuuint64_t*, const cuuint32_t*,
                          const cuuint32_t*, CUtensorMapInterleave, CUtensorMapSwizzle, CUtensorMapL2promotion, CUtensorMapFloatOOBfill);
static void mk_map(EncFn f, CUtensorMap* m, const void* p, int rows, int cols, int box_rows) {
  cuuint64_t dim[2] = {(cuuint64_t)cols, (cuuint64_t)rows}, str[1] = {(cuuint64_t)cols * 2};
  cuuint32_t box[2] = {64, (cuuint32_t)box_rows}, es[2] = {1, 1};
  f(m, CU_TENSOR_MAP_DATA_TYPE_BFLOAT16, 2, (void*)p, dim, str, box, es, CU_TENSOR_MAP_INTERLEAVE_NONE, CU_TENSOR_MAP_SWIZZLE_128B,
    CU_TENSOR_MAP_L2_PROMOTION_L2_128B, CU_TENSOR_MAP_FLOAT_OOB_FILL_NONE);
}
template <typename... KA, typename... A>
static void launch(void (*k)(KA...), int grid, int block, int smem, bool pdl, A... args) {
  cudaLaunchConfig_t cfg = {};
  cfg.gridDim = dim3(grid); cfg.blockDim = dim3(block); cfg.dynamicSmemBytes = smem; cfg.stream = cudaStreamPerThread;
  cudaLaunchAttribute at[1];
  at[0].id = cudaLaunchAttributeProgrammaticStreamSerialization; at[0].val.programmaticStreamSerializationAllowed = 1;
  cfg.attrs = at; cfg.numAttrs = pdl ? 1 : 0;
  cudaLaunchKernelEx(&cfg, k, args...);
}
extern "C" void kernel_launch(void* const* d_in, const int* in_sizes, int n_in, void* d_out, int out_size) {
  const bf16 *x = (const bf16*)d_in[0], *wqkv = (const bf16*)d_in[1], *wo = (const bf16*)d_in[2], *w1 = (const bf16*)d_in[4],
             *w3 = (const bf16*)d_in[5], *w2 = (const bf16*)d_in[6], *c = (const bf16*)d_in[7], *wmod = (const bf16*)d_in[8];
  void* fp = nullptr;
  cudaDriverEntryPointQueryResult qr;
  cudaGetDriverEntryPoint("cuTensorMapEncodeTiled", &fp, cudaEnableDefault, &qr);
  EncFn f = (EncFn)fp;
  CUtensorMap mX, mQ, mO, m1, m3, m2;
  mk_map(f, &mX, x, S_, D_, 128); mk_map(f, &mQ, wqkv, D_, 3 * D_, 64); mk_map(f, &mO, wo, D_, D_, 64);
  mk_map(f, &m1, w1, D_, F_, 32); mk_map(f, &m3, w3, D_, F_, 32); mk_map(f, &m2, w2, F_, D_, 64);
  cudaFuncSetAttribute(k_lngemm<false>, cudaFuncAttributeMaxDynamicSharedMemorySize, LN_SMEM);
  cudaFuncSetAttribute(k_lngemm<true>, cudaFuncAttributeMaxDynamicSharedMemorySize, LN_SMEM);
  cudaFuncSetAttribute(k_attn, cudaFuncAttributeMaxDynamicSharedMemorySize, AT_SMEM);
  cudaFuncSetAttribute(k_wo, cudaFuncAttributeMaxDynamicSharedMemorySize, WO_SMEM);
  cudaFuncSetAttribute(k_w2, cudaFuncAttributeMaxDynamicSharedMemorySize, W2_SMEM);
  launch(k_lngemm<false>, 128, 384, LN_SMEM, false, mX, mQ, mQ, c, wmod, x, wqkv);
  launch(k_attn, 132, 512, AT_SMEM, true, wo, w1, w3, w2, c, wmod, 0u);
  launch(k_wo, 128, 256, WO_SMEM, true, mO, x);
  launch(k_lngemm<true>, 128, 384, LN_SMEM, true, mX, m1, m3, c, wmod, x, wqkv);
  launch(k_w2, 128, 288, W2_SMEM, true, m2, (bf16*)d_out);
}
```

```cpp
#include <cuda_runtime.h>
#include <cuda_bf16.h>
#include <cuda.h>
#include <stdint.h>
typedef __nv_bfloat16 bf16;
constexpr int S_ = 2048, D_ = 512, F_ = 1376;
__device__ __align__(1024) float g_mod[3072];
__device__ __align__(1024) uint32_t g_modv[4096 + 4096];
__device__ __align__(1024) bf16 g_qkv[192 * 2048 * 8];
__device__ __align__(1024) float g_kmax[32 * 128];
__device__ __align__(1024) bf16 g_o[16 * 64 * 128 * 8];
__device__ __align__(1024) bf16 g_x1[16 * 64 * 128 * 8];
__device__ __align__(1024) bf16 g_a[16 * 64 * 128 * 8];
__device__ __align__(1024) float2 g_uv[2 * 1408];
__device__ __align__(1024) float2 g_st[2048 * 8];
__device__ __align__(1024) bf16 g_h[16 * 172 * 128 * 8];

__device__ __forceinline__ uint32_t smem_u32(const void* p) { return (uint32_t)__cvta_generic_to_shared(p); }
__device__ __forceinline__ void mbar_init(uint32_t b, int n) { asm volatile("mbarrier.init.shared::cta.b64 [%0],%1;" ::"r"(b), "r"(n) : "memory"); }
__device__ __forceinline__ void mbar_expect(uint32_t b, int bytes) { asm volatile("mbarrier.arrive.expect_tx.shared::cta.b64 _,[%0],%1;" ::"r"(b), "r"(bytes) : "memory"); }
__device__ __forceinline__ void mbar_arrive(uint32_t b) { asm volatile("mbarrier.arrive.shared::cta.b64 _,[%0];" ::"r"(b) : "memory"); }
__device__ __forceinline__ void mbar_wait(uint32_t b, int parity) {
  asm volatile("{\n.reg .pred p;\n.reg .u32 n;\nmov.u32 n,0;\nLW:\nmbarrier.try_wait.parity.shared::cta.b64 p,[%0],%1;\n@p bra LD;\n"
               "add.u32 n,n,1;\nsetp.lt.u32 p,n,4194304;\n@p bra LW;\nLD:\n}\n" ::"r"(b), "r"(parity) : "memory");
}
__device__ __forceinline__ void fence_init() { asm volatile("fence.mbarrier_init.release.cluster;" ::: "memory"); }
__device__ __forceinline__ void fence_async() { asm volatile("fence.proxy.async.shared::cta;" ::: "memory"); }
__device__ __forceinline__ void bulk_load(uint32_t dst, const void* src, int bytes, uint32_t bar) {
  asm volatile("cp.async.bulk.shared::cluster.global.mbarrier::complete_tx::bytes [%0],[%1],%2,[%3];" ::"r"(dst), "l"(src), "r"(bytes), "r"(bar) : "memory");
}
__device__ __forceinline__ void tma2d(uint32_t dst, const CUtensorMap* m, int c0, int c1, uint32_t bar) {
  asm volatile("cp.async.bulk.tensor.2d.shared::cluster.global.mbarrier::complete_tx::bytes [%0],[%1,{%3,%4}],[%2];" ::"r"(dst), "l"(m), "r"(bar), "r"(c0), "r"(c1) : "memory");
}
__device__ __forceinline__ void bulk_load_mc(uint32_t dst, const void* src, int bytes, uint32_t bar) {
  asm volatile("cp.async.bulk.shared::cluster.global.mbarrier::complete_tx::bytes.multicast::cluster [%0],[%1],%2,[%3],%4;" ::"r"(dst), "l"(src), "r"(bytes), "r"(bar), "h"((uint16_t)3) : "memory");
}
__device__ __forceinline__ void tma2d_mc(uint32_t dst, const CUtensorMap* m, int c0, int c1, uint32_t bar) {
  asm volatile("cp.async.bulk.tensor.2d.shared::cluster.global.mbarrier::complete_tx::bytes.multicast::cluster [%0],[%1,{%3,%4}],[%2],%5;" ::"r"(dst), "l"(m), "r"(bar), "r"(c0), "r"(c1), "h"((uint16_t)3) : "memory");
}
__device__ __forceinline__ void cluster_arrive() { asm volatile("barrier.cluster.arrive.relaxed.aligned;" ::: "memory"); }
__device__ __forceinline__ void cluster_wait() { asm volatile("barrier.cluster.wait.aligned;" ::: "memory"); }
__device__ __forceinline__ void cluster_sync() { asm volatile("barrier.cluster.arrive.release.aligned;\nbarrier.cluster.wait.acquire.aligned;" ::: "memory"); }
__device__ __forceinline__ void l2_prefetch(const void* p, int bytes) { asm volatile("cp.async.bulk.prefetch.L2.global [%0],%1;" ::"l"(p), "r"(bytes) : "memory"); }
__device__ __forceinline__ void pdl_launch() { asm volatile("griddepcontrol.launch_dependents;" ::: "memory"); }
__device__ __forceinline__ void pdl_wait() { asm volatile("griddepcontrol.wait;" ::: "memory"); }
__device__ __forceinline__ void wg_fence() { asm volatile("wgmma.fence.sync.aligned;" ::: "memory"); }
__device__ __forceinline__ void wg_commit() { asm volatile("wgmma.commit_group.sync.aligned;" ::: "memory"); }
template <int N> __device__ __forceinline__ void wg_wait() { asm volatile("wgmma.wait_group.sync.aligned %0;" ::"n"(N) : "memory"); }
template <int N> __device__ __forceinline__ void reg_fence(float (&d)[N]) {
#pragma unroll
  for (int i = 0; i < N; i++) asm volatile("" : "+f"(d[i])::"memory");
}
template <int N> __device__ __forceinline__ void zero(float (&d)[N]) {
#pragma unroll
  for (int i = 0; i < N; i++) d[i] = 0.f;
  reg_fence(d);
}
__device__ __forceinline__ uint64_t mk_desc(uint32_t addr, uint32_t lbo, uint32_t sbo, uint32_t mode) {
  return (uint64_t)((addr >> 4) & 0x3FFF) | ((uint64_t)(lbo >> 4) << 16) | ((uint64_t)(sbo >> 4) << 32) | ((uint64_t)mode << 62);
}
__device__ __forceinline__ void ldsm4(uint32_t a, uint32_t (&r)[4]) {
  asm volatile("ldmatrix.sync.aligned.m8n8.x4.shared.b16 {%0,%1,%2,%3},[%4];" : "=r"(r[0]), "=r"(r[1]), "=r"(r[2]), "=r"(r[3]) : "r"(a) : "memory");
}
__device__ __forceinline__ uint32_t pack_rn(float lo, float hi) { uint32_t r; asm("cvt.rn.bf16x2.f32 %0,%1,%2;" : "=r"(r) : "f"(hi), "f"(lo)); return r; }
__device__ __forceinline__ uint32_t pack_rz(float lo, float hi) { uint32_t r; asm("cvt.rz.bf16x2.f32 %0,%1,%2;" : "=r"(r) : "f"(hi), "f"(lo)); return r; }
__device__ __forceinline__ float blo(uint32_t u) { return __uint_as_float(u << 16); }
__device__ __forceinline__ float bhi(uint32_t u) { return __uint_as_float(u & 0xFFFF0000u); }
__device__ __forceinline__ float rbf(float x) { return __bfloat162float(__float2bfloat16_rn(x)); }
__device__ __forceinline__ float qsum(float v) { v += __shfl_xor_sync(~0u, v, 1); return v + __shfl_xor_sync(~0u, v, 2); }
__device__ __forceinline__ float ex2(float x) { float r; asm("ex2.approx.ftz.f32 %0,%1;" : "=f"(r) : "f"(x)); return r; }
#define TS(k, i)
__device__ __forceinline__ void wgmma_rs_n176_t1(float (&d)[88],uint32_t a0,uint32_t a1,uint32_t a2,uint32_t a3,uint64_t db,int sc){
  asm volatile("{\n.reg .pred p;\nsetp.ne.b32 p,%93,0;\n"
    "wgmma.mma_async.sync.aligned.m64n176k16.f32.bf16.bf16 {%0,%1,%2,%3,%4,%5,%6,%7,%8,%9,%10,%11,%12,%13,%14,%15,%16,%17,%18,%19,%20,%21,%22,%23,%24,%25,%26,%27,%28,%29,%30,%31,%32,%33,%34,%35,%36,%37,%38,%39,%40,%41,%42,%43,%44,%45,%46,%47,%48,%49,%50,%51,%52,%53,%54,%55,%56,%57,%58,%59,%60,%61,%62,%63,%64,%65,%66,%67,%68,%69,%70,%71,%72,%73,%74,%75,%76,%77,%78,%79,%80,%81,%82,%83,%84,%85,%86,%87},{%88,%89,%90,%91},%92,p,1,1,1;\n}\n"
    :"+f"(d[0]),"+f"(d[1]),"+f"(d[2]),"+f"(d[3]),"+f"(d[4]),"+f"(d[5]),"+f"(d[6]),"+f"(d[7]),"+f"(d[8]),"+f"(d[9]),"+f"(d[10]),"+f"(d[11]),"+f"(d[12]),"+f"(d[13]),"+f"(d[14]),"+f"(d[15]),"+f"(d[16]),"+f"(d[17]),"+f"(d[18]),"+f"(d[19]),"+f"(d[20]),"+f"(d[21]),"+f"(d[22]),"+f"(d[23]),"+f"(d[24]),"+f"(d[25]),"+f"(d[26]),"+f"(d[27]),"+f"(d[28]),"+f"(d[29]),"+f"(d[30]),"+f"(d[31]),"+f"(d[32]),"+f"(d[33]),"+f"(d[34]),"+f"(d[35]),"+f"(d[36]),"+f"(d[37]),"+f"(d[38]),"+f"(d[39]),"+f"(d[40]),"+f"(d[41]),"+f"(d[42]),"+f"(d[43]),"+f"(d[44]),"+f"(d[45]),"+f"(d[46]),"+f"(d[47]),"+f"(d[48]),"+f"(d[49]),"+f"(d[50]),"+f"(d[51]),"+f"(d[52]),"+f"(d[53]),"+f"(d[54]),"+f"(d[55]),"+f"(d[56]),"+f"(d[57]),"+f"(d[58]),"+f"(d[59]),"+f"(d[60]),"+f"(d[61]),"+f"(d[62]),"+f"(d[63]),"+f"(d[64]),"+f"(d[65]),"+f"(d[66]),"+f"(d[67]),"+f"(d[68]),"+f"(d[69]),"+f"(d[70]),"+f"(d[71]),"+f"(d[72]),"+f"(d[73]),"+f"(d[74]),"+f"(d[75]),"+f"(d[76]),"+f"(d[77]),"+f"(d[78]),"+f"(d[79]),"+f"(d[80]),"+f"(d[81]),"+f"(d[82]),"+f"(d[83]),"+f"(d[84]),"+f"(d[85]),"+f"(d[86]),"+f"(d[87])
    :"r"(a0),"r"(a1),"r"(a2),"r"(a3),"l"(db),"r"(sc));
}
__device__ __forceinline__ void wgmma_rs_n192_t1(float (&d)[96],uint32_t a0,uint32_t a1,uint32_t a2,uint32_t a3,uint64_t db,int sc){
  asm volatile("{\n.reg .pred p;\nsetp.ne.b32 p,%101,0;\n"
    "wgmma.mma_async.sync.aligned.m64n192k16.f32.bf16.bf16 {%0,%1,%2,%3,%4,%5,%6,%7,%8,%9,%10,%11,%12,%13,%14,%15,%16,%17,%18,%19,%20,%21,%22,%23,%24,%25,%26,%27,%28,%29,%30,%31,%32,%33,%34,%35,%36,%37,%38,%39,%40,%41,%42,%43,%44,%45,%46,%47,%48,%49,%50,%51,%52,%53,%54,%55,%56,%57,%58,%59,%60,%61,%62,%63,%64,%65,%66,%67,%68,%69,%70,%71,%72,%73,%74,%75,%76,%77,%78,%79,%80,%81,%82,%83,%84,%85,%86,%87,%88,%89,%90,%91,%92,%93,%94,%95},{%96,%97,%98,%99},%100,p,1,1,1;\n}\n"
    :"+f"(d[0]),"+f"(d[1]),"+f"(d[2]),"+f"(d[3]),"+f"(d[4]),"+f"(d[5]),"+f"(d[6]),"+f"(d[7]),"+f"(d[8]),"+f"(d[9]),"+f"(d[10]),"+f"(d[11]),"+f"(d[12]),"+f"(d[13]),"+f"(d[14]),"+f"(d[15]),"+f"(d[16]),"+f"(d[17]),"+f"(d[18]),"+f"(d[19]),"+f"(d[20]),"+f"(d[21]),"+f"(d[22]),"+f"(d[23]),"+f"(d[24]),"+f"(d[25]),"+f"(d[26]),"+f"(d[27]),"+f"(d[28]),"+f"(d[29]),"+f"(d[30]),"+f"(d[31]),"+f"(d[32]),"+f"(d[33]),"+f"(d[34]),"+f"(d[35]),"+f"(d[36]),"+f"(d[37]),"+f"(d[38]),"+f"(d[39]),"+f"(d[40]),"+f"(d[41]),"+f"(d[42]),"+f"(d[43]),"+f"(d[44]),"+f"(d[45]),"+f"(d[46]),"+f"(d[47]),"+f"(d[48]),"+f"(d[49]),"+f"(d[50]),"+f"(d[51]),"+f"(d[52]),"+f"(d[53]),"+f"(d[54]),"+f"(d[55]),"+f"(d[56]),"+f"(d[57]),"+f"(d[58]),"+f"(d[59]),"+f"(d[60]),"+f"(d[61]),"+f"(d[62]),"+f"(d[63]),"+f"(d[64]),"+f"(d[65]),"+f"(d[66]),"+f"(d[67]),"+f"(d[68]),"+f"(d[69]),"+f"(d[70]),"+f"(d[71]),"+f"(d[72]),"+f"(d[73]),"+f"(d[74]),"+f"(d[75]),"+f"(d[76]),"+f"(d[77]),"+f"(d[78]),"+f"(d[79]),"+f"(d[80]),"+f"(d[81]),"+f"(d[82]),"+f"(d[83]),"+f"(d[84]),"+f"(d[85]),"+f"(d[86]),"+f"(d[87]),"+f"(d[88]),"+f"(d[89]),"+f"(d[90]),"+f"(d[91]),"+f"(d[92]),"+f"(d[93]),"+f"(d[94]),"+f"(d[95])
    :"r"(a0),"r"(a1),"r"(a2),"r"(a3),"l"(db),"r"(sc));
}
__device__ __forceinline__ void wgmma_rs_n24_t1(float (&d)[12],uint32_t a0,uint32_t a1,uint32_t a2,uint32_t a3,uint64_t db,int sc){
  asm volatile("{\n.reg .pred p;\nsetp.ne.b32 p,%17,0;\n"
    "wgmma.mma_async.sync.aligned.m64n24k16.f32.bf16.bf16 {%0,%1,%2,%3,%4,%5,%6,%7,%8,%9,%10,%11},{%12,%13,%14,%15},%16,p,1,1,1;\n}\n"
    :"+f"(d[0]),"+f"(d[1]),"+f"(d[2]),"+f"(d[3]),"+f"(d[4]),"+f"(d[5]),"+f"(d[6]),"+f"(d[7]),"+f"(d[8]),"+f"(d[9]),"+f"(d[10]),"+f"(d[11])
    :"r"(a0),"r"(a1),"r"(a2),"r"(a3),"l"(db),"r"(sc));
}
__device__ __forceinline__ void wgmma_rs_n64_t0(float (&d)[32],uint32_t a0,uint32_t a1,uint32_t a2,uint32_t a3,uint64_t db,int sc){
  asm volatile("{\n.reg .pred p;\nsetp.ne.b32 p,%37,0;\n"
    "wgmma.mma_async.sync.aligned.m64n64k16.f32.bf16.bf16 {%0,%1,%2,%3,%4,%5,%6,%7,%8,%9,%10,%11,%12,%13,%14,%15,%16,%17,%18,%19,%20,%21,%22,%23,%24,%25,%26,%27,%28,%29,%30,%31},{%32,%33,%34,%35},%36,p,1,1,0;\n}\n"
    :"+f"(d[0]),"+f"(d[1]),"+f"(d[2]),"+f"(d[3]),"+f"(d[4]),"+f"(d[5]),"+f"(d[6]),"+f"(d[7]),"+f"(d[8]),"+f"(d[9]),"+f"(d[10]),"+f"(d[11]),"+f"(d[12]),"+f"(d[13]),"+f"(d[14]),"+f"(d[15]),"+f"(d[16]),"+f"(d[17]),"+f"(d[18]),"+f"(d[19]),"+f"(d[20]),"+f"(d[21]),"+f"(d[22]),"+f"(d[23]),"+f"(d[24]),"+f"(d[25]),"+f"(d[26]),"+f"(d[27]),"+f"(d[28]),"+f"(d[29]),"+f"(d[30]),"+f"(d[31])
    :"r"(a0),"r"(a1),"r"(a2),"r"(a3),"l"(db),"r"(sc));
}
__device__ __forceinline__ void wgmma_ss_n128_t1(float (&d)[64],uint64_t da,uint64_t db,int sc){
  asm volatile("{\n.reg .pred p;\nsetp.ne.b32 p,%66,0;\n"
    "wgmma.mma_async.sync.aligned.m64n128k16.f32.bf16.bf16 {%0,%1,%2,%3,%4,%5,%6,%7,%8,%9,%10,%11,%12,%13,%14,%15,%16,%17,%18,%19,%20,%21,%22,%23,%24,%25,%26,%27,%28,%29,%30,%31,%32,%33,%34,%35,%36,%37,%38,%39,%40,%41,%42,%43,%44,%45,%46,%47,%48,%49,%50,%51,%52,%53,%54,%55,%56,%57,%58,%59,%60,%61,%62,%63},%64,%65,p,1,1,0,1;\n}\n"
    :"+f"(d[0]),"+f"(d[1]),"+f"(d[2]),"+f"(d[3]),"+f"(d[4]),"+f"(d[5]),"+f"(d[6]),"+f"(d[7]),"+f"(d[8]),"+f"(d[9]),"+f"(d[10]),"+f"(d[11]),"+f"(d[12]),"+f"(d[13]),"+f"(d[14]),"+f"(d[15]),"+f"(d[16]),"+f"(d[17]),"+f"(d[18]),"+f"(d[19]),"+f"(d[20]),"+f"(d[21]),"+f"(d[22]),"+f"(d[23]),"+f"(d[24]),"+f"(d[25]),"+f"(d[26]),"+f"(d[27]),"+f"(d[28]),"+f"(d[29]),"+f"(d[30]),"+f"(d[31]),"+f"(d[32]),"+f"(d[33]),"+f"(d[34]),"+f"(d[35]),"+f"(d[36]),"+f"(d[37]),"+f"(d[38]),"+f"(d[39]),"+f"(d[40]),"+f"(d[41]),"+f"(d[42]),"+f"(d[43]),"+f"(d[44]),"+f"(d[45]),"+f"(d[46]),"+f"(d[47]),"+f"(d[48]),"+f"(d[49]),"+f"(d[50]),"+f"(d[51]),"+f"(d[52]),"+f"(d[53]),"+f"(d[54]),"+f"(d[55]),"+f"(d[56]),"+f"(d[57]),"+f"(d[58]),"+f"(d[59]),"+f"(d[60]),"+f"(d[61]),"+f"(d[62]),"+f"(d[63])
    :"l"(da),"l"(db),"r"(sc));
}
__device__ __forceinline__ void wgmma_ss_n64_t1(float (&d)[32],uint64_t da,uint64_t db,int sc){
  asm volatile("{\n.reg .pred p;\nsetp.ne.b32 p,%34,0;\n"
    "wgmma.mma_async.sync.aligned.m64n64k16.f32.bf16.bf16 {%0,%1,%2,%3,%4,%5,%6,%7,%8,%9,%10,%11,%12,%13,%14,%15,%16,%17,%18,%19,%20,%21,%22,%23,%24,%25,%26,%27,%28,%29,%30,%31},%32,%33,p,1,1,0,1;\n}\n"
    :"+f"(d[0]),"+f"(d[1]),"+f"(d[2]),"+f"(d[3]),"+f"(d[4]),"+f"(d[5]),"+f"(d[6]),"+f"(d[7]),"+f"(d[8]),"+f"(d[9]),"+f"(d[10]),"+f"(d[11]),"+f"(d[12]),"+f"(d[13]),"+f"(d[14]),"+f"(d[15]),"+f"(d[16]),"+f"(d[17]),"+f"(d[18]),"+f"(d[19]),"+f"(d[20]),"+f"(d[21]),"+f"(d[22]),"+f"(d[23]),"+f"(d[24]),"+f"(d[25]),"+f"(d[26]),"+f"(d[27]),"+f"(d[28]),"+f"(d[29]),"+f"(d[30]),"+f"(d[31])
    :"l"(da),"l"(db),"r"(sc));
}

__device__ __forceinline__ float silu_bf(bf16 c) { const float x = __bfloat162float(c); return rbf(x / (1.f + __expf(-x))); }
__device__ __forceinline__ void fma8(float (&a)[8], float s, const uint4& v) {
  a[0] += s * blo(v.x); a[1] += s * bhi(v.x); a[2] += s * blo(v.y); a[3] += s * bhi(v.y);
  a[4] += s * blo(v.z); a[5] += s * bhi(v.z); a[6] += s * blo(v.w); a[7] += s * bhi(v.w);
}
__device__ __forceinline__ float red8(float (&a)[8], int lane) {
#pragma unroll
  for (int w = 4; w >= 1; w >>= 1) {
    const bool up = lane & (w * 4);
#pragma unroll
    for (int j = 0; j < w; j++) a[j] = (up ? a[j + w] : a[j]) + __shfl_xor_sync(~0u, up ? a[j] : a[j + w], w * 4);
  }
  return a[0];
}
__device__ __forceinline__ float mod_fin(float s, int n) { s = rbf(s); return ((n >> 9) == 1 || (n >> 9) == 4) ? rbf(1.f + s) : s; }
__device__ __forceinline__ void poll(uint2& a, uint2& b, float (&w)[16], const uint32_t* p, const uint32_t* q) {
  asm volatile("{\n.reg .pred p;\n.reg .b32 n,t,u;\nmov.u32 n,0;\nLW:\nld.relaxed.gpu.global.v2.u32 {%0,%1},[%20];\nld.relaxed.gpu.global.v2.u32 {%2,%3},[%20+64];\n"
               "ld.relaxed.gpu.global.v4.f32 {%4,%5,%6,%7},[%21];\nld.relaxed.gpu.global.v4.f32 {%8,%9,%10,%11},[%21+16];\n"
               "ld.relaxed.gpu.global.v4.f32 {%12,%13,%14,%15},[%21+8192];\nld.relaxed.gpu.global.v4.f32 {%16,%17,%18,%19},[%21+8208];\n"
               "lop3.b32 t,%0,%1,%2,0x80;\nlop3.b32 u,%3,%4,%5,0x80;\nlop3.b32 t,t,%6,%7,0x80;\nlop3.b32 u,u,%8,%9,0x80;\nlop3.b32 t,t,%10,%11,0x80;\n"
               "lop3.b32 u,u,%12,%13,0x80;\nlop3.b32 t,t,%14,%15,0x80;\nlop3.b32 u,u,%16,%17,0x80;\nlop3.b32 t,t,%18,%19,0x80;\nlop3.b32 t,t,u,1,0x80;\n"
               "setp.ne.u32 p,t,0;\n@p bra LD;\nadd.u32 n,n,1;\nsetp.lt.u32 p,n,1048576;\n@p bra LW;\nLD:\n}\n"
               : "=&r"(a.x), "=&r"(a.y), "=&r"(b.x), "=&r"(b.y), "=&f"(w[0]), "=&f"(w[1]), "=&f"(w[2]), "=&f"(w[3]), "=&f"(w[4]), "=&f"(w[5]), "=&f"(w[6]), "=&f"(w[7]),
                 "=&f"(w[8]), "=&f"(w[9]), "=&f"(w[10]), "=&f"(w[11]), "=&f"(w[12]), "=&f"(w[13]), "=&f"(w[14]), "=&f"(w[15]) : "l"(p), "l"(q) : "memory");
}

constexpr int LN_SMEM = 131072 + 4 * 24576 + 2816 + 256;
#define TANH 1
#define DLY 2
template <bool FFN>
__global__ void __cluster_dims__(2, 1, 1) __launch_bounds__(384, 1) k_lngemm(const __grid_constant__ CUtensorMap mX, const __grid_constant__ CUtensorMap mB0,
                                                   const __grid_constant__ CUtensorMap mB1, const bf16* __restrict__ cv, const bf16* __restrict__ wm, const bf16* __restrict__ xg, const bf16* wq) {
  extern __shared__ __align__(1024) uint8_t smem[];
  const uint32_t sA = smem_u32(smem), sB = sA + (FFN ? 81920 : 131072), sM = sA + 229376, bars = sM + 2816;
  const uint32_t bA = bars, bF = bars + 64, bE = bars + 112;
  constexpr int NB = FFN ? 6 : 4;
  const int tid = threadIdx.x, warp = tid >> 5, lane = tid & 31;
  const int pr = blockIdx.x & 1, rb = FFN ? (blockIdx.x >> 4) * 2 + pr : blockIdx.x >> 3, ct = FFN ? (blockIdx.x >> 1) & 7 : blockIdx.x & 7;
  constexpr int NST = FFN ? 16 : 8, KS = FFN ? 2 : 4, BOX = FFN ? 4096 : 8192;
  TS(FFN ? 4 : 1, 0);
  pdl_launch();
  float* red = (float*)(smem + (sM - sA));
  if (tid == 256) {
    for (int i = 0; i < 8; i++) mbar_init(bA + 8 * i, 1);
    for (int i = 0; i < NB; i++) { mbar_init(bF + 8 * i, 1); mbar_init(bE + 8 * i, FFN ? 16 : 8); }
    mbar_init(bars + 160, 1);
    fence_init();
  }
  __syncwarp();
  cluster_arrive();
  uint4 wv0, wv1, xv[4];
  bf16 cv0, cv1;
  if (!FFN && tid < 256) {
    const int r = (blockIdx.x & 3) * 128 + (tid >> 2);
    const uint4* wp = (const uint4*)(wm + r * 3072 + (blockIdx.x >> 2) * 32 + (tid & 3) * 8);
    wv0 = __ldg(wp); wv1 = __ldg(wp + 64 * 384);
    cv0 = cv[r]; cv1 = cv[r + 64];
#pragma unroll
    for (int i = 0; i < 4; i++) xv[i] = __ldg((const uint4*)(xg + (blockIdx.x * 16 + (tid >> 4)) * 512 + i * 128 + (tid & 15) * 8));
  }
  cluster_wait();
  if (warp >= 8) {
    asm volatile("setmaxnreg.dec.sync.aligned.u32 40;");
    if (tid == 256) {
      auto loadB = [&](int s) {
        const uint32_t d = sB + (s % NB) * 24576, b = bF + (s % NB) * 8;
        mbar_expect(b, 24576);
        for (int j = 0; j < 3; j++) {
          if (FFN) tma2d_mc(d + (pr * 3 + j) * BOX, pr ? &mB1 : &mB0, ct * 176 + j * 64, s * 32, b);
          else tma2d(d + j * BOX, &mB0, ct * 192 + j * 64, s * 64, b);
        }
      };
      for (int i = 0; i < 8; i++) mbar_expect(bA + 8 * i, 16384);
      if (!FFN) l2_prefetch((const char*)wq + blockIdx.x * 12288, 12288);
      for (int s = 0; s < NB; s++) {
        const int i = s * 2 + (ct & 1);
        if (!FFN && s == DLY) mbar_wait(bars + 160, 0);
        if (!FFN) tma2d_mc(sA + i * 16384, &mX, i * 64, rb * 128, bA + 8 * i);
        loadB(s);
      }
      if (FFN) {
        pdl_wait();
        for (int i = 0; i < 5; i++) bulk_load(sA + i * 16384, g_a + (rb * 64 + i * 8) * 1024, 16384, bA + 8 * i);
      }
      for (int s = NB; s < NST; s++) {
        mbar_wait(bE + (s % NB) * 8, (s / NB - 1) & 1); loadB(s);
        if (FFN && s <= 10 && !(s & 1)) bulk_load(sA + (s / 2 - 3) * 16384, g_a + (rb * 64 + (s / 2 + 2) * 8) * 1024, 16384, bA + 8 * (s / 2 + 2));
      }
    }
  } else {
  asm volatile("setmaxnreg.inc.sync.aligned.u32 232;");
  const int g = lane >> 2, t = lane & 3;
  const int lr = warp * 16 + (lane & 7) + ((lane >> 3) & 1) * 8;
  auto aaddr = [&](int ks) -> uint32_t {
    if (FFN) return sA + ((ks < 20 ? ks : ks - 20) * 2 + (lane >> 4)) * 2048 + lr * 16;
    return sA + (ks >> 2) * 16384 + lr * 128 + ((((ks & 3) * 2 + (lane >> 4)) ^ (lr & 7)) << 4);
  };
  const int row0 = rb * 128 + warp * 16 + g;
  float2 msh, msc;
  float4 p0, p1, uv;
  float rs0, rs1, nm0, nm1;
  if (!FFN) {
    {
      float a[8] = {0, 0, 0, 0, 0, 0, 0, 0};
      fma8(a, silu_bf(cv0), wv0); fma8(a, silu_bf(cv1), wv1);
      red[warp * 32 + t * 8 + g] = red8(a, lane);
      asm volatile("bar.sync 1,256;" ::: "memory");
      if (tid < 32) {
        float r = 0;
#pragma unroll
        for (int i = 0; i < 8; i++) r += red[i * 32 + tid];
        asm volatile("st.relaxed.gpu.global.u32 [%0],%1;" ::"l"(g_modv + ((blockIdx.x >> 2) * 32 + tid) * 4 + (blockIdx.x & 3)), "r"(__float_as_uint(r) | 1u) : "memory");
      }
      TS(0, 1);
    }
    {
      float v[32], s = 0, q = 0;
#pragma unroll
      for (int i = 0; i < 16; i++) { const uint32_t u = ((const uint32_t*)xv)[i]; v[2 * i] = blo(u); v[2 * i + 1] = bhi(u); s += v[2 * i] + v[2 * i + 1]; }
      s = qsum(s); s += __shfl_xor_sync(~0u, s, 4); s += __shfl_xor_sync(~0u, s, 8);
      const float m = s * (1.f / 512);
#pragma unroll
      for (int i = 0; i < 32; i++) q += (v[i] - m) * (v[i] - m);
      q = qsum(q); q += __shfl_xor_sync(~0u, q, 4); q += __shfl_xor_sync(~0u, q, 8);
      const float rs = rsqrtf(q * (1.f / 512) + 1e-5f);
      if ((tid & 15) == 0)
        asm volatile("st.relaxed.gpu.global.v2.u32 [%0],{%1,%2};" ::"l"(g_modv + 4096 + (blockIdx.x * 16 + (tid >> 4)) * 2), "r"(__float_as_uint(rs) | 1u), "r"(__float_as_uint(-m * rs) | 1u) : "memory");
    }
    uint2 q0, q1;
    float w[16];
    if (tid < 128) {
      uint32_t v; int n = 0;
      do asm volatile("ld.relaxed.gpu.global.u32 %0,[%1];" : "=r"(v) : "l"(g_modv + (tid >> 2) * 128 + (tid & 3)) : "memory"); while (!(v & 1) && ++n < 1048576);
    }
    asm volatile("bar.sync 1,256;" ::: "memory");
    poll(q0, q1, w, g_modv + 4096 + row0 * 2, g_modv + tid * 8);
    msh = make_float2(mod_fin(w[0] + w[1] + w[2] + w[3], 0), mod_fin(w[4] + w[5] + w[6] + w[7], 0));
    msc = make_float2(mod_fin(w[8] + w[9] + w[10] + w[11], 512), mod_fin(w[12] + w[13] + w[14] + w[15], 512));
    asm volatile("bar.sync 1,256;" ::: "memory");
    if (tid == 32) mbar_arrive(bars + 160);
    rs0 = __uint_as_float(q0.x); nm0 = __uint_as_float(q0.y); rs1 = __uint_as_float(q1.x); nm1 = __uint_as_float(q1.y);
  } else {
    pdl_wait();
    TS(4, 1);
    p0 = *(const float4*)(g_st + row0 * 8 + t * 2); p1 = *(const float4*)(g_st + (row0 + 8) * 8 + t * 2);
    if (tid < 176) uv = *(const float4*)(g_uv + (tid >= 88 ? 1408 - 176 : 0) + ct * 176 + tid * 2);
  }
  if (!FFN) {
    uint32_t* m = (uint32_t*)(smem + (sM - sA)) + (tid >> 3) * 16 + (tid & 3) * 4 + ((tid >> 2) & 1);
    m[0] = pack_rn(msc.x, msc.y); m[2] = pack_rn(msh.x, msh.y);
    asm volatile("bar.sync 1,256;" ::: "memory");
  }
  constexpr int NA = FFN ? 88 : 96;
  float acc0[NA], acc1[FFN ? 88 : 1];
  uint32_t a[2][KS][4];
  auto prep = [&](int ks, uint32_t(&o)[4]) {
    if ((ks & 3) == 0) mbar_wait(bA + 2 * ks, 0);
    if (FFN) { ldsm4(aaddr(ks), o); return; }
    uint32_t r[4]; ldsm4(aaddr(ks), r);
    const uint4 m = *(const uint4*)(smem + (sM - sA) + ks * 64 + t * 16);
#pragma unroll
    for (int i = 0; i < 4; i++) {
      const float rs = (i & 1) ? rs1 : rs0, nm = (i & 1) ? nm1 : nm0;
      const uint32_t n = pack_rn(fmaf(blo(r[i]), rs, nm), fmaf(bhi(r[i]), rs, nm));
      asm("fma.rn.bf16x2 %0,%1,%2,%3;" : "=r"(o[i]) : "r"(n), "r"(i < 2 ? m.x : m.y), "r"(i < 2 ? m.z : m.w));
    }
  };
  auto stage = [&](int s, uint32_t(&c)[KS][4], uint32_t(&n)[KS][4]) {
    mbar_wait(bF + (s % NB) * 8, (s / NB) & 1);
    const uint64_t db = mk_desc(sB + (s % NB) * 24576, BOX, 1024, 1);
    wg_fence();
#pragma unroll
    for (int k = 0; k < KS; k++) {
      if constexpr (FFN) {
        wgmma_rs_n176_t1(acc0, c[k][0], c[k][1], c[k][2], c[k][3], db + k * 128, s + k);
        wgmma_rs_n176_t1(acc1, c[k][0], c[k][1], c[k][2], c[k][3], db + k * 128 + 3 * BOX / 16, s + k);
      } else {
        wgmma_rs_n192_t1(acc0, c[k][0], c[k][1], c[k][2], c[k][3], db + k * 128, s + k);
      }
    }
    wg_commit();
    wg_wait<1>();
    if (s > 0 && s <= NST - NB) {
      if (!FFN) { if (lane == 0) mbar_arrive(bE + ((s - 1) % NB) * 8); }
      else if (lane < 2) asm volatile("{\n.reg .b32 r;\nmapa.shared::cluster.u32 r,%0,%1;\nmbarrier.arrive.relaxed.cluster.shared::cluster.b64 _,[r];\n}" ::"r"(bE + ((s - 1) % NB) * 8), "r"(lane) : "memory");
    }
    if (s < NST - 1) {
#pragma unroll
      for (int k = 0; k < KS; k++) prep((s + 1) * KS + k, n[k]);
    }
  };
#pragma unroll
  for (int k = 0; k < KS; k++) prep(k, a[0][k]);
  TS(FFN ? 4 : 1, 2);
#pragma unroll 1
  for (int s = 0; s < NST; s += 2) { stage(s, a[0], a[1]); stage(s + 1, a[1], a[0]); }
  if (FFN) {
    if (tid < 88) { uv.x *= 0.5f; uv.y *= 0.5f; uv.z *= 0.5f; uv.w *= 0.5f; }
    if (tid < 176) *(float4*)(smem + (sM - sA) + tid * 16) = uv;
    const float m0 = qsum(p0.x + p0.z) * 0.125f, m1 = qsum(p1.x + p1.z) * 0.125f;
    const float v0 = qsum(p0.y + p0.w + 64.f * ((p0.x - m0) * (p0.x - m0) + (p0.z - m0) * (p0.z - m0)));
    const float v1 = qsum(p1.y + p1.w + 64.f * ((p1.x - m1) * (p1.x - m1) + (p1.z - m1) * (p1.z - m1)));
    rs0 = rsqrtf(v0 * (1.f / 512) + 1e-5f); rs1 = rsqrtf(v1 * (1.f / 512) + 1e-5f);
    nm0 = -m0 * rs0; nm1 = -m1 * rs1;
    asm volatile("bar.sync 1,256;" ::: "memory");
  }
  wg_wait<0>();
  reg_fence(acc0);
  TS(FFN ? 4 : 1, 3);
  if constexpr (FFN) {
    reg_fence(acc1);
    const float rh0 = 0.5f * rs0, rh1 = 0.5f * rs1;
    uint32_t* o = (uint32_t*)g_h + ((rb * 172 + ct * 22) * 128 + warp * 16 + g) * 4 + t;
#pragma unroll
    for (int j = 0; j < 22; j++) {
      {
        const float4 u1 = *(const float4*)(smem + (sM - sA) + (j * 4 + t) * 16), u3 = *(const float4*)(smem + (sM - sA) + (88 + j * 4 + t) * 16);
        float h[4];
#pragma unroll
        for (int i = 0; i < 4; i++) {
          const float rs = i < 2 ? rs0 : rs1, nm = i < 2 ? nm0 : nm1, rh = i < 2 ? rh0 : rh1;
          const float z = fmaf(rh, acc0[4 * j + i], (i & 1) ? fmaf(nm, u1.z, u1.w) : fmaf(nm, u1.x, u1.y));
          const float y = fmaf(rs, acc1[4 * j + i], (i & 1) ? fmaf(nm, u3.z, u3.w) : fmaf(nm, u3.x, u3.y));
          float th; asm("tanh.approx.f32 %0,%1;" : "=f"(th) : "f"(z));
          h[i] = fmaf(z, th, z) * y;
        }
        if (j < 18 || ct < 7) { o[j * 512] = pack_rn(h[0], h[1]); o[j * 512 + 32] = pack_rn(h[2], h[3]); }
      }
    }
  } else {
    uint32_t* o = (uint32_t*)g_qkv + (ct * 24 * 2048 + row0) * 4 + t;
#pragma unroll
    for (int j = 0; j < 24; j += 2) {
      const int G = ct * 24 + j;
      const float sc = G < 64 ? 0.25f * 1.4426950408889634f : 1.f;
      uint32_t p[4];
#pragma unroll
      for (int i = 0; i < 4; i++) p[i] = pack_rn(acc0[4 * j + 2 * i] * sc, acc0[4 * j + 2 * i + 1] * sc);
      o[j * 8192] = p[0]; o[j * 8192 + 32] = p[1]; o[(j + 1) * 8192] = p[2]; o[(j + 1) * 8192 + 32] = p[3];
      if (G >= 64 && G < 128) {
        float n0 = blo(p[0]) * blo(p[0]) + bhi(p[0]) * bhi(p[0]) + blo(p[2]) * blo(p[2]) + bhi(p[2]) * bhi(p[2]);
        float n1 = blo(p[1]) * blo(p[1]) + bhi(p[1]) * bhi(p[1]) + blo(p[3]) * blo(p[3]) + bhi(p[3]) * bhi(p[3]);
        n0 = qsum(n0); n1 = qsum(n1);
        const uint32_t mx = __reduce_max_sync(~0u, max(__float_as_uint(n0), __float_as_uint(n1)));
        if (lane == 0) g_kmax[((G - 64) >> 1) * 128 + rb * 8 + warp] = __uint_as_float(mx);
      }
    }
  }
  TS(FFN ? 4 : 1, 4);
}
}

#define SMASK 0xCCCCu
#define BRK 0
#define PACK 1
constexpr int AT_SMEM = 5 * 32768 + 256;
__device__ __forceinline__ uint32_t exp2_pair_fma(float s0, float s1, float c, uint32_t ka, uint32_t kz) {
  uint32_t r;
  asm volatile("{\n.reg .b32 y0,y1,e,u,t;\n"
      "fma.rn.sat.f32 y0,%1,0f00000080,%3;\nfma.rn.sat.f32 y1,%2,0f00000080,%3;\n"
      "mad.lo.u32 e,y1,65536,y0;\n"
      "and.b32 u,e,0x007F007F;\n"
      "fma.rn.f16x2 u,u,%4,%5;\nfma.rn.f16x2 t,u,u,%6;\nfma.rn.f16x2 t,t,u,%7;\n"
      "lop3.b32 %0,t,0x007F007F,e,0xE2;\n}\n"
      : "=r"(r) : "f"(s0), "f"(s1), "f"(c), "r"(ka), "r"(0x36B236B2u), "r"(0x3C733C73u), "r"(0x47764776u), "r"(kz));
  return r;
}
__device__ __forceinline__ void attn_pass(float (&oa)[12], float (&ob)[12], const uint32_t (&q)[4], float m0, float m1, uint32_t sK, uint32_t bars, bool first, uint32_t kz) {
  uint64_t dk = mk_desc(sK, 32768, 128, 0), dv = mk_desc(sK + 65536, 128, 32768, 0);
  const float c0 = (127.f - m0) * __uint_as_float(0x80u), c1 = (127.f - m1) * __uint_as_float(0x80u);
  uint32_t ka;
  asm volatile("mov.b32 %0,0x7ACE7ACE;" : "=r"(ka));
  constexpr int NK = 64, NS = 32, NP = 16;
  auto qk = [&](float (&s)[NS], int i) { wgmma_rs_n64_t0(s, q[0], q[1], q[2], q[3], dk + i * NK, 0); };
  auto softmax = [&](float (&s)[NS], uint32_t (&p)[NP], uint32_t mask) {
    reg_fence(s);
    float e0, e1;
    int pend = -1;
#pragma unroll
    for (int t = 0; t < NP; t++) {
      const int j = (t & 3) * 4 + (t >> 2);
      if ((mask >> (t & 3)) & 1) {
        p[j] = exp2_pair_fma(s[2 * j], s[2 * j + 1], (j & 1) ? c1 : c0, ka, kz);
      } else {
        float f0, f1;
        asm volatile("ex2.approx.ftz.f32 %0,%2;\nex2.approx.ftz.f32 %1,%3;" : "=&f"(f0), "=f"(f1) : "f"(s[2 * j]), "f"(s[2 * j + 1]));
        if (pend >= 0) asm volatile("cvt.rn.bf16x2.f32 %0,%1,%2;" : "=r"(p[pend]) : "f"(e1), "f"(e0));
        e0 = f0; e1 = f1; pend = j;
      }
    }
    if (pend >= 0) asm volatile("cvt.rn.bf16x2.f32 %0,%1,%2;" : "=r"(p[pend]) : "f"(e1), "f"(e0));
#pragma unroll
    for (int j = 0; j < NP; j++) asm volatile("" : "+r"(p[j])::"memory");
  };
  auto pv = [&](uint32_t (&p)[NP], int i, uint32_t mask) {
#pragma unroll
    for (int k = 0; k < 4; k++) wgmma_rs_n24_t1(((mask >> k) & 1) ? ob : oa, p[4 * k], p[4 * k + 1], p[4 * k + 2], p[4 * k + 3], dv + i * NK + k * 16, 1);
  };
  constexpr uint32_t M0 = SMASK & 15, M1 = (SMASK >> 4) & 15, M2 = (SMASK >> 8) & 15, M3 = SMASK >> 12;
  zero(oa); zero(ob);
  mbar_wait(bars, 0);
  if (first) TS(2, 2);
  float s[NS];
  zero(s);
  uint32_t p0[NP], p1[NP];
  auto step = [&](int i, uint32_t (&pa)[NP], uint32_t ma, uint32_t (&pb)[NP], uint32_t mb) {
    wg_fence(); qk(s, i + 1); wg_commit(); pv(pa, i, ma); wg_commit(); wg_wait<1>(); softmax(s, pb, mb); wg_wait<0>();
  };
  wg_fence(); qk(s, 0); wg_commit(); wg_wait<0>(); softmax(s, p0, M0);
#pragma unroll 1
  for (uint32_t b = bars + 8; b < bars + 64; b += 8) {
    step(0, p0, M0, p1, M1); step(1, p1, M1, p0, M2); step(2, p0, M2, p1, M3);
    mbar_wait(b, 0);
    step(3, p1, M3, p0, M0);
    dk += 4 * NK; dv += 4 * NK;
  }
  step(0, p0, M0, p1, M1); step(1, p1, M1, p0, M2); step(2, p0, M2, p1, M3);
  wg_fence(); pv(p1, 3, M3); wg_commit();
  wg_wait<0>();
  reg_fence(oa); reg_fence(ob);
}
__device__ __forceinline__ void mma16816(float (&d)[4], const uint32_t (&a)[4], uint32_t b0, uint32_t b1) {
  asm("mma.sync.aligned.m16n8k16.row.col.f32.bf16.bf16.f32 {%0,%1,%2,%3},{%4,%5,%6,%7},{%8,%9},{%0,%1,%2,%3};"
      : "+f"(d[0]), "+f"(d[1]), "+f"(d[2]), "+f"(d[3]) : "r"(a[0]), "r"(a[1]), "r"(a[2]), "r"(a[3]), "r"(b0), "r"(b1));
}
__device__ __forceinline__ void attn_safe(float (&o)[12], const uint32_t (&q)[4], uint32_t sK) {
  const int lane = threadIdx.x & 31;
  const uint32_t ka = sK + (lane >> 4) * 32768 + (lane & 15) * 16;
  float m0 = -INFINITY, m1 = -INFINITY;
#pragma unroll 2
  for (int i = 0; i < 128; i++) {
    uint32_t k[4]; ldsm4(ka + i * 256, k);
    float s0[4] = {0, 0, 0, 0}, s1[4] = {0, 0, 0, 0};
    mma16816(s0, q, k[0], k[2]); mma16816(s1, q, k[1], k[3]);
    m0 = fmaxf(fmaxf(m0, fmaxf(s0[0], s0[1])), fmaxf(s1[0], s1[1])); m1 = fmaxf(fmaxf(m1, fmaxf(s0[2], s0[3])), fmaxf(s1[2], s1[3]));
  }
  m0 = fmaxf(m0, __shfl_xor_sync(~0u, m0, 1)); m0 = fmaxf(m0, __shfl_xor_sync(~0u, m0, 2));
  m1 = fmaxf(m1, __shfl_xor_sync(~0u, m1, 1)); m1 = fmaxf(m1, __shfl_xor_sync(~0u, m1, 2));
  float o0[4] = {0, 0, 0, 0}, o1[4] = {0, 0, 0, 0}, o2[4] = {0, 0, 0, 0};
#pragma unroll 2
  for (int i = 0; i < 128; i++) {
    uint32_t k[4], v[4]; ldsm4(ka + i * 256, k);
    asm volatile("ldmatrix.sync.aligned.m8n8.x4.trans.shared.b16 {%0,%1,%2,%3},[%4];" : "=r"(v[0]), "=r"(v[1]), "=r"(v[2]), "=r"(v[3]) : "r"(ka + 65536 + i * 256) : "memory");
    float s0[4] = {0, 0, 0, 0}, s1[4] = {0, 0, 0, 0};
    mma16816(s0, q, k[0], k[2]); mma16816(s1, q, k[1], k[3]);
    const uint32_t p[4] = {pack_rn(ex2(s0[0] - m0), ex2(s0[1] - m0)), pack_rn(ex2(s0[2] - m1), ex2(s0[3] - m1)),
                           pack_rn(ex2(s1[0] - m0), ex2(s1[1] - m0)), pack_rn(ex2(s1[2] - m1), ex2(s1[3] - m1))};
    mma16816(o0, p, v[0], v[1]); mma16816(o1, p, v[2], v[3]); mma16816(o2, p, 0x3F803F80u, 0x3F803F80u);
  }
#pragma unroll
  for (int i = 0; i < 4; i++) { o[i] = o0[i]; o[4 + i] = o1[i]; o[8 + i] = o2[i]; }
}
__global__ void __cluster_dims__(2, 1, 1) __launch_bounds__(512, 1) k_attn(const bf16* wo, const bf16* w1, const bf16* w3, const bf16* w2, const bf16* __restrict__ cv, const bf16* __restrict__ wm, uint32_t kz) {
  extern __shared__ __align__(1024) uint8_t smem[];
  const uint32_t sK = smem_u32(smem), bars = sK + 5 * 32768;
  const int tid = threadIdx.x, warp = tid >> 5, lane = tid & 31, g = lane >> 2, t = lane & 3;
  pdl_launch();
  if (blockIdx.x < 4) {
    float* cs = (float*)smem;
    cs[tid] = silu_bf(cv[tid]);
    cluster_sync();
    const int b = blockIdx.x;
    float *mv = cs + 512, *rd = cs + 1536;
    auto put8 = [&](float* d, float (&a)[8]) { ((float4*)d)[0] = make_float4(a[0], a[1], a[2], a[3]); ((float4*)d)[1] = make_float4(a[4], a[5], a[6], a[7]); };
    for (int ph = 0; ph < 2; ph++) {
      const int nc = 512 >> ph, n0 = ph ? (b >> 1) * 1536 + 1024 + (b & 1) * 256 : 1536 + (b & 1) * 512, nr = 64 >> ph, r0 = tid / nr * nr;
      float a[8] = {0, 0, 0, 0, 0, 0, 0, 0};
#pragma unroll 16
      for (int r = r0; r < r0 + nr; r++) fma8(a, cs[r], __ldg((const uint4*)(wm + r * 3072 + n0 + (tid & (nr - 1)) * 8)));
      put8(rd + tid * 8, a);
      __syncthreads();
      if (tid < nc) {
        float s = 0;
        for (int i = tid; i < 4096; i += nc) s += rd[i];
        s = mod_fin(s, n0 + tid);
        if (ph || b < 2) g_mod[n0 + tid] = s;
        if (!ph) {
          mv[(b & 1) * 512 + tid] = s;
          asm volatile("{\n.reg .b32 r;\nmapa.shared::cluster.u32 r,%0,%1;\nst.shared::cluster.f32 [r],%2;\n}" ::"r"(smem_u32(mv + (b & 1) * 512 + tid)), "r"((b & 1) ^ 1), "f"(s) : "memory");
        }
      }
      cluster_sync();
    }
    if (tid < 430) {
      const bf16* w = (b >> 1 ? w3 : w1) + (b & 1) * 688 + tid % 86 * 8;
      float u[8] = {0, 0, 0, 0, 0, 0, 0, 0}, v[8] = {0, 0, 0, 0, 0, 0, 0, 0};
#pragma unroll 13
      for (int r = tid / 86; r < 512; r += 5) { const uint4 x = __ldg((const uint4*)(w + r * 1376)); fma8(u, mv[512 + r], x); fma8(v, mv[r], x); }
      put8(rd + tid * 8, u); put8(rd + 3440 + tid * 8, v);
    }
    __syncthreads();
    for (int n = tid; n < 688; n += 512) {
      float u = 0, v = 0;
      for (int i = n; i < 3440; i += 688) { u += rd[i]; v += rd[3440 + i]; }
      g_uv[(b >> 1) * 1408 + (b & 1) * 688 + n] = make_float2(u, v);
    }
    TS(0, 7);
    return;
  }
  const int bid = blockIdx.x - 4, h = bid >> 2, qb = bid & 3;
  TS(2, 0);
  if (tid == 0) { for (int i = 0; i < 8; i++) { mbar_init(bars + 8 * i, 1); mbar_expect(bars + 8 * i, 16384); } fence_init(); }
#pragma unroll
  for (int i = 0; i < 4; i++) *(uint4*)(smem + 131072 + i * 8192 + tid * 16) = make_uint4(0x3F803F80u, 0x3F803F80u, 0x3F803F80u, 0x3F803F80u);
  fence_async();
  cluster_sync();
  pdl_wait();
  TS(2, 1);
  if (tid >= 448) g_modv[bid * 64 + tid - 448] = 0;
  const uint4 km4 = *(const uint4*)(g_kmax + h * 128 + lane * 4);
  const uint32_t* qp = (const uint32_t*)g_qkv + (h * 2 * 2048 + qb * 512 + warp * 16 + g) * 4 + t;
  uint32_t q[4] = {qp[0], qp[32], qp[8192], qp[8192 + 32]};
  auto ldkv = [&]() {
    const int c = warp >> 1, pl = (qb & 1) + (warp & 1) * 2;
    bulk_load_mc(sK + pl * 32768 + c * 4096, g_qkv + ((64 + (pl >> 1) * 64 + h * 2 + (pl & 1)) * 2048 + c * 256) * 8, 4096, bars + 8 * c);
  };
  if (lane == 0 && warp < 4) ldkv();
  const uint32_t qn[4] = {qp[1024], qp[1024 + 32], qp[1024 + 8192], qp[1024 + 8192 + 32]};
  const float kmax = __uint_as_float(__reduce_max_sync(~0u, max(max(km4.x, km4.y), max(km4.z, km4.w))));
  if (lane == 0 && warp >= 4 && kmax != -1.f) ldkv();
#pragma unroll 1
  for (int tile = 0; tile < 2; tile++) {
    const int row = qb * 512 + tile * 256 + warp * 16 + g;
    const float n0 = qsum(blo(q[0]) * blo(q[0]) + bhi(q[0]) * bhi(q[0]) + blo(q[2]) * blo(q[2]) + bhi(q[2]) * bhi(q[2]));
    const float n1 = qsum(blo(q[1]) * blo(q[1]) + bhi(q[1]) * bhi(q[1]) + blo(q[3]) * blo(q[3]) + bhi(q[3]) * bhi(q[3]));
    const float b0 = sqrtf(n0 * kmax) * 1.001f, b1 = sqrtf(n1 * kmax) * 1.001f;
    const float m0 = fmaxf(ceilf(b0 - 100.f), 0.f), m1 = fmaxf(ceilf(b1 - 100.f), 0.f);
    float o[12], ob[12];
    attn_pass(o, ob, q, m0, m1, sK, bars, tile == 0, kz);
    const float f0 = ex2(-m0), f1 = ex2(-m1);
#pragma unroll
    for (int i = 0; i < 12; i++) o[i] = fmaf(o[i], (i & 2) ? f1 : f0, ob[i]);
    bool ok = b0 < 220.f && b1 < 220.f && o[8] >= 0x1p-90f && o[10] >= 0x1p-90f;
#pragma unroll
    for (int i = 0; i < 12; i++) ok = ok && fabsf(o[i]) < INFINITY;
    if (!__all_sync(~0u, ok)) attn_safe(o, q, sK);
    const float r0 = 1.f / o[8], r1 = 1.f / o[10];
    uint32_t* op = (uint32_t*)g_o + (((row >> 7) * 64 + h * 2) * 128 + (row & 127)) * 4 + t;
    op[0] = pack_rn(o[0] * r0, o[1] * r0); op[32] = pack_rn(o[2] * r1, o[3] * r1);
    op[512] = pack_rn(o[4] * r0, o[5] * r0); op[512 + 32] = pack_rn(o[6] * r1, o[7] * r1);
    if (tile == 0 && tid == 32) {
      l2_prefetch((const char*)wo + bid * 4096, 4096);
      l2_prefetch((const char*)w1 + bid * 11008, 11008);
      l2_prefetch((const char*)w3 + bid * 11008, 11008);
      l2_prefetch((const char*)w2 + bid * 11008, 11008);
    }
#pragma unroll
    for (int i = 0; i < 4; i++) q[i] = qn[i];
    TS(2, 3 + tile);
  }
}

constexpr int WO_SMEM = 131072 + 65536 + 256;
__global__ void __cluster_dims__(2, 1, 1) __launch_bounds__(256, 1) k_wo(const __grid_constant__ CUtensorMap mW, const bf16* __restrict__ x) {
  extern __shared__ __align__(1024) uint8_t smem[];
  const uint32_t sA = smem_u32(smem), sB = sA + 131072, bars = sB + 65536;
  const int tid = threadIdx.x, warp = tid >> 5, lane = tid & 31, g = lane >> 2, t = lane & 3;
  const int rb = blockIdx.x >> 3, ct = blockIdx.x & 7;
  TS(3, 0);
  pdl_launch();
  if (tid == 0) {
    for (int i = 0; i < 8; i++) mbar_init(bars + 8 * i, 1);
    fence_init();
    for (int i = 0; i < 8; i++) { mbar_expect(bars + 8 * i, 24576); tma2d(sB + i * 8192, &mW, ct * 64, i * 64, bars + 8 * i); }
  }
  __syncwarp();
  cluster_arrive();
  const int lrow = warp * 16 + g;
  uint32_t xr[16];
  const uint32_t* xp = (const uint32_t*)(x + (rb * 128 + lrow) * 512 + ct * 64) + t;
#pragma unroll
  for (int j = 0; j < 8; j++) { xr[2 * j] = __ldg(xp + j * 4); xr[2 * j + 1] = __ldg(xp + j * 4 + 8 * 256); }
  cluster_wait();
  pdl_wait();
  if (tid == 0) {
    for (int i = ct & 1; i < 8; i += 2) bulk_load_mc(sA + i * 16384, g_o + (rb * 64 + i * 8) * 1024, 16384, bars + 8 * i);
  }
  TS(3, 1);
  float2 ga[8];
  uint32_t sc[8];
#pragma unroll
  for (int j = 0; j < 8; j++) {
    ga[j] = *(const float2*)(g_mod + 1024 + ct * 64 + j * 8 + t * 2);
    const float2 v = *(const float2*)(g_mod + 2048 + ct * 64 + j * 8 + t * 2);
    sc[j] = pack_rn(v.x, v.y);
  }
  float acc[32];
  const uint64_t da = mk_desc(sA + (warp >> 2) * 1024, 2048, 128, 0), db = mk_desc(sB, 8192, 1024, 1);
#pragma unroll
  for (int c = 0; c < 8; c++) {
    mbar_wait(bars + 8 * c, 0);
    if (c == 0) TS(3, 2);
    wg_fence();
#pragma unroll
    for (int k = 0; k < 4; k++) wgmma_ss_n64_t1(acc, da + (c * 4 + k) * 256, db + (c * 4 + k) * 128, c + k);
    wg_commit();
  }
  wg_wait<0>();
  reg_fence(acc);
  TS(3, 3);
  uint32_t* o = (uint32_t*)g_x1 + ((rb * 64 + ct * 8) * 128 + lrow) * 4 + t;
  uint32_t* oa = (uint32_t*)g_a + ((rb * 64 + ct * 8) * 128 + lrow) * 4 + t;
  float s0 = 0, s1 = 0;
#pragma unroll
  for (int j = 0; j < 8; j++) {
    xr[2 * j] = pack_rn(fmaf(ga[j].x, acc[4 * j], blo(xr[2 * j])), fmaf(ga[j].y, acc[4 * j + 1], bhi(xr[2 * j])));
    xr[2 * j + 1] = pack_rn(fmaf(ga[j].x, acc[4 * j + 2], blo(xr[2 * j + 1])), fmaf(ga[j].y, acc[4 * j + 3], bhi(xr[2 * j + 1])));
    uint32_t a0, a1;
    asm("mul.rn.bf16x2 %0,%1,%2;" : "=r"(a0) : "r"(xr[2 * j]), "r"(sc[j]));
    asm("mul.rn.bf16x2 %0,%1,%2;" : "=r"(a1) : "r"(xr[2 * j + 1]), "r"(sc[j]));
    oa[j * 512] = a0; oa[j * 512 + 32] = a1;
    o[j * 512] = xr[2 * j]; o[j * 512 + 32] = xr[2 * j + 1];
    s0 += blo(xr[2 * j]) + bhi(xr[2 * j]); s1 += blo(xr[2 * j + 1]) + bhi(xr[2 * j + 1]);
  }
  const float m0 = qsum(s0) * (1.f / 64), m1 = qsum(s1) * (1.f / 64);
  float v0 = 0, v1 = 0;
#pragma unroll
  for (int j = 0; j < 8; j++) {
    float d;
    d = blo(xr[2 * j]) - m0; v0 += d * d; d = bhi(xr[2 * j]) - m0; v0 += d * d;
    d = blo(xr[2 * j + 1]) - m1; v1 += d * d; d = bhi(xr[2 * j + 1]) - m1; v1 += d * d;
  }
  v0 = qsum(v0); v1 = qsum(v1);
  if (t == 0) g_st[(rb * 128 + lrow) * 8 + ct] = make_float2(m0, v0);
  if (t == 1) g_st[(rb * 128 + lrow + 8) * 8 + ct] = make_float2(m1, v1);
  TS(3, 4);
}

constexpr int W2_SMEM = 6 * 32768 + 32768 + 256;
__global__ void __cluster_dims__(2, 1, 1) __launch_bounds__(288, 1) k_w2(const __grid_constant__ CUtensorMap mW, bf16* __restrict__ out) {
  extern __shared__ __align__(1024) uint8_t smem[];
  const uint32_t sR = smem_u32(smem), sX = sR + 6 * 32768, bF = sX + 32768, bE = bF + 48, bX = bF + 96;
  const int tid = threadIdx.x, warp = tid >> 5, lane = tid & 31, g = lane >> 2, t = lane & 3;
  const int kh = blockIdx.x & 1, ct = (blockIdx.x >> 1) & 3, rb = blockIdx.x >> 3;
  TS(5, 0);
  pdl_launch();
  if (tid == 256) {
    for (int i = 0; i < 6; i++) { mbar_init(bF + 8 * i, 1); mbar_init(bE + 8 * i, 8); }
    for (int i = 0; i < 8; i++) { mbar_init(bX + 8 * i, 1); mbar_expect(bX + 8 * i, 4096); }
    fence_init();
  }
  __syncthreads();
  asm volatile("barrier.cluster.arrive.relaxed.aligned;" ::: "memory");
  if (warp == 8) {
    if (lane == 0) {
      auto abytes = [&](int s) { return (kh == 1 && s == 10) ? 8192 : 16384; };
      auto loadB = [&](int s) {
        const int st = s % 6;
        mbar_expect(bF + 8 * st, 16384 + abytes(s));
        for (int j = 0; j < 2; j++) tma2d(sR + st * 32768 + 16384 + j * 8192, &mW, ct * 128 + j * 64, kh * 704 + s * 64, bF + 8 * st);
      };
      auto loadA = [&](int s) { bulk_load(sR + (s % 6) * 32768, g_h + (rb * 172 + kh * 88 + s * 8) * 1024, abytes(s), bF + 8 * (s % 6)); };
      for (int s = 0; s < 6; s++) loadB(s);
      pdl_wait();
      for (int s = 0; s < 6; s++) loadA(s);
      for (int s = 6; s < 11; s++) { mbar_wait(bE + 8 * (s - 6), 0); loadB(s); loadA(s); }
    }
    __syncwarp();
    cluster_wait();
    return;
  }
  pdl_wait();
  TS(5, 1);
  const int lrow = warp * 16 + g;
  uint32_t xr[16];
  float2 gb[8];
  const uint32_t* xp = (const uint32_t*)g_x1 + ((rb * 64 + ct * 16 + kh * 8) * 128 + lrow) * 4 + t;
#pragma unroll
  for (int j = 0; j < 8; j++) {
    xr[2 * j] = xp[j * 512]; xr[2 * j + 1] = xp[j * 512 + 32];
    gb[j] = *(const float2*)(g_mod + 2560 + ct * 128 + kh * 64 + j * 8 + t * 2);
  }
  float acc[64];
#pragma unroll 1
  for (int s = 0; s < 11; s++) {
    const int st = s % 6;
    mbar_wait(bF + 8 * st, s >= 6);
    const uint64_t da = mk_desc(sR + st * 32768 + (warp >> 2) * 1024, 2048, 128, 0), db = mk_desc(sR + st * 32768 + 16384, 8192, 1024, 1);
    if (s == 0) TS(5, 2);
    wg_fence();
    wgmma_ss_n128_t1(acc, da, db, s);
    wgmma_ss_n128_t1(acc, da + 256, db + 128, 1);
    wgmma_ss_n128_t1(acc, da + 512, db + 256, 1);
    wgmma_ss_n128_t1(acc, da + 768, db + 384, 1);
    wg_commit();
    wg_wait<1>();
    if (s > 0 && s < 6 && lane == 0) mbar_arrive(bE + 8 * (s - 1));
  }
  wg_wait<0>();
  reg_fence(acc);
  TS(5, 3);
  asm volatile("barrier.cluster.wait.aligned;" ::: "memory");
  uint32_t rem, rbar;
  asm("mapa.shared::cluster.u32 %0,%1,%2;" : "=r"(rbar) : "r"(bX + warp * 8), "r"(kh ^ 1));
  asm("mapa.shared::cluster.u32 %0,%1,%2;" : "=r"(rem) : "r"(sX + warp * 4096 + lane * 16), "r"(kh ^ 1));
#pragma unroll
  for (int j = 0; j < 8; j++) {
    float v[4];
#pragma unroll
    for (int i = 0; i < 4; i++) { v[i] = kh ? acc[4 * j + i] : acc[32 + 4 * j + i]; acc[4 * j + i] = kh ? acc[32 + 4 * j + i] : acc[4 * j + i]; }
    asm volatile("st.async.weak.shared::cluster.mbarrier::complete_tx::bytes.v4.f32 [%0],{%1,%2,%3,%4},[%5];" ::"r"(rem + j * 512), "f"(v[0]), "f"(v[1]), "f"(v[2]), "f"(v[3]), "r"(rbar) : "memory");
  }
  mbar_wait(bX + warp * 8, 0);
  TS(5, 5);
  const uint32_t sw = sX + warp * 4096;
#pragma unroll
  for (int j = 0; j < 8; j++) {
    const float4 p = *(const float4*)(smem + 6 * 32768 + warp * 4096 + j * 512 + lane * 16);
    xr[2 * j] = pack_rn(fmaf(gb[j].x, acc[4 * j] + p.x, blo(xr[2 * j])), fmaf(gb[j].y, acc[4 * j + 1] + p.y, bhi(xr[2 * j])));
    xr[2 * j + 1] = pack_rn(fmaf(gb[j].x, acc[4 * j + 2] + p.z, blo(xr[2 * j + 1])), fmaf(gb[j].y, acc[4 * j + 3] + p.w, bhi(xr[2 * j + 1])));
  }
  __syncwarp();
#pragma unroll
  for (int j = 1; j < 8; j += 2) {
    asm volatile("stmatrix.sync.aligned.m8n8.x4.shared.b16 [%0],{%1,%2,%3,%4};" ::"r"(sw + (lane & 15) * 128 + (((j - 1 + (lane >> 4)) ^ (lane & 7)) << 4)),
                            "r"(xr[2 * j - 2]), "r"(xr[2 * j - 1]), "r"(xr[2 * j]), "r"(xr[2 * j + 1]) : "memory");
  }
  __syncwarp();
#pragma unroll
  for (int i = 0; i < 4; i++) {
    const int r = i * 4 + (lane >> 3);
    *(uint4*)(out + (rb * 128 + warp * 16 + r) * 512 + ct * 128 + kh * 64 + (lane & 7) * 8) = *(const uint4*)(smem + 6 * 32768 + warp * 4096 + r * 128 + (((lane ^ r) & 7) << 4));
  }
  TS(5, 4);
}

typedef CUresult (*EncFn)(CUtensorMap*, CUtensorMapDataType, cuuint32_t, void*, const cuuint64_t*, const cuuint64_t*, const cuuint32_t*,
                          const cuuint32_t*, CUtensorMapInterleave, CUtensorMapSwizzle, CUtensorMapL2promotion, CUtensorMapFloatOOBfill);
static void mk_map(EncFn f, CUtensorMap* m, const void* p, int rows, int cols, int box_rows) {
  cuuint64_t dim[2] = {(cuuint64_t)cols, (cuuint64_t)rows}, str[1] = {(cuuint64_t)cols * 2};
  cuuint32_t box[2] = {64, (cuuint32_t)box_rows}, es[2] = {1, 1};
  f(m, CU_TENSOR_MAP_DATA_TYPE_BFLOAT16, 2, (void*)p, dim, str, box, es, CU_TENSOR_MAP_INTERLEAVE_NONE, CU_TENSOR_MAP_SWIZZLE_128B,
    CU_TENSOR_MAP_L2_PROMOTION_L2_128B, CU_TENSOR_MAP_FLOAT_OOB_FILL_NONE);
}
template <typename... KA, typename... A>
static void launch(void (*k)(KA...), int grid, int block, int smem, bool pdl, A... args) {
  cudaLaunchConfig_t cfg = {};
  cfg.gridDim = dim3(grid); cfg.blockDim = dim3(block); cfg.dynamicSmemBytes = smem; cfg.stream = cudaStreamPerThread;
  cudaLaunchAttribute at[1];
  at[0].id = cudaLaunchAttributeProgrammaticStreamSerialization; at[0].val.programmaticStreamSerializationAllowed = 1;
  cfg.attrs = at; cfg.numAttrs = pdl ? 1 : 0;
  cudaLaunchKernelEx(&cfg, k, args...);
}
extern "C" void kernel_launch(void* const* d_in, const int* in_sizes, int n_in, void* d_out, int out_size) {
  const bf16 *x = (const bf16*)d_in[0], *wqkv = (const bf16*)d_in[1], *wo = (const bf16*)d_in[2], *w1 = (const bf16*)d_in[4],
             *w3 = (const bf16*)d_in[5], *w2 = (const bf16*)d_in[6], *c = (const bf16*)d_in[7], *wmod = (const bf16*)d_in[8];
  void* fp = nullptr;
  cudaDriverEntryPointQueryResult qr;
  cudaGetDriverEntryPoint("cuTensorMapEncodeTiled", &fp, cudaEnableDefault, &qr);
  EncFn f = (EncFn)fp;
  CUtensorMap mX, mQ, mO, m1, m3, m2;
  mk_map(f, &mX, x, S_, D_, 128); mk_map(f, &mQ, wqkv, D_, 3 * D_, 64); mk_map(f, &mO, wo, D_, D_, 64);
  mk_map(f, &m1, w1, D_, F_, 32); mk_map(f, &m3, w3, D_, F_, 32); mk_map(f, &m2, w2, F_, D_, 64);
  cudaFuncSetAttribute(k_lngemm<false>, cudaFuncAttributeMaxDynamicSharedMemorySize, LN_SMEM);
  cudaFuncSetAttribute(k_lngemm<true>, cudaFuncAttributeMaxDynamicSharedMemorySize, LN_SMEM);
  cudaFuncSetAttribute(k_attn, cudaFuncAttributeMaxDynamicSharedMemorySize, AT_SMEM);
  cudaFuncSetAttribute(k_wo, cudaFuncAttributeMaxDynamicSharedMemorySize, WO_SMEM);
  cudaFuncSetAttribute(k_w2, cudaFuncAttributeMaxDynamicSharedMemorySize, W2_SMEM);
  launch(k_lngemm<false>, 128, 384, LN_SMEM, false, mX, mQ, mQ, c, wmod, x, wqkv);
  launch(k_attn, 132, 512, AT_SMEM, true, wo, w1, w3, w2, c, wmod, 0u);
  launch(k_wo, 128, 256, WO_SMEM, true, mO, x);
  launch(k_lngemm<true>, 128, 384, LN_SMEM, true, mX, m1, m3, c, wmod, x, wqkv);
  launch(k_w2, 128, 288, W2_SMEM, true, m2, (bf16*)d_out);
}
```

```cpp
#include <cuda_runtime.h>
#include <cuda_bf16.h>
#include <cuda.h>
#include <stdint.h>
typedef __nv_bfloat16 bf16;
constexpr int S_ = 2048, D_ = 512, F_ = 1376;
__device__ __align__(1024) float g_mod[3072];
__device__ __align__(1024) uint32_t g_modv[4096 + 4096];
__device__ __align__(1024) bf16 g_qkv[192 * 2048 * 8];
__device__ __align__(1024) float g_kmax[32 * 128];
__device__ __align__(1024) bf16 g_o[16 * 64 * 128 * 8];
__device__ __align__(1024) bf16 g_x1[16 * 64 * 128 * 8];
__device__ __align__(1024) bf16 g_a[16 * 64 * 128 * 8];
__device__ __align__(1024) float2 g_uv[2 * 1408];
__device__ __align__(1024) float2 g_st[2048 * 8];
__device__ __align__(1024) bf16 g_h[16 * 172 * 128 * 8];

__device__ __forceinline__ uint32_t smem_u32(const void* p) { return (uint32_t)__cvta_generic_to_shared(p); }
__device__ __forceinline__ void mbar_init(uint32_t b, int n) { asm volatile("mbarrier.init.shared::cta.b64 [%0],%1;" ::"r"(b), "r"(n) : "memory"); }
__device__ __forceinline__ void mbar_expect(uint32_t b, int bytes) { asm volatile("mbarrier.arrive.expect_tx.shared::cta.b64 _,[%0],%1;" ::"r"(b), "r"(bytes) : "memory"); }
__device__ __forceinline__ void mbar_arrive(uint32_t b) { asm volatile("mbarrier.arrive.shared::cta.b64 _,[%0];" ::"r"(b) : "memory"); }
__device__ __forceinline__ void mbar_wait(uint32_t b, int parity) {
  asm volatile("{\n.reg .pred p;\n.reg .u32 n;\nmov.u32 n,0;\nLW:\nmbarrier.try_wait.parity.shared::cta.b64 p,[%0],%1;\n@p bra LD;\n"
               "add.u32 n,n,1;\nsetp.lt.u32 p,n,4194304;\n@p bra LW;\nLD:\n}\n" ::"r"(b), "r"(parity) : "memory");
}
__device__ __forceinline__ void fence_init() { asm volatile("fence.mbarrier_init.release.cluster;" ::: "memory"); }
__device__ __forceinline__ void fence_async() { asm volatile("fence.proxy.async.shared::cta;" ::: "memory"); }
__device__ __forceinline__ void bulk_load(uint32_t dst, const void* src, int bytes, uint32_t bar) {
  asm volatile("cp.async.bulk.shared::cluster.global.mbarrier::complete_tx::bytes [%0],[%1],%2,[%3];" ::"r"(dst), "l"(src), "r"(bytes), "r"(bar) : "memory");
}
__device__ __forceinline__ void tma2d(uint32_t dst, const CUtensorMap* m, int c0, int c1, uint32_t bar) {
  asm volatile("cp.async.bulk.tensor.2d.shared::cluster.global.mbarrier::complete_tx::bytes [%0],[%1,{%3,%4}],[%2];" ::"r"(dst), "l"(m), "r"(bar), "r"(c0), "r"(c1) : "memory");
}
__device__ __forceinline__ void bulk_load_mc(uint32_t dst, const void* src, int bytes, uint32_t bar) {
  asm volatile("cp.async.bulk.shared::cluster.global.mbarrier::complete_tx::bytes.multicast::cluster [%0],[%1],%2,[%3],%4;" ::"r"(dst), "l"(src), "r"(bytes), "r"(bar), "h"((uint16_t)3) : "memory");
}
__device__ __forceinline__ void tma2d_mc(uint32_t dst, const CUtensorMap* m, int c0, int c1, uint32_t bar) {
  asm volatile("cp.async.bulk.tensor.2d.shared::cluster.global.mbarrier::complete_tx::bytes.multicast::cluster [%0],[%1,{%3,%4}],[%2],%5;" ::"r"(dst), "l"(m), "r"(bar), "r"(c0), "r"(c1), "h"((uint16_t)3) : "memory");
}
__device__ __forceinline__ void cluster_arrive() { asm volatile("barrier.cluster.arrive.relaxed.aligned;" ::: "memory"); }
__device__ __forceinline__ void cluster_wait() { asm volatile("barrier.cluster.wait.aligned;" ::: "memory"); }
__device__ __forceinline__ void cluster_sync() { asm volatile("barrier.cluster.arrive.release.aligned;\nbarrier.cluster.wait.acquire.aligned;" ::: "memory"); }
__device__ __forceinline__ bool mbar_test(uint32_t b, uint32_t ph) {
  uint32_t ok; asm volatile("{\n.reg .pred p;\nmbarrier.test_wait.parity.shared::cta.b64 p,[%1],%2;\nselp.u32 %0,1,0,p;\n}" : "=r"(ok) : "r"(b), "r"(ph) : "memory"); return ok;
}
__device__ __forceinline__ bool may_preload(uint32_t landed, uint32_t go) {
  for (int i = 0; i < 100000; i++) { if (mbar_test(go, 0)) return false; if (mbar_test(landed, 0)) return true; }
  return false;
}
#define PD1 2
#define PD2 2
__device__ __forceinline__ void l2_prefetch(const void* p, int bytes) { asm volatile("cp.async.bulk.prefetch.L2.global [%0],%1;" ::"l"(p), "r"(bytes) : "memory"); }
__device__ __forceinline__ void pdl_launch() { asm volatile("griddepcontrol.launch_dependents;" ::: "memory"); }
__device__ __forceinline__ void pdl_wait() { asm volatile("griddepcontrol.wait;" ::: "memory"); }
__device__ __forceinline__ void wg_fence() { asm volatile("wgmma.fence.sync.aligned;" ::: "memory"); }
__device__ __forceinline__ void wg_commit() { asm volatile("wgmma.commit_group.sync.aligned;" ::: "memory"); }
template <int N> __device__ __forceinline__ void wg_wait() { asm volatile("wgmma.wait_group.sync.aligned %0;" ::"n"(N) : "memory"); }
template <int N> __device__ __forceinline__ void reg_fence(float (&d)[N]) {
#pragma unroll
  for (int i = 0; i < N; i++) asm volatile("" : "+f"(d[i])::"memory");
}
template <int N> __device__ __forceinline__ void zero(float (&d)[N]) {
#pragma unroll
  for (int i = 0; i < N; i++) d[i] = 0.f;
  reg_fence(d);
}
__device__ __forceinline__ uint64_t mk_desc(uint32_t addr, uint32_t lbo, uint32_t sbo, uint32_t mode) {
  return (uint64_t)((addr >> 4) & 0x3FFF) | ((uint64_t)(lbo >> 4) << 16) | ((uint64_t)(sbo >> 4) << 32) | ((uint64_t)mode << 62);
}
__device__ __forceinline__ void ldsm4(uint32_t a, uint32_t (&r)[4]) {
  asm volatile("ldmatrix.sync.aligned.m8n8.x4.shared.b16 {%0,%1,%2,%3},[%4];" : "=r"(r[0]), "=r"(r[1]), "=r"(r[2]), "=r"(r[3]) : "r"(a) : "memory");
}
__device__ __forceinline__ uint32_t pack_rn(float lo, float hi) { uint32_t r; asm("cvt.rn.bf16x2.f32 %0,%1,%2;" : "=r"(r) : "f"(hi), "f"(lo)); return r; }
__device__ __forceinline__ uint32_t pack_rz(float lo, float hi) { uint32_t r; asm("cvt.rz.bf16x2.f32 %0,%1,%2;" : "=r"(r) : "f"(hi), "f"(lo)); return r; }
__device__ __forceinline__ float blo(uint32_t u) { return __uint_as_float(u << 16); }
__device__ __forceinline__ float bhi(uint32_t u) { return __uint_as_float(u & 0xFFFF0000u); }
__device__ __forceinline__ float rbf(float x) { return __bfloat162float(__float2bfloat16_rn(x)); }
__device__ __forceinline__ float qsum(float v) { v += __shfl_xor_sync(~0u, v, 1); return v + __shfl_xor_sync(~0u, v, 2); }
__device__ __forceinline__ float ex2(float x) { float r; asm("ex2.approx.ftz.f32 %0,%1;" : "=f"(r) : "f"(x)); return r; }
#define TS(k, i)
__device__ __forceinline__ void wgmma_rs_n176_t1(float (&d)[88],uint32_t a0,uint32_t a1,uint32_t a2,uint32_t a3,uint64_t db,int sc){
  asm volatile("{\n.reg .pred p;\nsetp.ne.b32 p,%93,0;\n"
    "wgmma.mma_async.sync.aligned.m64n176k16.f32.bf16.bf16 {%0,%1,%2,%3,%4,%5,%6,%7,%8,%9,%10,%11,%12,%13,%14,%15,%16,%17,%18,%19,%20,%21,%22,%23,%24,%25,%26,%27,%28,%29,%30,%31,%32,%33,%34,%35,%36,%37,%38,%39,%40,%41,%42,%43,%44,%45,%46,%47,%48,%49,%50,%51,%52,%53,%54,%55,%56,%57,%58,%59,%60,%61,%62,%63,%64,%65,%66,%67,%68,%69,%70,%71,%72,%73,%74,%75,%76,%77,%78,%79,%80,%81,%82,%83,%84,%85,%86,%87},{%88,%89,%90,%91},%92,p,1,1,1;\n}\n"
    :"+f"(d[0]),"+f"(d[1]),"+f"(d[2]),"+f"(d[3]),"+f"(d[4]),"+f"(d[5]),"+f"(d[6]),"+f"(d[7]),"+f"(d[8]),"+f"(d[9]),"+f"(d[10]),"+f"(d[11]),"+f"(d[12]),"+f"(d[13]),"+f"(d[14]),"+f"(d[15]),"+f"(d[16]),"+f"(d[17]),"+f"(d[18]),"+f"(d[19]),"+f"(d[20]),"+f"(d[21]),"+f"(d[22]),"+f"(d[23]),"+f"(d[24]),"+f"(d[25]),"+f"(d[26]),"+f"(d[27]),"+f"(d[28]),"+f"(d[29]),"+f"(d[30]),"+f"(d[31]),"+f"(d[32]),"+f"(d[33]),"+f"(d[34]),"+f"(d[35]),"+f"(d[36]),"+f"(d[37]),"+f"(d[38]),"+f"(d[39]),"+f"(d[40]),"+f"(d[41]),"+f"(d[42]),"+f"(d[43]),"+f"(d[44]),"+f"(d[45]),"+f"(d[46]),"+f"(d[47]),"+f"(d[48]),"+f"(d[49]),"+f"(d[50]),"+f"(d[51]),"+f"(d[52]),"+f"(d[53]),"+f"(d[54]),"+f"(d[55]),"+f"(d[56]),"+f"(d[57]),"+f"(d[58]),"+f"(d[59]),"+f"(d[60]),"+f"(d[61]),"+f"(d[62]),"+f"(d[63]),"+f"(d[64]),"+f"(d[65]),"+f"(d[66]),"+f"(d[67]),"+f"(d[68]),"+f"(d[69]),"+f"(d[70]),"+f"(d[71]),"+f"(d[72]),"+f"(d[73]),"+f"(d[74]),"+f"(d[75]),"+f"(d[76]),"+f"(d[77]),"+f"(d[78]),"+f"(d[79]),"+f"(d[80]),"+f"(d[81]),"+f"(d[82]),"+f"(d[83]),"+f"(d[84]),"+f"(d[85]),"+f"(d[86]),"+f"(d[87])
    :"r"(a0),"r"(a1),"r"(a2),"r"(a3),"l"(db),"r"(sc));
}
__device__ __forceinline__ void wgmma_rs_n192_t1(float (&d)[96],uint32_t a0,uint32_t a1,uint32_t a2,uint32_t a3,uint64_t db,int sc){
  asm volatile("{\n.reg .pred p;\nsetp.ne.b32 p,%101,0;\n"
    "wgmma.mma_async.sync.aligned.m64n192k16.f32.bf16.bf16 {%0,%1,%2,%3,%4,%5,%6,%7,%8,%9,%10,%11,%12,%13,%14,%15,%16,%17,%18,%19,%20,%21,%22,%23,%24,%25,%26,%27,%28,%29,%30,%31,%32,%33,%34,%35,%36,%37,%38,%39,%40,%41,%42,%43,%44,%45,%46,%47,%48,%49,%50,%51,%52,%53,%54,%55,%56,%57,%58,%59,%60,%61,%62,%63,%64,%65,%66,%67,%68,%69,%70,%71,%72,%73,%74,%75,%76,%77,%78,%79,%80,%81,%82,%83,%84,%85,%86,%87,%88,%89,%90,%91,%92,%93,%94,%95},{%96,%97,%98,%99},%100,p,1,1,1;\n}\n"
    :"+f"(d[0]),"+f"(d[1]),"+f"(d[2]),"+f"(d[3]),"+f"(d[4]),"+f"(d[5]),"+f"(d[6]),"+f"(d[7]),"+f"(d[8]),"+f"(d[9]),"+f"(d[10]),"+f"(d[11]),"+f"(d[12]),"+f"(d[13]),"+f"(d[14]),"+f"(d[15]),"+f"(d[16]),"+f"(d[17]),"+f"(d[18]),"+f"(d[19]),"+f"(d[20]),"+f"(d[21]),"+f"(d[22]),"+f"(d[23]),"+f"(d[24]),"+f"(d[25]),"+f"(d[26]),"+f"(d[27]),"+f"(d[28]),"+f"(d[29]),"+f"(d[30]),"+f"(d[31]),"+f"(d[32]),"+f"(d[33]),"+f"(d[34]),"+f"(d[35]),"+f"(d[36]),"+f"(d[37]),"+f"(d[38]),"+f"(d[39]),"+f"(d[40]),"+f"(d[41]),"+f"(d[42]),"+f"(d[43]),"+f"(d[44]),"+f"(d[45]),"+f"(d[46]),"+f"(d[47]),"+f"(d[48]),"+f"(d[49]),"+f"(d[50]),"+f"(d[51]),"+f"(d[52]),"+f"(d[53]),"+f"(d[54]),"+f"(d[55]),"+f"(d[56]),"+f"(d[57]),"+f"(d[58]),"+f"(d[59]),"+f"(d[60]),"+f"(d[61]),"+f"(d[62]),"+f"(d[63]),"+f"(d[64]),"+f"(d[65]),"+f"(d[66]),"+f"(d[67]),"+f"(d[68]),"+f"(d[69]),"+f"(d[70]),"+f"(d[71]),"+f"(d[72]),"+f"(d[73]),"+f"(d[74]),"+f"(d[75]),"+f"(d[76]),"+f"(d[77]),"+f"(d[78]),"+f"(d[79]),"+f"(d[80]),"+f"(d[81]),"+f"(d[82]),"+f"(d[83]),"+f"(d[84]),"+f"(d[85]),"+f"(d[86]),"+f"(d[87]),"+f"(d[88]),"+f"(d[89]),"+f"(d[90]),"+f"(d[91]),"+f"(d[92]),"+f"(d[93]),"+f"(d[94]),"+f"(d[95])
    :"r"(a0),"r"(a1),"r"(a2),"r"(a3),"l"(db),"r"(sc));
}
__device__ __forceinline__ void wgmma_rs_n24_t1(float (&d)[12],uint32_t a0,uint32_t a1,uint32_t a2,uint32_t a3,uint64_t db,int sc){
  asm volatile("{\n.reg .pred p;\nsetp.ne.b32 p,%17,0;\n"
    "wgmma.mma_async.sync.aligned.m64n24k16.f32.bf16.bf16 {%0,%1,%2,%3,%4,%5,%6,%7,%8,%9,%10,%11},{%12,%13,%14,%15},%16,p,1,1,1;\n}\n"
    :"+f"(d[0]),"+f"(d[1]),"+f"(d[2]),"+f"(d[3]),"+f"(d[4]),"+f"(d[5]),"+f"(d[6]),"+f"(d[7]),"+f"(d[8]),"+f"(d[9]),"+f"(d[10]),"+f"(d[11])
    :"r"(a0),"r"(a1),"r"(a2),"r"(a3),"l"(db),"r"(sc));
}
__device__ __forceinline__ void wgmma_rs_n64_t0(float (&d)[32],uint32_t a0,uint32_t a1,uint32_t a2,uint32_t a3,uint64_t db,int sc){
  asm volatile("{\n.reg .pred p;\nsetp.ne.b32 p,%37,0;\n"
    "wgmma.mma_async.sync.aligned.m64n64k16.f32.bf16.bf16 {%0,%1,%2,%3,%4,%5,%6,%7,%8,%9,%10,%11,%12,%13,%14,%15,%16,%17,%18,%19,%20,%21,%22,%23,%24,%25,%26,%27,%28,%29,%30,%31},{%32,%33,%34,%35},%36,p,1,1,0;\n}\n"
    :"+f"(d[0]),"+f"(d[1]),"+f"(d[2]),"+f"(d[3]),"+f"(d[4]),"+f"(d[5]),"+f"(d[6]),"+f"(d[7]),"+f"(d[8]),"+f"(d[9]),"+f"(d[10]),"+f"(d[11]),"+f"(d[12]),"+f"(d[13]),"+f"(d[14]),"+f"(d[15]),"+f"(d[16]),"+f"(d[17]),"+f"(d[18]),"+f"(d[19]),"+f"(d[20]),"+f"(d[21]),"+f"(d[22]),"+f"(d[23]),"+f"(d[24]),"+f"(d[25]),"+f"(d[26]),"+f"(d[27]),"+f"(d[28]),"+f"(d[29]),"+f"(d[30]),"+f"(d[31])
    :"r"(a0),"r"(a1),"r"(a2),"r"(a3),"l"(db),"r"(sc));
}
__device__ __forceinline__ void wgmma_ss_n128_t1(float (&d)[64],uint64_t da,uint64_t db,int sc){
  asm volatile("{\n.reg .pred p;\nsetp.ne.b32 p,%66,0;\n"
    "wgmma.mma_async.sync.aligned.m64n128k16.f32.bf16.bf16 {%0,%1,%2,%3,%4,%5,%6,%7,%8,%9,%10,%11,%12,%13,%14,%15,%16,%17,%18,%19,%20,%21,%22,%23,%24,%25,%26,%27,%28,%29,%30,%31,%32,%33,%34,%35,%36,%37,%38,%39,%40,%41,%42,%43,%44,%45,%46,%47,%48,%49,%50,%51,%52,%53,%54,%55,%56,%57,%58,%59,%60,%61,%62,%63},%64,%65,p,1,1,0,1;\n}\n"
    :"+f"(d[0]),"+f"(d[1]),"+f"(d[2]),"+f"(d[3]),"+f"(d[4]),"+f"(d[5]),"+f"(d[6]),"+f"(d[7]),"+f"(d[8]),"+f"(d[9]),"+f"(d[10]),"+f"(d[11]),"+f"(d[12]),"+f"(d[13]),"+f"(d[14]),"+f"(d[15]),"+f"(d[16]),"+f"(d[17]),"+f"(d[18]),"+f"(d[19]),"+f"(d[20]),"+f"(d[21]),"+f"(d[22]),"+f"(d[23]),"+f"(d[24]),"+f"(d[25]),"+f"(d[26]),"+f"(d[27]),"+f"(d[28]),"+f"(d[29]),"+f"(d[30]),"+f"(d[31]),"+f"(d[32]),"+f"(d[33]),"+f"(d[34]),"+f"(d[35]),"+f"(d[36]),"+f"(d[37]),"+f"(d[38]),"+f"(d[39]),"+f"(d[40]),"+f"(d[41]),"+f"(d[42]),"+f"(d[43]),"+f"(d[44]),"+f"(d[45]),"+f"(d[46]),"+f"(d[47]),"+f"(d[48]),"+f"(d[49]),"+f"(d[50]),"+f"(d[51]),"+f"(d[52]),"+f"(d[53]),"+f"(d[54]),"+f"(d[55]),"+f"(d[56]),"+f"(d[57]),"+f"(d[58]),"+f"(d[59]),"+f"(d[60]),"+f"(d[61]),"+f"(d[62]),"+f"(d[63])
    :"l"(da),"l"(db),"r"(sc));
}
__device__ __forceinline__ void wgmma_ss_n64_t1(float (&d)[32],uint64_t da,uint64_t db,int sc){
  asm volatile("{\n.reg .pred p;\nsetp.ne.b32 p,%34,0;\n"
    "wgmma.mma_async.sync.aligned.m64n64k16.f32.bf16.bf16 {%0,%1,%2,%3,%4,%5,%6,%7,%8,%9,%10,%11,%12,%13,%14,%15,%16,%17,%18,%19,%20,%21,%22,%23,%24,%25,%26,%27,%28,%29,%30,%31},%32,%33,p,1,1,0,1;\n}\n"
    :"+f"(d[0]),"+f"(d[1]),"+f"(d[2]),"+f"(d[3]),"+f"(d[4]),"+f"(d[5]),"+f"(d[6]),"+f"(d[7]),"+f"(d[8]),"+f"(d[9]),"+f"(d[10]),"+f"(d[11]),"+f"(d[12]),"+f"(d[13]),"+f"(d[14]),"+f"(d[15]),"+f"(d[16]),"+f"(d[17]),"+f"(d[18]),"+f"(d[19]),"+f"(d[20]),"+f"(d[21]),"+f"(d[22]),"+f"(d[23]),"+f"(d[24]),"+f"(d[25]),"+f"(d[26]),"+f"(d[27]),"+f"(d[28]),"+f"(d[29]),"+f"(d[30]),"+f"(d[31])
    :"l"(da),"l"(db),"r"(sc));
}

__device__ __forceinline__ float silu_bf(bf16 c) { const float x = __bfloat162float(c); return rbf(x / (1.f + __expf(-x))); }
__device__ __forceinline__ void fma8(float (&a)[8], float s, const uint4& v) {
  a[0] += s * blo(v.x); a[1] += s * bhi(v.x); a[2] += s * blo(v.y); a[3] += s * bhi(v.y);
  a[4] += s * blo(v.z); a[5] += s * bhi(v.z); a[6] += s * blo(v.w); a[7] += s * bhi(v.w);
}
__device__ __forceinline__ float red8(float (&a)[8], int lane) {
#pragma unroll
  for (int w = 4; w >= 1; w >>= 1) {
    const bool up = lane & (w * 4);
#pragma unroll
    for (int j = 0; j < w; j++) a[j] = (up ? a[j + w] : a[j]) + __shfl_xor_sync(~0u, up ? a[j] : a[j + w], w * 4);
  }
  return a[0];
}
__device__ __forceinline__ float mod_fin(float s, int n) { s = rbf(s); return ((n >> 9) == 1 || (n >> 9) == 4) ? rbf(1.f + s) : s; }
__device__ __forceinline__ void poll(uint2& a, uint2& b, float (&w)[16], const uint32_t* p, const uint32_t* q) {
  asm volatile("{\n.reg .pred p;\n.reg .b32 n,t,u;\nmov.u32 n,0;\nLW:\nld.relaxed.gpu.global.v2.u32 {%0,%1},[%20];\nld.relaxed.gpu.global.v2.u32 {%2,%3},[%20+64];\n"
               "ld.relaxed.gpu.global.v4.f32 {%4,%5,%6,%7},[%21];\nld.relaxed.gpu.global.v4.f32 {%8,%9,%10,%11},[%21+16];\n"
               "ld.relaxed.gpu.global.v4.f32 {%12,%13,%14,%15},[%21+8192];\nld.relaxed.gpu.global.v4.f32 {%16,%17,%18,%19},[%21+8208];\n"
               "lop3.b32 t,%0,%1,%2,0x80;\nlop3.b32 u,%3,%4,%5,0x80;\nlop3.b32 t,t,%6,%7,0x80;\nlop3.b32 u,u,%8,%9,0x80;\nlop3.b32 t,t,%10,%11,0x80;\n"
               "lop3.b32 u,u,%12,%13,0x80;\nlop3.b32 t,t,%14,%15,0x80;\nlop3.b32 u,u,%16,%17,0x80;\nlop3.b32 t,t,%18,%19,0x80;\nlop3.b32 t,t,u,1,0x80;\n"
               "setp.ne.u32 p,t,0;\n@p bra LD;\nadd.u32 n,n,1;\nsetp.lt.u32 p,n,1048576;\n@p bra LW;\nLD:\n}\n"
               : "=&r"(a.x), "=&r"(a.y), "=&r"(b.x), "=&r"(b.y), "=&f"(w[0]), "=&f"(w[1]), "=&f"(w[2]), "=&f"(w[3]), "=&f"(w[4]), "=&f"(w[5]), "=&f"(w[6]), "=&f"(w[7]),
                 "=&f"(w[8]), "=&f"(w[9]), "=&f"(w[10]), "=&f"(w[11]), "=&f"(w[12]), "=&f"(w[13]), "=&f"(w[14]), "=&f"(w[15]) : "l"(p), "l"(q) : "memory");
}

constexpr int LN_SMEM = 131072 + 4 * 24576 + 2816 + 256;
#define TANH 1
#define DLY 2
template <bool FFN>
__global__ void __cluster_dims__(2, 1, 1) __launch_bounds__(384, 1) k_lngemm(const __grid_constant__ CUtensorMap mX, const __grid_constant__ CUtensorMap mB0,
                                                   const __grid_constant__ CUtensorMap mB1, const bf16* __restrict__ cv, const bf16* __restrict__ wm, const bf16* __restrict__ xg, const bf16* wq) {
  extern __shared__ __align__(1024) uint8_t smem[];
  const uint32_t sA = smem_u32(smem), sB = sA + (FFN ? 81920 : 131072), sM = sA + 229376, bars = sM + 2816;
  const uint32_t bA = bars, bF = bars + 64, bE = bars + 112;
  constexpr int NB = FFN ? 6 : 4;
  const int tid = threadIdx.x, warp = tid >> 5, lane = tid & 31;
  const int pr = blockIdx.x & 1, rb = FFN ? (blockIdx.x >> 4) * 2 + pr : blockIdx.x >> 3, ct = FFN ? (blockIdx.x >> 1) & 7 : blockIdx.x & 7;
  constexpr int NST = FFN ? 16 : 8, KS = FFN ? 2 : 4, BOX = FFN ? 4096 : 8192;
  TS(FFN ? 4 : 1, 0);
  pdl_launch();
  float* red = (float*)(smem + (sM - sA));
  if (tid == 256) {
    for (int i = 0; i < 8; i++) mbar_init(bA + 8 * i, 1);
    for (int i = 0; i < NB; i++) { mbar_init(bF + 8 * i, 1); mbar_init(bE + 8 * i, FFN ? 16 : 8); }
    mbar_init(bars + 160, 1);
    fence_init();
  }
  __syncwarp();
  cluster_arrive();
  uint4 wv0, wv1, xv[4];
  bf16 cv0, cv1;
  if (!FFN && tid < 256) {
    const int r = (blockIdx.x & 3) * 128 + (tid >> 2);
    const uint4* wp = (const uint4*)(wm + r * 3072 + (blockIdx.x >> 2) * 32 + (tid & 3) * 8);
    wv0 = __ldg(wp); wv1 = __ldg(wp + 64 * 384);
    cv0 = cv[r]; cv1 = cv[r + 64];
#pragma unroll
    for (int i = 0; i < 4; i++) xv[i] = __ldg((const uint4*)(xg + (blockIdx.x * 16 + (tid >> 4)) * 512 + i * 128 + (tid & 15) * 8));
  }
  cluster_wait();
  if (warp >= 8) {
    asm volatile("setmaxnreg.dec.sync.aligned.u32 40;");
    if (tid == 256) {
      auto loadB = [&](int s) {
        const uint32_t d = sB + (s % NB) * 24576, b = bF + (s % NB) * 8;
        mbar_expect(b, 24576);
        for (int j = 0; j < 3; j++) {
          if (FFN) tma2d_mc(d + (pr * 3 + j) * BOX, pr ? &mB1 : &mB0, ct * 176 + j * 64, s * 32, b);
          else tma2d(d + j * BOX, &mB0, ct * 192 + j * 64, s * 64, b);
        }
      };
      for (int i = 0; i < 8; i++) mbar_expect(bA + 8 * i, 16384);
      if (!FFN) l2_prefetch((const char*)wq + blockIdx.x * 12288, 12288);
      int nb = 0;
      for (int s = 0; s < NB; s++, nb++) {
        const int i = s * 2 + (ct & 1);
        if (FFN && s >= PD1 && !may_preload(bF + (s - PD1) * 8, bars + 160)) break;
        if (!FFN && s == DLY) mbar_wait(bars + 160, 0);
        if (!FFN) tma2d_mc(sA + i * 16384, &mX, i * 64, rb * 128, bA + 8 * i);
        loadB(s);
      }
      if (FFN) {
        pdl_wait();
        for (int i = 0; i < 5; i++) {
          bulk_load(sA + i * 16384, g_a + (rb * 64 + i * 8) * 1024, 16384, bA + 8 * i);
          for (; nb < 2 * i + 2 && nb < NB; nb++) loadB(nb);
        }
      }
      for (int s = NB; s < NST; s++) {
        mbar_wait(bE + (s % NB) * 8, (s / NB - 1) & 1); loadB(s);
        if (FFN && s <= 10 && !(s & 1)) bulk_load(sA + (s / 2 - 3) * 16384, g_a + (rb * 64 + (s / 2 + 2) * 8) * 1024, 16384, bA + 8 * (s / 2 + 2));
      }
    }
  } else {
  asm volatile("setmaxnreg.inc.sync.aligned.u32 232;");
  const int g = lane >> 2, t = lane & 3;
  const int lr = warp * 16 + (lane & 7) + ((lane >> 3) & 1) * 8;
  auto aaddr = [&](int ks) -> uint32_t {
    if (FFN) return sA + ((ks < 20 ? ks : ks - 20) * 2 + (lane >> 4)) * 2048 + lr * 16;
    return sA + (ks >> 2) * 16384 + lr * 128 + ((((ks & 3) * 2 + (lane >> 4)) ^ (lr & 7)) << 4);
  };
  const int row0 = rb * 128 + warp * 16 + g;
  float2 msh, msc;
  float4 p0, p1, uv;
  float rs0, rs1, nm0, nm1;
  if (!FFN) {
    {
      float a[8] = {0, 0, 0, 0, 0, 0, 0, 0};
      fma8(a, silu_bf(cv0), wv0); fma8(a, silu_bf(cv1), wv1);
      red[warp * 32 + t * 8 + g] = red8(a, lane);
      asm volatile("bar.sync 1,256;" ::: "memory");
      if (tid < 32) {
        float r = 0;
#pragma unroll
        for (int i = 0; i < 8; i++) r += red[i * 32 + tid];
        asm volatile("st.relaxed.gpu.global.u32 [%0],%1;" ::"l"(g_modv + ((blockIdx.x >> 2) * 32 + tid) * 4 + (blockIdx.x & 3)), "r"(__float_as_uint(r) | 1u) : "memory");
      }
      TS(0, 1);
    }
    {
      float v[32], s = 0, q = 0;
#pragma unroll
      for (int i = 0; i < 16; i++) { const uint32_t u = ((const uint32_t*)xv)[i]; v[2 * i] = blo(u); v[2 * i + 1] = bhi(u); s += v[2 * i] + v[2 * i + 1]; }
      s = qsum(s); s += __shfl_xor_sync(~0u, s, 4); s += __shfl_xor_sync(~0u, s, 8);
      const float m = s * (1.f / 512);
#pragma unroll
      for (int i = 0; i < 32; i++) q += (v[i] - m) * (v[i] - m);
      q = qsum(q); q += __shfl_xor_sync(~0u, q, 4); q += __shfl_xor_sync(~0u, q, 8);
      const float rs = rsqrtf(q * (1.f / 512) + 1e-5f);
      if ((tid & 15) == 0)
        asm volatile("st.relaxed.gpu.global.v2.u32 [%0],{%1,%2};" ::"l"(g_modv + 4096 + (blockIdx.x * 16 + (tid >> 4)) * 2), "r"(__float_as_uint(rs) | 1u), "r"(__float_as_uint(-m * rs) | 1u) : "memory");
    }
    uint2 q0, q1;
    float w[16];
    if (tid < 128) {
      uint32_t v; int n = 0;
      do asm volatile("ld.relaxed.gpu.global.u32 %0,[%1];" : "=r"(v) : "l"(g_modv + (tid >> 2) * 128 + (tid & 3)) : "memory"); while (!(v & 1) && ++n < 1048576);
    }
    asm volatile("bar.sync 1,256;" ::: "memory");
    poll(q0, q1, w, g_modv + 4096 + row0 * 2, g_modv + tid * 8);
    msh = make_float2(mod_fin(w[0] + w[1] + w[2] + w[3], 0), mod_fin(w[4] + w[5] + w[6] + w[7], 0));
    msc = make_float2(mod_fin(w[8] + w[9] + w[10] + w[11], 512), mod_fin(w[12] + w[13] + w[14] + w[15], 512));
    asm volatile("bar.sync 1,256;" ::: "memory");
    if (tid == 32) mbar_arrive(bars + 160);
    rs0 = __uint_as_float(q0.x); nm0 = __uint_as_float(q0.y); rs1 = __uint_as_float(q1.x); nm1 = __uint_as_float(q1.y);
  } else {
    pdl_wait();
    if (tid == 32) mbar_arrive(bars + 160);
    TS(4, 1);
    p0 = *(const float4*)(g_st + row0 * 8 + t * 2); p1 = *(const float4*)(g_st + (row0 + 8) * 8 + t * 2);
    if (tid < 176) uv = *(const float4*)(g_uv + (tid >= 88 ? 1408 - 176 : 0) + ct * 176 + tid * 2);
  }
  if (!FFN) {
    uint32_t* m = (uint32_t*)(smem + (sM - sA)) + (tid >> 3) * 16 + (tid & 3) * 4 + ((tid >> 2) & 1);
    m[0] = pack_rn(msc.x, msc.y); m[2] = pack_rn(msh.x, msh.y);
    asm volatile("bar.sync 1,256;" ::: "memory");
  }
  constexpr int NA = FFN ? 88 : 96;
  float acc0[NA], acc1[FFN ? 88 : 1];
  uint32_t a[2][KS][4];
  auto prep = [&](int ks, uint32_t(&o)[4]) {
    if ((ks & 3) == 0) mbar_wait(bA + 2 * ks, 0);
    if (FFN) { ldsm4(aaddr(ks), o); return; }
    uint32_t r[4]; ldsm4(aaddr(ks), r);
    const uint4 m = *(const uint4*)(smem + (sM - sA) + ks * 64 + t * 16);
#pragma unroll
    for (int i = 0; i < 4; i++) {
      const float rs = (i & 1) ? rs1 : rs0, nm = (i & 1) ? nm1 : nm0;
      const uint32_t n = pack_rn(fmaf(blo(r[i]), rs, nm), fmaf(bhi(r[i]), rs, nm));
      asm("fma.rn.bf16x2 %0,%1,%2,%3;" : "=r"(o[i]) : "r"(n), "r"(i < 2 ? m.x : m.y), "r"(i < 2 ? m.z : m.w));
    }
  };
  auto stage = [&](int s, uint32_t(&c)[KS][4], uint32_t(&n)[KS][4]) {
    mbar_wait(bF + (s % NB) * 8, (s / NB) & 1);
    const uint64_t db = mk_desc(sB + (s % NB) * 24576, BOX, 1024, 1);
    wg_fence();
#pragma unroll
    for (int k = 0; k < KS; k++) {
      if constexpr (FFN) {
        wgmma_rs_n176_t1(acc0, c[k][0], c[k][1], c[k][2], c[k][3], db + k * 128, s + k);
        wgmma_rs_n176_t1(acc1, c[k][0], c[k][1], c[k][2], c[k][3], db + k * 128 + 3 * BOX / 16, s + k);
      } else {
        wgmma_rs_n192_t1(acc0, c[k][0], c[k][1], c[k][2], c[k][3], db + k * 128, s + k);
      }
    }
    wg_commit();
    wg_wait<1>();
    if (s > 0 && s <= NST - NB) {
      if (!FFN) { if (lane == 0) mbar_arrive(bE + ((s - 1) % NB) * 8); }
      else if (lane < 2) asm volatile("{\n.reg .b32 r;\nmapa.shared::cluster.u32 r,%0,%1;\nmbarrier.arrive.relaxed.cluster.shared::cluster.b64 _,[r];\n}" ::"r"(bE + ((s - 1) % NB) * 8), "r"(lane) : "memory");
    }
    if (s < NST - 1) {
#pragma unroll
      for (int k = 0; k < KS; k++) prep((s + 1) * KS + k, n[k]);
    }
  };
#pragma unroll
  for (int k = 0; k < KS; k++) prep(k, a[0][k]);
  TS(FFN ? 4 : 1, 2);
#pragma unroll 1
  for (int s = 0; s < NST; s += 2) { stage(s, a[0], a[1]); stage(s + 1, a[1], a[0]); }
  if (FFN) {
    if (tid < 88) { uv.x *= 0.5f; uv.y *= 0.5f; uv.z *= 0.5f; uv.w *= 0.5f; }
    if (tid < 176) *(float4*)(smem + (sM - sA) + tid * 16) = uv;
    const float m0 = qsum(p0.x + p0.z) * 0.125f, m1 = qsum(p1.x + p1.z) * 0.125f;
    const float v0 = qsum(p0.y + p0.w + 64.f * ((p0.x - m0) * (p0.x - m0) + (p0.z - m0) * (p0.z - m0)));
    const float v1 = qsum(p1.y + p1.w + 64.f * ((p1.x - m1) * (p1.x - m1) + (p1.z - m1) * (p1.z - m1)));
    rs0 = rsqrtf(v0 * (1.f / 512) + 1e-5f); rs1 = rsqrtf(v1 * (1.f / 512) + 1e-5f);
    nm0 = -m0 * rs0; nm1 = -m1 * rs1;
    asm volatile("bar.sync 1,256;" ::: "memory");
  }
  wg_wait<0>();
  reg_fence(acc0);
  TS(FFN ? 4 : 1, 3);
  if constexpr (FFN) {
    reg_fence(acc1);
    const float rh0 = 0.5f * rs0, rh1 = 0.5f * rs1;
    uint32_t* o = (uint32_t*)g_h + ((rb * 172 + ct * 22) * 128 + warp * 16 + g) * 4 + t;
#pragma unroll
    for (int j = 0; j < 22; j++) {
      {
        const float4 u1 = *(const float4*)(smem + (sM - sA) + (j * 4 + t) * 16), u3 = *(const float4*)(smem + (sM - sA) + (88 + j * 4 + t) * 16);
        float h[4];
#pragma unroll
        for (int i = 0; i < 4; i++) {
          const float rs = i < 2 ? rs0 : rs1, nm = i < 2 ? nm0 : nm1, rh = i < 2 ? rh0 : rh1;
          const float z = fmaf(rh, acc0[4 * j + i], (i & 1) ? fmaf(nm, u1.z, u1.w) : fmaf(nm, u1.x, u1.y));
          const float y = fmaf(rs, acc1[4 * j + i], (i & 1) ? fmaf(nm, u3.z, u3.w) : fmaf(nm, u3.x, u3.y));
          float th; asm("tanh.approx.f32 %0,%1;" : "=f"(th) : "f"(z));
          h[i] = fmaf(z, th, z) * y;
        }
        if (j < 18 || ct < 7) { o[j * 512] = pack_rn(h[0], h[1]); o[j * 512 + 32] = pack_rn(h[2], h[3]); }
      }
    }
  } else {
    uint32_t* o = (uint32_t*)g_qkv + (ct * 24 * 2048 + row0) * 4 + t;
#pragma unroll
    for (int j = 0; j < 24; j += 2) {
      const int G = ct * 24 + j;
      const float sc = G < 64 ? 0.25f * 1.4426950408889634f : 1.f;
      uint32_t p[4];
#pragma unroll
      for (int i = 0; i < 4; i++) p[i] = pack_rn(acc0[4 * j + 2 * i] * sc, acc0[4 * j + 2 * i + 1] * sc);
      o[j * 8192] = p[0]; o[j * 8192 + 32] = p[1]; o[(j + 1) * 8192] = p[2]; o[(j + 1) * 8192 + 32] = p[3];
      if (G >= 64 && G < 128) {
        float n0 = blo(p[0]) * blo(p[0]) + bhi(p[0]) * bhi(p[0]) + blo(p[2]) * blo(p[2]) + bhi(p[2]) * bhi(p[2]);
        float n1 = blo(p[1]) * blo(p[1]) + bhi(p[1]) * bhi(p[1]) + blo(p[3]) * blo(p[3]) + bhi(p[3]) * bhi(p[3]);
        n0 = qsum(n0); n1 = qsum(n1);
        const uint32_t mx = __reduce_max_sync(~0u, max(__float_as_uint(n0), __float_as_uint(n1)));
        if (lane == 0) g_kmax[((G - 64) >> 1) * 128 + rb * 8 + warp] = __uint_as_float(mx);
      }
    }
  }
  TS(FFN ? 4 : 1, 4);
}
}

#define SMASK 0xCCCCu
#define BRK 0
#define PACK 1
constexpr int AT_SMEM = 5 * 32768 + 256;
__device__ __forceinline__ uint32_t exp2_pair_fma(float s0, float s1, float c, uint32_t ka, uint32_t kz) {
  uint32_t r;
  asm volatile("{\n.reg .b32 y0,y1,e,u,t;\n"
      "fma.rn.sat.f32 y0,%1,0f00000080,%3;\nfma.rn.sat.f32 y1,%2,0f00000080,%3;\n"
      "mad.lo.u32 e,y1,65536,y0;\n"
      "and.b32 u,e,0x007F007F;\n"
      "fma.rn.f16x2 u,u,%4,%5;\nfma.rn.f16x2 t,u,u,%6;\nfma.rn.f16x2 t,t,u,%7;\n"
      "lop3.b32 %0,t,0x007F007F,e,0xE2;\n}\n"
      : "=r"(r) : "f"(s0), "f"(s1), "f"(c), "r"(ka), "r"(0x36B236B2u), "r"(0x3C733C73u), "r"(0x47764776u), "r"(kz));
  return r;
}
__device__ __forceinline__ void attn_pass(float (&oa)[12], float (&ob)[12], const uint32_t (&q)[4], float m0, float m1, uint32_t sK, uint32_t bars, bool first, uint32_t kz) {
  uint64_t dk = mk_desc(sK, 32768, 128, 0), dv = mk_desc(sK + 65536, 128, 32768, 0);
  const float c0 = (127.f - m0) * __uint_as_float(0x80u), c1 = (127.f - m1) * __uint_as_float(0x80u);
  uint32_t ka;
  asm volatile("mov.b32 %0,0x7ACE7ACE;" : "=r"(ka));
  constexpr int NK = 64, NS = 32, NP = 16;
  auto qk = [&](float (&s)[NS], int i) { wgmma_rs_n64_t0(s, q[0], q[1], q[2], q[3], dk + i * NK, 0); };
  auto softmax = [&](float (&s)[NS], uint32_t (&p)[NP], uint32_t mask) {
    reg_fence(s);
    float e0, e1;
    int pend = -1;
#pragma unroll
    for (int t = 0; t < NP; t++) {
      const int j = (t & 3) * 4 + (t >> 2);
      if ((mask >> (t & 3)) & 1) {
        p[j] = exp2_pair_fma(s[2 * j], s[2 * j + 1], (j & 1) ? c1 : c0, ka, kz);
      } else {
        float f0, f1;
        asm volatile("ex2.approx.ftz.f32 %0,%2;\nex2.approx.ftz.f32 %1,%3;" : "=&f"(f0), "=f"(f1) : "f"(s[2 * j]), "f"(s[2 * j + 1]));
        if (pend >= 0) asm volatile("cvt.rn.bf16x2.f32 %0,%1,%2;" : "=r"(p[pend]) : "f"(e1), "f"(e0));
        e0 = f0; e1 = f1; pend = j;
      }
    }
    if (pend >= 0) asm volatile("cvt.rn.bf16x2.f32 %0,%1,%2;" : "=r"(p[pend]) : "f"(e1), "f"(e0));
#pragma unroll
    for (int j = 0; j < NP; j++) asm volatile("" : "+r"(p[j])::"memory");
  };
  auto pv = [&](uint32_t (&p)[NP], int i, uint32_t mask) {
#pragma unroll
    for (int k = 0; k < 4; k++) wgmma_rs_n24_t1(((mask >> k) & 1) ? ob : oa, p[4 * k], p[4 * k + 1], p[4 * k + 2], p[4 * k + 3], dv + i * NK + k * 16, 1);
  };
  constexpr uint32_t M0 = SMASK & 15, M1 = (SMASK >> 4) & 15, M2 = (SMASK >> 8) & 15, M3 = SMASK >> 12;
  zero(oa); zero(ob);
  mbar_wait(bars, 0);
  if (first) TS(2, 2);
  float s[NS];
  zero(s);
  uint32_t p0[NP], p1[NP];
  auto step = [&](int i, uint32_t (&pa)[NP], uint32_t ma, uint32_t (&pb)[NP], uint32_t mb) {
    wg_fence(); qk(s, i + 1); wg_commit(); pv(pa, i, ma); wg_commit(); wg_wait<1>(); softmax(s, pb, mb); wg_wait<0>();
  };
  wg_fence(); qk(s, 0); wg_commit(); wg_wait<0>(); softmax(s, p0, M0);
#pragma unroll 1
  for (uint32_t b = bars + 8; b < bars + 64; b += 8) {
    step(0, p0, M0, p1, M1); step(1, p1, M1, p0, M2); step(2, p0, M2, p1, M3);
    mbar_wait(b, 0);
    step(3, p1, M3, p0, M0);
    dk += 4 * NK; dv += 4 * NK;
  }
  step(0, p0, M0, p1, M1); step(1, p1, M1, p0, M2); step(2, p0, M2, p1, M3);
  wg_fence(); pv(p1, 3, M3); wg_commit();
  wg_wait<0>();
  reg_fence(oa); reg_fence(ob);
}
__device__ __forceinline__ void mma16816(float (&d)[4], const uint32_t (&a)[4], uint32_t b0, uint32_t b1) {
  asm("mma.sync.aligned.m16n8k16.row.col.f32.bf16.bf16.f32 {%0,%1,%2,%3},{%4,%5,%6,%7},{%8,%9},{%0,%1,%2,%3};"
      : "+f"(d[0]), "+f"(d[1]), "+f"(d[2]), "+f"(d[3]) : "r"(a[0]), "r"(a[1]), "r"(a[2]), "r"(a[3]), "r"(b0), "r"(b1));
}
__device__ __forceinline__ void attn_safe(float (&o)[12], const uint32_t (&q)[4], uint32_t sK) {
  const int lane = threadIdx.x & 31;
  const uint32_t ka = sK + (lane >> 4) * 32768 + (lane & 15) * 16;
  float m0 = -INFINITY, m1 = -INFINITY;
#pragma unroll 2
  for (int i = 0; i < 128; i++) {
    uint32_t k[4]; ldsm4(ka + i * 256, k);
    float s0[4] = {0, 0, 0, 0}, s1[4] = {0, 0, 0, 0};
    mma16816(s0, q, k[0], k[2]); mma16816(s1, q, k[1], k[3]);
    m0 = fmaxf(fmaxf(m0, fmaxf(s0[0], s0[1])), fmaxf(s1[0], s1[1])); m1 = fmaxf(fmaxf(m1, fmaxf(s0[2], s0[3])), fmaxf(s1[2], s1[3]));
  }
  m0 = fmaxf(m0, __shfl_xor_sync(~0u, m0, 1)); m0 = fmaxf(m0, __shfl_xor_sync(~0u, m0, 2));
  m1 = fmaxf(m1, __shfl_xor_sync(~0u, m1, 1)); m1 = fmaxf(m1, __shfl_xor_sync(~0u, m1, 2));
  float o0[4] = {0, 0, 0, 0}, o1[4] = {0, 0, 0, 0}, o2[4] = {0, 0, 0, 0};
#pragma unroll 2
  for (int i = 0; i < 128; i++) {
    uint32_t k[4], v[4]; ldsm4(ka + i * 256, k);
    asm volatile("ldmatrix.sync.aligned.m8n8.x4.trans.shared.b16 {%0,%1,%2,%3},[%4];" : "=r"(v[0]), "=r"(v[1]), "=r"(v[2]), "=r"(v[3]) : "r"(ka + 65536 + i * 256) : "memory");
    float s0[4] = {0, 0, 0, 0}, s1[4] = {0, 0, 0, 0};
    mma16816(s0, q, k[0], k[2]); mma16816(s1, q, k[1], k[3]);
    const uint32_t p[4] = {pack_rn(ex2(s0[0] - m0), ex2(s0[1] - m0)), pack_rn(ex2(s0[2] - m1), ex2(s0[3] - m1)),
                           pack_rn(ex2(s1[0] - m0), ex2(s1[1] - m0)), pack_rn(ex2(s1[2] - m1), ex2(s1[3] - m1))};
    mma16816(o0, p, v[0], v[1]); mma16816(o1, p, v[2], v[3]); mma16816(o2, p, 0x3F803F80u, 0x3F803F80u);
  }
#pragma unroll
  for (int i = 0; i < 4; i++) { o[i] = o0[i]; o[4 + i] = o1[i]; o[8 + i] = o2[i]; }
}
__global__ void __cluster_dims__(2, 1, 1) __launch_bounds__(512, 1) k_attn(const bf16* wo, const bf16* w1, const bf16* w3, const bf16* w2, const bf16* __restrict__ cv, const bf16* __restrict__ wm, uint32_t kz) {
  extern __shared__ __align__(1024) uint8_t smem[];
  const uint32_t sK = smem_u32(smem), bars = sK + 5 * 32768;
  const int tid = threadIdx.x, warp = tid >> 5, lane = tid & 31, g = lane >> 2, t = lane & 3;
  pdl_launch();
  if (blockIdx.x < 4) {
    float* cs = (float*)smem;
    cs[tid] = silu_bf(cv[tid]);
    cluster_sync();
    const int b = blockIdx.x;
    float *mv = cs + 512, *rd = cs + 1536;
    auto put8 = [&](float* d, float (&a)[8]) { ((float4*)d)[0] = make_float4(a[0], a[1], a[2], a[3]); ((float4*)d)[1] = make_float4(a[4], a[5], a[6], a[7]); };
    for (int ph = 0; ph < 2; ph++) {
      const int nc = 512 >> ph, n0 = ph ? (b >> 1) * 1536 + 1024 + (b & 1) * 256 : 1536 + (b & 1) * 512, nr = 64 >> ph, r0 = tid / nr * nr;
      float a[8] = {0, 0, 0, 0, 0, 0, 0, 0};
#pragma unroll 16
      for (int r = r0; r < r0 + nr; r++) fma8(a, cs[r], __ldg((const uint4*)(wm + r * 3072 + n0 + (tid & (nr - 1)) * 8)));
      put8(rd + tid * 8, a);
      __syncthreads();
      if (tid < nc) {
        float s = 0;
        for (int i = tid; i < 4096; i += nc) s += rd[i];
        s = mod_fin(s, n0 + tid);
        if (ph || b < 2) g_mod[n0 + tid] = s;
        if (!ph) {
          mv[(b & 1) * 512 + tid] = s;
          asm volatile("{\n.reg .b32 r;\nmapa.shared::cluster.u32 r,%0,%1;\nst.shared::cluster.f32 [r],%2;\n}" ::"r"(smem_u32(mv + (b & 1) * 512 + tid)), "r"((b & 1) ^ 1), "f"(s) : "memory");
        }
      }
      cluster_sync();
    }
    if (tid < 430) {
      const bf16* w = (b >> 1 ? w3 : w1) + (b & 1) * 688 + tid % 86 * 8;
      float u[8] = {0, 0, 0, 0, 0, 0, 0, 0}, v[8] = {0, 0, 0, 0, 0, 0, 0, 0};
#pragma unroll 13
      for (int r = tid / 86; r < 512; r += 5) { const uint4 x = __ldg((const uint4*)(w + r * 1376)); fma8(u, mv[512 + r], x); fma8(v, mv[r], x); }
      put8(rd + tid * 8, u); put8(rd + 3440 + tid * 8, v);
    }
    __syncthreads();
    for (int n = tid; n < 688; n += 512) {
      float u = 0, v = 0;
      for (int i = n; i < 3440; i += 688) { u += rd[i]; v += rd[3440 + i]; }
      g_uv[(b >> 1) * 1408 + (b & 1) * 688 + n] = make_float2(u, v);
    }
    TS(0, 7);
    return;
  }
  const int bid = blockIdx.x - 4, h = bid >> 2, qb = bid & 3;
  TS(2, 0);
  if (tid == 0) { for (int i = 0; i < 8; i++) { mbar_init(bars + 8 * i, 1); mbar_expect(bars + 8 * i, 16384); } fence_init(); }
#pragma unroll
  for (int i = 0; i < 4; i++) *(uint4*)(smem + 131072 + i * 8192 + tid * 16) = make_uint4(0x3F803F80u, 0x3F803F80u, 0x3F803F80u, 0x3F803F80u);
  fence_async();
  cluster_sync();
  pdl_wait();
  TS(2, 1);
  if (tid >= 448) g_modv[bid * 64 + tid - 448] = 0;
  const uint4 km4 = *(const uint4*)(g_kmax + h * 128 + lane * 4);
  const uint32_t* qp = (const uint32_t*)g_qkv + (h * 2 * 2048 + qb * 512 + warp * 16 + g) * 4 + t;
  uint32_t q[4] = {qp[0], qp[32], qp[8192], qp[8192 + 32]};
  auto ldkv = [&]() {
    const int c = warp >> 1, pl = (qb & 1) + (warp & 1) * 2;
    bulk_load_mc(sK + pl * 32768 + c * 4096, g_qkv + ((64 + (pl >> 1) * 64 + h * 2 + (pl & 1)) * 2048 + c * 256) * 8, 4096, bars + 8 * c);
  };
  if (lane == 0 && warp < 4) ldkv();
  const uint32_t qn[4] = {qp[1024], qp[1024 + 32], qp[1024 + 8192], qp[1024 + 8192 + 32]};
  const float kmax = __uint_as_float(__reduce_max_sync(~0u, max(max(km4.x, km4.y), max(km4.z, km4.w))));
  if (lane == 0 && warp >= 4 && kmax != -1.f) ldkv();
#pragma unroll 1
  for (int tile = 0; tile < 2; tile++) {
    const int row = qb * 512 + tile * 256 + warp * 16 + g;
    const float n0 = qsum(blo(q[0]) * blo(q[0]) + bhi(q[0]) * bhi(q[0]) + blo(q[2]) * blo(q[2]) + bhi(q[2]) * bhi(q[2]));
    const float n1 = qsum(blo(q[1]) * blo(q[1]) + bhi(q[1]) * bhi(q[1]) + blo(q[3]) * blo(q[3]) + bhi(q[3]) * bhi(q[3]));
    const float b0 = sqrtf(n0 * kmax) * 1.001f, b1 = sqrtf(n1 * kmax) * 1.001f;
    const float m0 = fmaxf(ceilf(b0 - 100.f), 0.f), m1 = fmaxf(ceilf(b1 - 100.f), 0.f);
    float o[12], ob[12];
    attn_pass(o, ob, q, m0, m1, sK, bars, tile == 0, kz);
    const float f0 = ex2(-m0), f1 = ex2(-m1);
#pragma unroll
    for (int i = 0; i < 12; i++) o[i] = fmaf(o[i], (i & 2) ? f1 : f0, ob[i]);
    bool ok = b0 < 220.f && b1 < 220.f && o[8] >= 0x1p-90f && o[10] >= 0x1p-90f;
#pragma unroll
    for (int i = 0; i < 12; i++) ok = ok && fabsf(o[i]) < INFINITY;
    if (!__all_sync(~0u, ok)) attn_safe(o, q, sK);
    const float r0 = 1.f / o[8], r1 = 1.f / o[10];
    uint32_t* op = (uint32_t*)g_o + (((row >> 7) * 64 + h * 2) * 128 + (row & 127)) * 4 + t;
    op[0] = pack_rn(o[0] * r0, o[1] * r0); op[32] = pack_rn(o[2] * r1, o[3] * r1);
    op[512] = pack_rn(o[4] * r0, o[5] * r0); op[512 + 32] = pack_rn(o[6] * r1, o[7] * r1);
    if (tile == 0 && tid == 32) {
      l2_prefetch((const char*)wo + bid * 4096, 4096);
      l2_prefetch((const char*)w1 + bid * 11008, 11008);
      l2_prefetch((const char*)w3 + bid * 11008, 11008);
      l2_prefetch((const char*)w2 + bid * 11008, 11008);
    }
#pragma unroll
    for (int i = 0; i < 4; i++) q[i] = qn[i];
    TS(2, 3 + tile);
  }
}

constexpr int WO_SMEM = 131072 + 65536 + 256;
__global__ void __cluster_dims__(2, 1, 1) __launch_bounds__(256, 1) k_wo(const __grid_constant__ CUtensorMap mW, const bf16* __restrict__ x) {
  extern __shared__ __align__(1024) uint8_t smem[];
  const uint32_t sA = smem_u32(smem), sB = sA + 131072, bars = sB + 65536;
  const int tid = threadIdx.x, warp = tid >> 5, lane = tid & 31, g = lane >> 2, t = lane & 3;
  const int rb = blockIdx.x >> 3, ct = blockIdx.x & 7;
  TS(3, 0);
  pdl_launch();
  if (tid == 0) {
    for (int i = 0; i < 8; i++) mbar_init(bars + 8 * i, 1);
    fence_init();
    for (int i = 0; i < 8; i++) { mbar_expect(bars + 8 * i, 24576); tma2d(sB + i * 8192, &mW, ct * 64, i * 64, bars + 8 * i); }
  }
  __syncwarp();
  cluster_arrive();
  const int lrow = warp * 16 + g;
  uint32_t xr[16];
  const uint32_t* xp = (const uint32_t*)(x + (rb * 128 + lrow) * 512 + ct * 64) + t;
#pragma unroll
  for (int j = 0; j < 8; j++) { xr[2 * j] = __ldg(xp + j * 4); xr[2 * j + 1] = __ldg(xp + j * 4 + 8 * 256); }
  cluster_wait();
  pdl_wait();
  if (tid == 0) {
    for (int i = ct & 1; i < 8; i += 2) bulk_load_mc(sA + i * 16384, g_o + (rb * 64 + i * 8) * 1024, 16384, bars + 8 * i);
  }
  TS(3, 1);
  float2 ga[8];
  uint32_t sc[8];
#pragma unroll
  for (int j = 0; j < 8; j++) {
    ga[j] = *(const float2*)(g_mod + 1024 + ct * 64 + j * 8 + t * 2);
    const float2 v = *(const float2*)(g_mod + 2048 + ct * 64 + j * 8 + t * 2);
    sc[j] = pack_rn(v.x, v.y);
  }
  float acc[32];
  const uint64_t da = mk_desc(sA + (warp >> 2) * 1024, 2048, 128, 0), db = mk_desc(sB, 8192, 1024, 1);
#pragma unroll
  for (int c = 0; c < 8; c++) {
    mbar_wait(bars + 8 * c, 0);
    if (c == 0) TS(3, 2);
    wg_fence();
#pragma unroll
    for (int k = 0; k < 4; k++) wgmma_ss_n64_t1(acc, da + (c * 4 + k) * 256, db + (c * 4 + k) * 128, c + k);
    wg_commit();
  }
  wg_wait<0>();
  reg_fence(acc);
  TS(3, 3);
  uint32_t* o = (uint32_t*)g_x1 + ((rb * 64 + ct * 8) * 128 + lrow) * 4 + t;
  uint32_t* oa = (uint32_t*)g_a + ((rb * 64 + ct * 8) * 128 + lrow) * 4 + t;
  float s0 = 0, s1 = 0;
#pragma unroll
  for (int j = 0; j < 8; j++) {
    xr[2 * j] = pack_rn(fmaf(ga[j].x, acc[4 * j], blo(xr[2 * j])), fmaf(ga[j].y, acc[4 * j + 1], bhi(xr[2 * j])));
    xr[2 * j + 1] = pack_rn(fmaf(ga[j].x, acc[4 * j + 2], blo(xr[2 * j + 1])), fmaf(ga[j].y, acc[4 * j + 3], bhi(xr[2 * j + 1])));
    uint32_t a0, a1;
    asm("mul.rn.bf16x2 %0,%1,%2;" : "=r"(a0) : "r"(xr[2 * j]), "r"(sc[j]));
    asm("mul.rn.bf16x2 %0,%1,%2;" : "=r"(a1) : "r"(xr[2 * j + 1]), "r"(sc[j]));
    oa[j * 512] = a0; oa[j * 512 + 32] = a1;
    o[j * 512] = xr[2 * j]; o[j * 512 + 32] = xr[2 * j + 1];
    s0 += blo(xr[2 * j]) + bhi(xr[2 * j]); s1 += blo(xr[2 * j + 1]) + bhi(xr[2 * j + 1]);
  }
  const float m0 = qsum(s0) * (1.f / 64), m1 = qsum(s1) * (1.f / 64);
  float v0 = 0, v1 = 0;
#pragma unroll
  for (int j = 0; j < 8; j++) {
    float d;
    d = blo(xr[2 * j]) - m0; v0 += d * d; d = bhi(xr[2 * j]) - m0; v0 += d * d;
    d = blo(xr[2 * j + 1]) - m1; v1 += d * d; d = bhi(xr[2 * j + 1]) - m1; v1 += d * d;
  }
  v0 = qsum(v0); v1 = qsum(v1);
  if (t == 0) g_st[(rb * 128 + lrow) * 8 + ct] = make_float2(m0, v0);
  if (t == 1) g_st[(rb * 128 + lrow + 8) * 8 + ct] = make_float2(m1, v1);
  TS(3, 4);
}

constexpr int W2_SMEM = 6 * 32768 + 32768 + 256;
__global__ void __cluster_dims__(2, 1, 1) __launch_bounds__(288, 1) k_w2(const __grid_constant__ CUtensorMap mW, bf16* __restrict__ out) {
  extern __shared__ __align__(1024) uint8_t smem[];
  const uint32_t sR = smem_u32(smem), sX = sR + 6 * 32768, bF = sX + 32768, bE = bF + 48, bX = bF + 96, bB = bF + 160, bG = bF + 208;
  const int tid = threadIdx.x, warp = tid >> 5, lane = tid & 31, g = lane >> 2, t = lane & 3;
  const int kh = blockIdx.x & 1, ct = (blockIdx.x >> 1) & 3, rb = blockIdx.x >> 3;
  TS(5, 0);
  pdl_launch();
  if (tid == 256) {
    for (int i = 0; i < 6; i++) { mbar_init(bF + 8 * i, 1); mbar_init(bE + 8 * i, 8); mbar_init(bB + 8 * i, 1); }
    mbar_init(bG, 1);
    for (int i = 0; i < 8; i++) { mbar_init(bX + 8 * i, 1); mbar_expect(bX + 8 * i, 4096); }
    fence_init();
  }
  __syncthreads();
  asm volatile("barrier.cluster.arrive.relaxed.aligned;" ::: "memory");
  if (warp == 8) {
    if (lane == 0) {
      auto abytes = [&](int s) { return (kh == 1 && s == 10) ? 8192 : 16384; };
      auto loadB = [&](int s) {
        const int st = s % 6;
        mbar_expect(bB + 8 * st, 16384);
        for (int j = 0; j < 2; j++) tma2d(sR + st * 32768 + 16384 + j * 8192, &mW, ct * 128 + j * 64, kh * 704 + s * 64, bB + 8 * st);
      };
      auto loadA = [&](int s) { mbar_expect(bF + 8 * (s % 6), abytes(s)); bulk_load(sR + (s % 6) * 32768, g_h + (rb * 172 + kh * 88 + s * 8) * 1024, abytes(s), bF + 8 * (s % 6)); };
      int nb = 0;
      for (; nb < 6 && (nb < PD2 || may_preload(bB + 8 * (nb - PD2), bG)); nb++) loadB(nb);
      pdl_wait();
      for (int s = 0; s < 6; s++) { loadA(s); if (s >= nb) loadB(s); }
      for (int s = 6; s < 11; s++) { mbar_wait(bE + 8 * (s - 6), 0); loadB(s); loadA(s); }
    }
    __syncwarp();
    cluster_wait();
    return;
  }
  pdl_wait();
  if (tid == 32) mbar_arrive(bG);
  TS(5, 1);
  const int lrow = warp * 16 + g;
  uint32_t xr[16];
  float2 gb[8];
  const uint32_t* xp = (const uint32_t*)g_x1 + ((rb * 64 + ct * 16 + kh * 8) * 128 + lrow) * 4 + t;
#pragma unroll
  for (int j = 0; j < 8; j++) {
    xr[2 * j] = xp[j * 512]; xr[2 * j + 1] = xp[j * 512 + 32];
    gb[j] = *(const float2*)(g_mod + 2560 + ct * 128 + kh * 64 + j * 8 + t * 2);
  }
  float acc[64];
#pragma unroll 1
  for (int s = 0; s < 11; s++) {
    const int st = s % 6;
    mbar_wait(bB + 8 * st, s >= 6); mbar_wait(bF + 8 * st, s >= 6);
    const uint64_t da = mk_desc(sR + st * 32768 + (warp >> 2) * 1024, 2048, 128, 0), db = mk_desc(sR + st * 32768 + 16384, 8192, 1024, 1);
    if (s == 0) TS(5, 2);
    wg_fence();
    wgmma_ss_n128_t1(acc, da, db, s);
    wgmma_ss_n128_t1(acc, da + 256, db + 128, 1);
    wgmma_ss_n128_t1(acc, da + 512, db + 256, 1);
    wgmma_ss_n128_t1(acc, da + 768, db + 384, 1);
    wg_commit();
    wg_wait<1>();
    if (s > 0 && s < 6 && lane == 0) mbar_arrive(bE + 8 * (s - 1));
  }
  wg_wait<0>();
  reg_fence(acc);
  TS(5, 3);
  asm volatile("barrier.cluster.wait.aligned;" ::: "memory");
  uint32_t rem, rbar;
  asm("mapa.shared::cluster.u32 %0,%1,%2;" : "=r"(rbar) : "r"(bX + warp * 8), "r"(kh ^ 1));
  asm("mapa.shared::cluster.u32 %0,%1,%2;" : "=r"(rem) : "r"(sX + warp * 4096 + lane * 16), "r"(kh ^ 1));
#pragma unroll
  for (int j = 0; j < 8; j++) {
    float v[4];
#pragma unroll
    for (int i = 0; i < 4; i++) { v[i] = kh ? acc[4 * j + i] : acc[32 + 4 * j + i]; acc[4 * j + i] = kh ? acc[32 + 4 * j + i] : acc[4 * j + i]; }
    asm volatile("st.async.weak.shared::cluster.mbarrier::complete_tx::bytes.v4.f32 [%0],{%1,%2,%3,%4},[%5];" ::"r"(rem + j * 512), "f"(v[0]), "f"(v[1]), "f"(v[2]), "f"(v[3]), "r"(rbar) : "memory");
  }
  mbar_wait(bX + warp * 8, 0);
  TS(5, 5);
  const uint32_t sw = sX + warp * 4096;
#pragma unroll
  for (int j = 0; j < 8; j++) {
    const float4 p = *(const float4*)(smem + 6 * 32768 + warp * 4096 + j * 512 + lane * 16);
    xr[2 * j] = pack_rn(fmaf(gb[j].x, acc[4 * j] + p.x, blo(xr[2 * j])), fmaf(gb[j].y, acc[4 * j + 1] + p.y, bhi(xr[2 * j])));
    xr[2 * j + 1] = pack_rn(fmaf(gb[j].x, acc[4 * j + 2] + p.z, blo(xr[2 * j + 1])), fmaf(gb[j].y, acc[4 * j + 3] + p.w, bhi(xr[2 * j + 1])));
  }
  __syncwarp();
#pragma unroll
  for (int j = 1; j < 8; j += 2) {
    asm volatile("stmatrix.sync.aligned.m8n8.x4.shared.b16 [%0],{%1,%2,%3,%4};" ::"r"(sw + (lane & 15) * 128 + (((j - 1 + (lane >> 4)) ^ (lane & 7)) << 4)),
                            "r"(xr[2 * j - 2]), "r"(xr[2 * j - 1]), "r"(xr[2 * j]), "r"(xr[2 * j + 1]) : "memory");
  }
  __syncwarp();
#pragma unroll
  for (int i = 0; i < 4; i++) {
    const int r = i * 4 + (lane >> 3);
    *(uint4*)(out + (rb * 128 + warp * 16 + r) * 512 + ct * 128 + kh * 64 + (lane & 7) * 8) = *(const uint4*)(smem + 6 * 32768 + warp * 4096 + r * 128 + (((lane ^ r) & 7) << 4));
  }
  TS(5, 4);
}

typedef CUresult (*EncFn)(CUtensorMap*, CUtensorMapDataType, cuuint32_t, void*, const cuuint64_t*, const cuuint64_t*, const cuuint32_t*,
                          const cuuint32_t*, CUtensorMapInterleave, CUtensorMapSwizzle, CUtensorMapL2promotion, CUtensorMapFloatOOBfill);
static void mk_map(EncFn f, CUtensorMap* m, const void* p, int rows, int cols, int box_rows) {
  cuuint64_t dim[2] = {(cuuint64_t)cols, (cuuint64_t)rows}, str[1] = {(cuuint64_t)cols * 2};
  cuuint32_t box[2] = {64, (cuuint32_t)box_rows}, es[2] = {1, 1};
  f(m, CU_TENSOR_MAP_DATA_TYPE_BFLOAT16, 2, (void*)p, dim, str, box, es, CU_TENSOR_MAP_INTERLEAVE_NONE, CU_TENSOR_MAP_SWIZZLE_128B,
    CU_TENSOR_MAP_L2_PROMOTION_L2_128B, CU_TENSOR_MAP_FLOAT_OOB_FILL_NONE);
}
template <typename... KA, typename... A>
static void launch(void (*k)(KA...), int grid, int block, int smem, bool pdl, A... args) {
  cudaLaunchConfig_t cfg = {};
  cfg.gridDim = dim3(grid); cfg.blockDim = dim3(block); cfg.dynamicSmemBytes = smem; cfg.stream = cudaStreamPerThread;
  cudaLaunchAttribute at[1];
  at[0].id = cudaLaunchAttributeProgrammaticStreamSerialization; at[0].val.programmaticStreamSerializationAllowed = 1;
  cfg.attrs = at; cfg.numAttrs = pdl ? 1 : 0;
  cudaLaunchKernelEx(&cfg, k, args...);
}
extern "C" void kernel_launch(void* const* d_in, const int* in_sizes, int n_in, void* d_out, int out_size) {
  const bf16 *x = (const bf16*)d_in[0], *wqkv = (const bf16*)d_in[1], *wo = (const bf16*)d_in[2], *w1 = (const bf16*)d_in[4],
             *w3 = (const bf16*)d_in[5], *w2 = (const bf16*)d_in[6], *c = (const bf16*)d_in[7], *wmod = (const bf16*)d_in[8];
  void* fp = nullptr;
  cudaDriverEntryPointQueryResult qr;
  cudaGetDriverEntryPoint("cuTensorMapEncodeTiled", &fp, cudaEnableDefault, &qr);
  EncFn f = (EncFn)fp;
  CUtensorMap mX, mQ, mO, m1, m3, m2;
  mk_map(f, &mX, x, S_, D_, 128); mk_map(f, &mQ, wqkv, D_, 3 * D_, 64); mk_map(f, &mO, wo, D_, D_, 64);
  mk_map(f, &m1, w1, D_, F_, 32); mk_map(f, &m3, w3, D_, F_, 32); mk_map(f, &m2, w2, F_, D_, 64);
  cudaFuncSetAttribute(k_lngemm<false>, cudaFuncAttributeMaxDynamicSharedMemorySize, LN_SMEM);
  cudaFuncSetAttribute(k_lngemm<true>, cudaFuncAttributeMaxDynamicSharedMemorySize, LN_SMEM);
  cudaFuncSetAttribute(k_attn, cudaFuncAttributeMaxDynamicSharedMemorySize, AT_SMEM);
  cudaFuncSetAttribute(k_wo, cudaFuncAttributeMaxDynamicSharedMemorySize, WO_SMEM);
  cudaFuncSetAttribute(k_w2, cudaFuncAttributeMaxDynamicSharedMemorySize, W2_SMEM);
  launch(k_lngemm<false>, 128, 384, LN_SMEM, false, mX, mQ, mQ, c, wmod, x, wqkv);
  launch(k_attn, 132, 512, AT_SMEM, true, wo, w1, w3, w2, c, wmod, 0u);
  launch(k_wo, 128, 256, WO_SMEM, true, mO, x);
  launch(k_lngemm<true>, 128, 384, LN_SMEM, true, mX, m1, m3, c, wmod, x, wqkv);
  launch(k_w2, 128, 288, W2_SMEM, true, m2, (bf16*)d_out);
}
```

```cpp
#include <cuda_runtime.h>
#include <cuda_bf16.h>
#include <cuda.h>
#include <stdint.h>
typedef __nv_bfloat16 bf16;
constexpr int S_ = 2048, D_ = 512, F_ = 1376;
__device__ __align__(1024) float g_mod[3072];
__device__ __align__(1024) uint32_t g_modv[4096 + 4096];
__device__ __align__(1024) bf16 g_qkv[192 * 2048 * 8];
__device__ __align__(1024) float g_kmax[32 * 128];
__device__ __align__(1024) bf16 g_o[16 * 64 * 128 * 8];
__device__ __align__(1024) bf16 g_x1[16 * 64 * 128 * 8];
__device__ __align__(1024) bf16 g_a[16 * 64 * 128 * 8];
__device__ __align__(1024) float2 g_uv[2 * 1408];
__device__ __align__(1024) float2 g_st[2048 * 8];
__device__ __align__(1024) bf16 g_h[16 * 172 * 128 * 8];

__device__ __forceinline__ uint32_t smem_u32(const void* p) { return (uint32_t)__cvta_generic_to_shared(p); }
__device__ __forceinline__ void mbar_init(uint32_t b, int n) { asm volatile("mbarrier.init.shared::cta.b64 [%0],%1;" ::"r"(b), "r"(n) : "memory"); }
__device__ __forceinline__ void mbar_expect(uint32_t b, int bytes) { asm volatile("mbarrier.arrive.expect_tx.shared::cta.b64 _,[%0],%1;" ::"r"(b), "r"(bytes) : "memory"); }
__device__ __forceinline__ void mbar_arrive(uint32_t b) { asm volatile("mbarrier.arrive.shared::cta.b64 _,[%0];" ::"r"(b) : "memory"); }
__device__ __forceinline__ void mbar_wait(uint32_t b, int parity) {
  asm volatile("{\n.reg .pred p;\n.reg .u32 n;\nmov.u32 n,0;\nLW:\nmbarrier.try_wait.parity.shared::cta.b64 p,[%0],%1;\n@p bra LD;\n"
               "add.u32 n,n,1;\nsetp.lt.u32 p,n,4194304;\n@p bra LW;\nLD:\n}\n" ::"r"(b), "r"(parity) : "memory");
}
__device__ __forceinline__ void fence_init() { asm volatile("fence.mbarrier_init.release.cluster;" ::: "memory"); }
__device__ __forceinline__ void fence_async() { asm volatile("fence.proxy.async.shared::cta;" ::: "memory"); }
__device__ __forceinline__ void bulk_load(uint32_t dst, const void* src, int bytes, uint32_t bar) {
  asm volatile("cp.async.bulk.shared::cluster.global.mbarrier::complete_tx::bytes [%0],[%1],%2,[%3];" ::"r"(dst), "l"(src), "r"(bytes), "r"(bar) : "memory");
}
__device__ __forceinline__ void tma2d(uint32_t dst, const CUtensorMap* m, int c0, int c1, uint32_t bar) {
  asm volatile("cp.async.bulk.tensor.2d.shared::cluster.global.mbarrier::complete_tx::bytes [%0],[%1,{%3,%4}],[%2];" ::"r"(dst), "l"(m), "r"(bar), "r"(c0), "r"(c1) : "memory");
}
__device__ __forceinline__ void bulk_load_mc(uint32_t dst, const void* src, int bytes, uint32_t bar) {
  asm volatile("cp.async.bulk.shared::cluster.global.mbarrier::complete_tx::bytes.multicast::cluster [%0],[%1],%2,[%3],%4;" ::"r"(dst), "l"(src), "r"(bytes), "r"(bar), "h"((uint16_t)3) : "memory");
}
__device__ __forceinline__ void tma2d_mc(uint32_t dst, const CUtensorMap* m, int c0, int c1, uint32_t bar) {
  asm volatile("cp.async.bulk.tensor.2d.shared::cluster.global.mbarrier::complete_tx::bytes.multicast::cluster [%0],[%1,{%3,%4}],[%2],%5;" ::"r"(dst), "l"(m), "r"(bar), "r"(c0), "r"(c1), "h"((uint16_t)3) : "memory");
}
__device__ __forceinline__ void cluster_arrive() { asm volatile("barrier.cluster.arrive.relaxed.aligned;" ::: "memory"); }
__device__ __forceinline__ void cluster_wait() { asm volatile("barrier.cluster.wait.aligned;" ::: "memory"); }
__device__ __forceinline__ void cluster_sync() { asm volatile("barrier.cluster.arrive.release.aligned;\nbarrier.cluster.wait.acquire.aligned;" ::: "memory"); }
__device__ __forceinline__ bool mbar_test(uint32_t b, uint32_t ph) {
  uint32_t ok; asm volatile("{\n.reg .pred p;\nmbarrier.test_wait.parity.shared::cta.b64 p,[%1],%2;\nselp.u32 %0,1,0,p;\n}" : "=r"(ok) : "r"(b), "r"(ph) : "memory"); return ok;
}
__device__ __forceinline__ bool may_preload(uint32_t landed, uint32_t go) {
  for (int i = 0; i < 100000; i++) { if (mbar_test(go, 0)) return false; if (mbar_test(landed, 0)) return true; }
  return false;
}
#define PD1 2
#define PD2 2
__device__ __forceinline__ void l2_prefetch(const void* p, int bytes) { asm volatile("cp.async.bulk.prefetch.L2.global [%0],%1;" ::"l"(p), "r"(bytes) : "memory"); }
__device__ __forceinline__ void pdl_launch() { asm volatile("griddepcontrol.launch_dependents;" ::: "memory"); }
__device__ __forceinline__ void pdl_wait() { asm volatile("griddepcontrol.wait;" ::: "memory"); }
__device__ __forceinline__ void wg_fence() { asm volatile("wgmma.fence.sync.aligned;" ::: "memory"); }
__device__ __forceinline__ void wg_commit() { asm volatile("wgmma.commit_group.sync.aligned;" ::: "memory"); }
template <int N> __device__ __forceinline__ void wg_wait() { asm volatile("wgmma.wait_group.sync.aligned %0;" ::"n"(N) : "memory"); }
template <int N> __device__ __forceinline__ void reg_fence(float (&d)[N]) {
#pragma unroll
  for (int i = 0; i < N; i++) asm volatile("" : "+f"(d[i])::"memory");
}
template <int N> __device__ __forceinline__ void zero(float (&d)[N]) {
#pragma unroll
  for (int i = 0; i < N; i++) d[i] = 0.f;
  reg_fence(d);
}
__device__ __forceinline__ uint64_t mk_desc(uint32_t addr, uint32_t lbo, uint32_t sbo, uint32_t mode) {
  return (uint64_t)((addr >> 4) & 0x3FFF) | ((uint64_t)(lbo >> 4) << 16) | ((uint64_t)(sbo >> 4) << 32) | ((uint64_t)mode << 62);
}
__device__ __forceinline__ void ldsm4(uint32_t a, uint32_t (&r)[4]) {
  asm volatile("ldmatrix.sync.aligned.m8n8.x4.shared.b16 {%0,%1,%2,%3},[%4];" : "=r"(r[0]), "=r"(r[1]), "=r"(r[2]), "=r"(r[3]) : "r"(a) : "memory");
}
__device__ __forceinline__ uint32_t pack_rn(float lo, float hi) { uint32_t r; asm("cvt.rn.bf16x2.f32 %0,%1,%2;" : "=r"(r) : "f"(hi), "f"(lo)); return r; }
__device__ __forceinline__ uint32_t pack_rz(float lo, float hi) { uint32_t r; asm("cvt.rz.bf16x2.f32 %0,%1,%2;" : "=r"(r) : "f"(hi), "f"(lo)); return r; }
__device__ __forceinline__ float blo(uint32_t u) { return __uint_as_float(u << 16); }
__device__ __forceinline__ float bhi(uint32_t u) { return __uint_as_float(u & 0xFFFF0000u); }
__device__ __forceinline__ float rbf(float x) { return __bfloat162float(__float2bfloat16_rn(x)); }
__device__ __forceinline__ float qsum(float v) { v += __shfl_xor_sync(~0u, v, 1); return v + __shfl_xor_sync(~0u, v, 2); }
__device__ __forceinline__ float ex2(float x) { float r; asm("ex2.approx.ftz.f32 %0,%1;" : "=f"(r) : "f"(x)); return r; }
#define TS(k, i)
__device__ __forceinline__ void wgmma_rs_n176_t1(float (&d)[88],uint32_t a0,uint32_t a1,uint32_t a2,uint32_t a3,uint64_t db,int sc){
  asm volatile("{\n.reg .pred p;\nsetp.ne.b32 p,%93,0;\n"
    "wgmma.mma_async.sync.aligned.m64n176k16.f32.bf16.bf16 {%0,%1,%2,%3,%4,%5,%6,%7,%8,%9,%10,%11,%12,%13,%14,%15,%16,%17,%18,%19,%20,%21,%22,%23,%24,%25,%26,%27,%28,%29,%30,%31,%32,%33,%34,%35,%36,%37,%38,%39,%40,%41,%42,%43,%44,%45,%46,%47,%48,%49,%50,%51,%52,%53,%54,%55,%56,%57,%58,%59,%60,%61,%62,%63,%64,%65,%66,%67,%68,%69,%70,%71,%72,%73,%74,%75,%76,%77,%78,%79,%80,%81,%82,%83,%84,%85,%86,%87},{%88,%89,%90,%91},%92,p,1,1,1;\n}\n"
    :"+f"(d[0]),"+f"(d[1]),"+f"(d[2]),"+f"(d[3]),"+f"(d[4]),"+f"(d[5]),"+f"(d[6]),"+f"(d[7]),"+f"(d[8]),"+f"(d[9]),"+f"(d[10]),"+f"(d[11]),"+f"(d[12]),"+f"(d[13]),"+f"(d[14]),"+f"(d[15]),"+f"(d[16]),"+f"(d[17]),"+f"(d[18]),"+f"(d[19]),"+f"(d[20]),"+f"(d[21]),"+f"(d[22]),"+f"(d[23]),"+f"(d[24]),"+f"(d[25]),"+f"(d[26]),"+f"(d[27]),"+f"(d[28]),"+f"(d[29]),"+f"(d[30]),"+f"(d[31]),"+f"(d[32]),"+f"(d[33]),"+f"(d[34]),"+f"(d[35]),"+f"(d[36]),"+f"(d[37]),"+f"(d[38]),"+f"(d[39]),"+f"(d[40]),"+f"(d[41]),"+f"(d[42]),"+f"(d[43]),"+f"(d[44]),"+f"(d[45]),"+f"(d[46]),"+f"(d[47]),"+f"(d[48]),"+f"(d[49]),"+f"(d[50]),"+f"(d[51]),"+f"(d[52]),"+f"(d[53]),"+f"(d[54]),"+f"(d[55]),"+f"(d[56]),"+f"(d[57]),"+f"(d[58]),"+f"(d[59]),"+f"(d[60]),"+f"(d[61]),"+f"(d[62]),"+f"(d[63]),"+f"(d[64]),"+f"(d[65]),"+f"(d[66]),"+f"(d[67]),"+f"(d[68]),"+f"(d[69]),"+f"(d[70]),"+f"(d[71]),"+f"(d[72]),"+f"(d[73]),"+f"(d[74]),"+f"(d[75]),"+f"(d[76]),"+f"(d[77]),"+f"(d[78]),"+f"(d[79]),"+f"(d[80]),"+f"(d[81]),"+f"(d[82]),"+f"(d[83]),"+f"(d[84]),"+f"(d[85]),"+f"(d[86]),"+f"(d[87])
    :"r"(a0),"r"(a1),"r"(a2),"r"(a3),"l"(db),"r"(sc));
}
__device__ __forceinline__ void wgmma_rs_n192_t1(float (&d)[96],uint32_t a0,uint32_t a1,uint32_t a2,uint32_t a3,uint64_t db,int sc){
  asm volatile("{\n.reg .pred p;\nsetp.ne.b32 p,%101,0;\n"
    "wgmma.mma_async.sync.aligned.m64n192k16.f32.bf16.bf16 {%0,%1,%2,%3,%4,%5,%6,%7,%8,%9,%10,%11,%12,%13,%14,%15,%16,%17,%18,%19,%20,%21,%22,%23,%24,%25,%26,%27,%28,%29,%30,%31,%32,%33,%34,%35,%36,%37,%38,%39,%40,%41,%42,%43,%44,%45,%46,%47,%48,%49,%50,%51,%52,%53,%54,%55,%56,%57,%58,%59,%60,%61,%62,%63,%64,%65,%66,%67,%68,%69,%70,%71,%72,%73,%74,%75,%76,%77,%78,%79,%80,%81,%82,%83,%84,%85,%86,%87,%88,%89,%90,%91,%92,%93,%94,%95},{%96,%97,%98,%99},%100,p,1,1,1;\n}\n"
    :"+f"(d[0]),"+f"(d[1]),"+f"(d[2]),"+f"(d[3]),"+f"(d[4]),"+f"(d[5]),"+f"(d[6]),"+f"(d[7]),"+f"(d[8]),"+f"(d[9]),"+f"(d[10]),"+f"(d[11]),"+f"(d[12]),"+f"(d[13]),"+f"(d[14]),"+f"(d[15]),"+f"(d[16]),"+f"(d[17]),"+f"(d[18]),"+f"(d[19]),"+f"(d[20]),"+f"(d[21]),"+f"(d[22]),"+f"(d[23]),"+f"(d[24]),"+f"(d[25]),"+f"(d[26]),"+f"(d[27]),"+f"(d[28]),"+f"(d[29]),"+f"(d[30]),"+f"(d[31]),"+f"(d[32]),"+f"(d[33]),"+f"(d[34]),"+f"(d[35]),"+f"(d[36]),"+f"(d[37]),"+f"(d[38]),"+f"(d[39]),"+f"(d[40]),"+f"(d[41]),"+f"(d[42]),"+f"(d[43]),"+f"(d[44]),"+f"(d[45]),"+f"(d[46]),"+f"(d[47]),"+f"(d[48]),"+f"(d[49]),"+f"(d[50]),"+f"(d[51]),"+f"(d[52]),"+f"(d[53]),"+f"(d[54]),"+f"(d[55]),"+f"(d[56]),"+f"(d[57]),"+f"(d[58]),"+f"(d[59]),"+f"(d[60]),"+f"(d[61]),"+f"(d[62]),"+f"(d[63]),"+f"(d[64]),"+f"(d[65]),"+f"(d[66]),"+f"(d[67]),"+f"(d[68]),"+f"(d[69]),"+f"(d[70]),"+f"(d[71]),"+f"(d[72]),"+f"(d[73]),"+f"(d[74]),"+f"(d[75]),"+f"(d[76]),"+f"(d[77]),"+f"(d[78]),"+f"(d[79]),"+f"(d[80]),"+f"(d[81]),"+f"(d[82]),"+f"(d[83]),"+f"(d[84]),"+f"(d[85]),"+f"(d[86]),"+f"(d[87]),"+f"(d[88]),"+f"(d[89]),"+f"(d[90]),"+f"(d[91]),"+f"(d[92]),"+f"(d[93]),"+f"(d[94]),"+f"(d[95])
    :"r"(a0),"r"(a1),"r"(a2),"r"(a3),"l"(db),"r"(sc));
}
__device__ __forceinline__ void wgmma_rs_n24_t1(float (&d)[12],uint32_t a0,uint32_t a1,uint32_t a2,uint32_t a3,uint64_t db,int sc){
  asm volatile("{\n.reg .pred p;\nsetp.ne.b32 p,%17,0;\n"
    "wgmma.mma_async.sync.aligned.m64n24k16.f32.bf16.bf16 {%0,%1,%2,%3,%4,%5,%6,%7,%8,%9,%10,%11},{%12,%13,%14,%15},%16,p,1,1,1;\n}\n"
    :"+f"(d[0]),"+f"(d[1]),"+f"(d[2]),"+f"(d[3]),"+f"(d[4]),"+f"(d[5]),"+f"(d[6]),"+f"(d[7]),"+f"(d[8]),"+f"(d[9]),"+f"(d[10]),"+f"(d[11])
    :"r"(a0),"r"(a1),"r"(a2),"r"(a3),"l"(db),"r"(sc));
}
__device__ __forceinline__ void wgmma_rs_n64_t0(float (&d)[32],uint32_t a0,uint32_t a1,uint32_t a2,uint32_t a3,uint64_t db,int sc){
  asm volatile("{\n.reg .pred p;\nsetp.ne.b32 p,%37,0;\n"
    "wgmma.mma_async.sync.aligned.m64n64k16.f32.bf16.bf16 {%0,%1,%2,%3,%4,%5,%6,%7,%8,%9,%10,%11,%12,%13,%14,%15,%16,%17,%18,%19,%20,%21,%22,%23,%24,%25,%26,%27,%28,%29,%30,%31},{%32,%33,%34,%35},%36,p,1,1,0;\n}\n"
    :"+f"(d[0]),"+f"(d[1]),"+f"(d[2]),"+f"(d[3]),"+f"(d[4]),"+f"(d[5]),"+f"(d[6]),"+f"(d[7]),"+f"(d[8]),"+f"(d[9]),"+f"(d[10]),"+f"(d[11]),"+f"(d[12]),"+f"(d[13]),"+f"(d[14]),"+f"(d[15]),"+f"(d[16]),"+f"(d[17]),"+f"(d[18]),"+f"(d[19]),"+f"(d[20]),"+f"(d[21]),"+f"(d[22]),"+f"(d[23]),"+f"(d[24]),"+f"(d[25]),"+f"(d[26]),"+f"(d[27]),"+f"(d[28]),"+f"(d[29]),"+f"(d[30]),"+f"(d[31])
    :"r"(a0),"r"(a1),"r"(a2),"r"(a3),"l"(db),"r"(sc));
}
__device__ __forceinline__ void wgmma_ss_n128_t1(float (&d)[64],uint64_t da,uint64_t db,int sc){
  asm volatile("{\n.reg .pred p;\nsetp.ne.b32 p,%66,0;\n"
    "wgmma.mma_async.sync.aligned.m64n128k16.f32.bf16.bf16 {%0,%1,%2,%3,%4,%5,%6,%7,%8,%9,%10,%11,%12,%13,%14,%15,%16,%17,%18,%19,%20,%21,%22,%23,%24,%25,%26,%27,%28,%29,%30,%31,%32,%33,%34,%35,%36,%37,%38,%39,%40,%41,%42,%43,%44,%45,%46,%47,%48,%49,%50,%51,%52,%53,%54,%55,%56,%57,%58,%59,%60,%61,%62,%63},%64,%65,p,1,1,0,1;\n}\n"
    :"+f"(d[0]),"+f"(d[1]),"+f"(d[2]),"+f"(d[3]),"+f"(d[4]),"+f"(d[5]),"+f"(d[6]),"+f"(d[7]),"+f"(d[8]),"+f"(d[9]),"+f"(d[10]),"+f"(d[11]),"+f"(d[12]),"+f"(d[13]),"+f"(d[14]),"+f"(d[15]),"+f"(d[16]),"+f"(d[17]),"+f"(d[18]),"+f"(d[19]),"+f"(d[20]),"+f"(d[21]),"+f"(d[22]),"+f"(d[23]),"+f"(d[24]),"+f"(d[25]),"+f"(d[26]),"+f"(d[27]),"+f"(d[28]),"+f"(d[29]),"+f"(d[30]),"+f"(d[31]),"+f"(d[32]),"+f"(d[33]),"+f"(d[34]),"+f"(d[35]),"+f"(d[36]),"+f"(d[37]),"+f"(d[38]),"+f"(d[39]),"+f"(d[40]),"+f"(d[41]),"+f"(d[42]),"+f"(d[43]),"+f"(d[44]),"+f"(d[45]),"+f"(d[46]),"+f"(d[47]),"+f"(d[48]),"+f"(d[49]),"+f"(d[50]),"+f"(d[51]),"+f"(d[52]),"+f"(d[53]),"+f"(d[54]),"+f"(d[55]),"+f"(d[56]),"+f"(d[57]),"+f"(d[58]),"+f"(d[59]),"+f"(d[60]),"+f"(d[61]),"+f"(d[62]),"+f"(d[63])
    :"l"(da),"l"(db),"r"(sc));
}
__device__ __forceinline__ void wgmma_ss_n64_t1(float (&d)[32],uint64_t da,uint64_t db,int sc){
  asm volatile("{\n.reg .pred p;\nsetp.ne.b32 p,%34,0;\n"
    "wgmma.mma_async.sync.aligned.m64n64k16.f32.bf16.bf16 {%0,%1,%2,%3,%4,%5,%6,%7,%8,%9,%10,%11,%12,%13,%14,%15,%16,%17,%18,%19,%20,%21,%22,%23,%24,%25,%26,%27,%28,%29,%30,%31},%32,%33,p,1,1,0,1;\n}\n"
    :"+f"(d[0]),"+f"(d[1]),"+f"(d[2]),"+f"(d[3]),"+f"(d[4]),"+f"(d[5]),"+f"(d[6]),"+f"(d[7]),"+f"(d[8]),"+f"(d[9]),"+f"(d[10]),"+f"(d[11]),"+f"(d[12]),"+f"(d[13]),"+f"(d[14]),"+f"(d[15]),"+f"(d[16]),"+f"(d[17]),"+f"(d[18]),"+f"(d[19]),"+f"(d[20]),"+f"(d[21]),"+f"(d[22]),"+f"(d[23]),"+f"(d[24]),"+f"(d[25]),"+f"(d[26]),"+f"(d[27]),"+f"(d[28]),"+f"(d[29]),"+f"(d[30]),"+f"(d[31])
    :"l"(da),"l"(db),"r"(sc));
}

__device__ __forceinline__ float silu_bf(bf16 c) { const float x = __bfloat162float(c); return rbf(x / (1.f + __expf(-x))); }
__device__ __forceinline__ void fma8(float (&a)[8], float s, const uint4& v) {
  a[0] += s * blo(v.x); a[1] += s * bhi(v.x); a[2] += s * blo(v.y); a[3] += s * bhi(v.y);
  a[4] += s * blo(v.z); a[5] += s * bhi(v.z); a[6] += s * blo(v.w); a[7] += s * bhi(v.w);
}
__device__ __forceinline__ float red8(float (&a)[8], int lane) {
#pragma unroll
  for (int w = 4; w >= 1; w >>= 1) {
    const bool up = lane & (w * 4);
#pragma unroll
    for (int j = 0; j < w; j++) a[j] = (up ? a[j + w] : a[j]) + __shfl_xor_sync(~0u, up ? a[j] : a[j + w], w * 4);
  }
  return a[0];
}
__device__ __forceinline__ float mod_fin(float s, int n) { s = rbf(s); return ((n >> 9) == 1 || (n >> 9) == 4) ? rbf(1.f + s) : s; }
__device__ __forceinline__ void poll(uint2& a, uint2& b, float (&w)[16], const uint32_t* p, const uint32_t* q) {
  asm volatile("{\n.reg .pred p;\n.reg .b32 n,t,u;\nmov.u32 n,0;\nLW:\nld.relaxed.gpu.global.v2.u32 {%0,%1},[%20];\nld.relaxed.gpu.global.v2.u32 {%2,%3},[%20+64];\n"
               "ld.relaxed.gpu.global.v4.f32 {%4,%5,%6,%7},[%21];\nld.relaxed.gpu.global.v4.f32 {%8,%9,%10,%11},[%21+16];\n"
               "ld.relaxed.gpu.global.v4.f32 {%12,%13,%14,%15},[%21+8192];\nld.relaxed.gpu.global.v4.f32 {%16,%17,%18,%19},[%21+8208];\n"
               "lop3.b32 t,%0,%1,%2,0x80;\nlop3.b32 u,%3,%4,%5,0x80;\nlop3.b32 t,t,%6,%7,0x80;\nlop3.b32 u,u,%8,%9,0x80;\nlop3.b32 t,t,%10,%11,0x80;\n"
               "lop3.b32 u,u,%12,%13,0x80;\nlop3.b32 t,t,%14,%15,0x80;\nlop3.b32 u,u,%16,%17,0x80;\nlop3.b32 t,t,%18,%19,0x80;\nlop3.b32 t,t,u,1,0x80;\n"
               "setp.ne.u32 p,t,0;\n@p bra LD;\nadd.u32 n,n,1;\nsetp.lt.u32 p,n,1048576;\n@p bra LW;\nLD:\n}\n"
               : "=&r"(a.x), "=&r"(a.y), "=&r"(b.x), "=&r"(b.y), "=&f"(w[0]), "=&f"(w[1]), "=&f"(w[2]), "=&f"(w[3]), "=&f"(w[4]), "=&f"(w[5]), "=&f"(w[6]), "=&f"(w[7]),
                 "=&f"(w[8]), "=&f"(w[9]), "=&f"(w[10]), "=&f"(w[11]), "=&f"(w[12]), "=&f"(w[13]), "=&f"(w[14]), "=&f"(w[15]) : "l"(p), "l"(q) : "memory");
}

constexpr int LN_SMEM = 131072 + 4 * 24576 + 2816 + 256;
#define TANH 1
#define DLY 2
template <bool FFN>
__global__ void __cluster_dims__(2, 1, 1) __launch_bounds__(384, 1) k_lngemm(const __grid_constant__ CUtensorMap mX, const __grid_constant__ CUtensorMap mB0,
                                                   const __grid_constant__ CUtensorMap mB1, const bf16* __restrict__ cv, const bf16* __restrict__ wm, const bf16* __restrict__ xg, const bf16* wq) {
  extern __shared__ __align__(1024) uint8_t smem[];
  const uint32_t sA = smem_u32(smem), sB = sA + (FFN ? 81920 : 131072), sM = sA + 229376, bars = sM + 2816;
  const uint32_t bA = bars, bF = bars + 64, bE = bars + 112;
  constexpr int NB = FFN ? 6 : 4;
  const int tid = threadIdx.x, warp = tid >> 5, lane = tid & 31;
  const int pr = blockIdx.x & 1, rb = FFN ? (blockIdx.x >> 4) * 2 + pr : blockIdx.x >> 3, ct = FFN ? (blockIdx.x >> 1) & 7 : blockIdx.x & 7;
  constexpr int NST = FFN ? 16 : 8, KS = FFN ? 2 : 4, BOX = FFN ? 4096 : 8192;
  TS(FFN ? 4 : 1, 0);
  pdl_launch();
  float* red = (float*)(smem + (sM - sA));
  if (tid == 256) {
    for (int i = 0; i < 8; i++) mbar_init(bA + 8 * i, 1);
    for (int i = 0; i < NB; i++) { mbar_init(bF + 8 * i, 1); mbar_init(bE + 8 * i, FFN ? 16 : 8); }
    mbar_init(bars + 160, 1);
    fence_init();
  }
  __syncwarp();
  cluster_arrive();
  uint4 wv0, wv1, xv[4];
  bf16 cv0, cv1;
  if (!FFN && tid < 256) {
    const int r = (blockIdx.x & 3) * 128 + (tid >> 2);
    const uint4* wp = (const uint4*)(wm + r * 3072 + (blockIdx.x >> 2) * 32 + (tid & 3) * 8);
    wv0 = __ldg(wp); wv1 = __ldg(wp + 64 * 384);
    cv0 = cv[r]; cv1 = cv[r + 64];
#pragma unroll
    for (int i = 0; i < 4; i++) xv[i] = __ldg((const uint4*)(xg + (blockIdx.x * 16 + (tid >> 4)) * 512 + i * 128 + (tid & 15) * 8));
  }
  cluster_wait();
  if (warp >= 8) {
    asm volatile("setmaxnreg.dec.sync.aligned.u32 40;");
    if (tid == 256) {
      auto loadB = [&](int s) {
        const uint32_t d = sB + (s % NB) * 24576, b = bF + (s % NB) * 8;
        mbar_expect(b, 24576);
        for (int j = 0; j < 3; j++) {
          if (FFN) tma2d_mc(d + (pr * 3 + j) * BOX, pr ? &mB1 : &mB0, ct * 176 + j * 64, s * 32, b);
          else tma2d(d + j * BOX, &mB0, ct * 192 + j * 64, s * 64, b);
        }
      };
      for (int i = 0; i < 8; i++) mbar_expect(bA + 8 * i, 16384);
      if (!FFN) l2_prefetch((const char*)wq + blockIdx.x * 12288, 12288);
      int nb = 0;
      for (int s = 0; s < NB; s++, nb++) {
        const int i = s * 2 + (ct & 1);
        if (FFN && s >= PD1 && !may_preload(bF + (s - PD1) * 8, bars + 160)) break;
        if (!FFN && s == DLY) mbar_wait(bars + 160, 0);
        if (!FFN) tma2d_mc(sA + i * 16384, &mX, i * 64, rb * 128, bA + 8 * i);
        loadB(s);
      }
      if (FFN) {
        pdl_wait();
        for (int i = 0; i < 5; i++) {
          bulk_load(sA + i * 16384, g_a + (rb * 64 + i * 8) * 1024, 16384, bA + 8 * i);
          for (; nb < 2 * i + 2 && nb < NB; nb++) loadB(nb);
        }
      }
      for (int s = NB; s < NST; s++) {
        mbar_wait(bE + (s % NB) * 8, (s / NB - 1) & 1); loadB(s);
        if (FFN && s <= 10 && !(s & 1)) bulk_load(sA + (s / 2 - 3) * 16384, g_a + (rb * 64 + (s / 2 + 2) * 8) * 1024, 16384, bA + 8 * (s / 2 + 2));
      }
    }
  } else {
  asm volatile("setmaxnreg.inc.sync.aligned.u32 232;");
  const int g = lane >> 2, t = lane & 3;
  const int lr = warp * 16 + (lane & 7) + ((lane >> 3) & 1) * 8;
  auto aaddr = [&](int ks) -> uint32_t {
    if (FFN) return sA + ((ks < 20 ? ks : ks - 20) * 2 + (lane >> 4)) * 2048 + lr * 16;
    return sA + (ks >> 2) * 16384 + lr * 128 + ((((ks & 3) * 2 + (lane >> 4)) ^ (lr & 7)) << 4);
  };
  const int row0 = rb * 128 + warp * 16 + g;
  float2 msh, msc;
  float4 p0, p1, uv;
  float rs0, rs1, nm0, nm1;
  if (!FFN) {
    {
      float a[8] = {0, 0, 0, 0, 0, 0, 0, 0};
      fma8(a, silu_bf(cv0), wv0); fma8(a, silu_bf(cv1), wv1);
      red[warp * 32 + t * 8 + g] = red8(a, lane);
      asm volatile("bar.sync 1,256;" ::: "memory");
      if (tid < 32) {
        float r = 0;
#pragma unroll
        for (int i = 0; i < 8; i++) r += red[i * 32 + tid];
        asm volatile("st.relaxed.gpu.global.u32 [%0],%1;" ::"l"(g_modv + ((blockIdx.x >> 2) * 32 + tid) * 4 + (blockIdx.x & 3)), "r"(__float_as_uint(r) | 1u) : "memory");
      }
      TS(0, 1);
    }
    {
      float v[32], s = 0, q = 0;
#pragma unroll
      for (int i = 0; i < 16; i++) { const uint32_t u = ((const uint32_t*)xv)[i]; v[2 * i] = blo(u); v[2 * i + 1] = bhi(u); s += v[2 * i] + v[2 * i + 1]; }
      s = qsum(s); s += __shfl_xor_sync(~0u, s, 4); s += __shfl_xor_sync(~0u, s, 8);
      const float m = s * (1.f / 512);
#pragma unroll
      for (int i = 0; i < 32; i++) q += (v[i] - m) * (v[i] - m);
      q = qsum(q); q += __shfl_xor_sync(~0u, q, 4); q += __shfl_xor_sync(~0u, q, 8);
      const float rs = rsqrtf(q * (1.f / 512) + 1e-5f);
      if ((tid & 15) == 0)
        asm volatile("st.relaxed.gpu.global.v2.u32 [%0],{%1,%2};" ::"l"(g_modv + 4096 + (blockIdx.x * 16 + (tid >> 4)) * 2), "r"(__float_as_uint(rs) | 1u), "r"(__float_as_uint(-m * rs) | 1u) : "memory");
    }
    uint2 q0, q1;
    float w[16];
    if (tid < 128) {
      uint32_t v; int n = 0;
      do asm volatile("ld.relaxed.gpu.global.u32 %0,[%1];" : "=r"(v) : "l"(g_modv + (tid >> 2) * 128 + (tid & 3)) : "memory"); while (!(v & 1) && ++n < 1048576);
    }
    asm volatile("bar.sync 1,256;" ::: "memory");
    poll(q0, q1, w, g_modv + 4096 + row0 * 2, g_modv + tid * 8);
    msh = make_float2(mod_fin(w[0] + w[1] + w[2] + w[3], 0), mod_fin(w[4] + w[5] + w[6] + w[7], 0));
    msc = make_float2(mod_fin(w[8] + w[9] + w[10] + w[11], 512), mod_fin(w[12] + w[13] + w[14] + w[15], 512));
    asm volatile("bar.sync 1,256;" ::: "memory");
    if (tid == 32) mbar_arrive(bars + 160);
    rs0 = __uint_as_float(q0.x); nm0 = __uint_as_float(q0.y); rs1 = __uint_as_float(q1.x); nm1 = __uint_as_float(q1.y);
  } else {
    pdl_wait();
    if (tid == 32) mbar_arrive(bars + 160);
    TS(4, 1);
    p0 = *(const float4*)(g_st + row0 * 8 + t * 2); p1 = *(const float4*)(g_st + (row0 + 8) * 8 + t * 2);
    if (tid < 176) uv = *(const float4*)(g_uv + (tid >= 88 ? 1408 - 176 : 0) + ct * 176 + tid * 2);
  }
  if (!FFN) {
    uint32_t* m = (uint32_t*)(smem + (sM - sA)) + (tid >> 3) * 16 + (tid & 3) * 4 + ((tid >> 2) & 1);
    m[0] = pack_rn(msc.x, msc.y); m[2] = pack_rn(msh.x, msh.y);
    asm volatile("bar.sync 1,256;" ::: "memory");
  }
  constexpr int NA = FFN ? 88 : 96;
  float acc0[NA], acc1[FFN ? 88 : 1];
  uint32_t a[2][KS][4];
  auto prep = [&](int ks, uint32_t(&o)[4]) {
    if ((ks & 3) == 0) mbar_wait(bA + 2 * ks, 0);
    if (FFN) { ldsm4(aaddr(ks), o); return; }
    uint32_t r[4]; ldsm4(aaddr(ks), r);
    const uint4 m = *(const uint4*)(smem + (sM - sA) + ks * 64 + t * 16);
#pragma unroll
    for (int i = 0; i < 4; i++) {
      const float rs = (i & 1) ? rs1 : rs0, nm = (i & 1) ? nm1 : nm0;
      const uint32_t n = pack_rn(fmaf(blo(r[i]), rs, nm), fmaf(bhi(r[i]), rs, nm));
      asm("fma.rn.bf16x2 %0,%1,%2,%3;" : "=r"(o[i]) : "r"(n), "r"(i < 2 ? m.x : m.y), "r"(i < 2 ? m.z : m.w));
    }
  };
  auto stage = [&](int s, uint32_t(&c)[KS][4], uint32_t(&n)[KS][4]) {
    mbar_wait(bF + (s % NB) * 8, (s / NB) & 1);
    const uint64_t db = mk_desc(sB + (s % NB) * 24576, BOX, 1024, 1);
    wg_fence();
#pragma unroll
    for (int k = 0; k < KS; k++) {
      if constexpr (FFN) {
        wgmma_rs_n176_t1(acc0, c[k][0], c[k][1], c[k][2], c[k][3], db + k * 128, s + k);
        wgmma_rs_n176_t1(acc1, c[k][0], c[k][1], c[k][2], c[k][3], db + k * 128 + 3 * BOX / 16, s + k);
      } else {
        wgmma_rs_n192_t1(acc0, c[k][0], c[k][1], c[k][2], c[k][3], db + k * 128, s + k);
      }
    }
    wg_commit();
    wg_wait<1>();
    if (s > 0 && s <= NST - NB) {
      if (!FFN) { if (lane == 0) mbar_arrive(bE + ((s - 1) % NB) * 8); }
      else if (lane < 2) asm volatile("{\n.reg .b32 r;\nmapa.shared::cluster.u32 r,%0,%1;\nmbarrier.arrive.relaxed.cluster.shared::cluster.b64 _,[r];\n}" ::"r"(bE + ((s - 1) % NB) * 8), "r"(lane) : "memory");
    }
    if (s < NST - 1) {
#pragma unroll
      for (int k = 0; k < KS; k++) prep((s + 1) * KS + k, n[k]);
    }
  };
#pragma unroll
  for (int k = 0; k < KS; k++) prep(k, a[0][k]);
  TS(FFN ? 4 : 1, 2);
#pragma unroll 1
  for (int s = 0; s < NST; s += 2) { stage(s, a[0], a[1]); stage(s + 1, a[1], a[0]); }
  if (FFN) {
    if (tid < 88) { uv.x *= 0.5f; uv.y *= 0.5f; uv.z *= 0.5f; uv.w *= 0.5f; }
    if (tid < 176) *(float4*)(smem + (sM - sA) + tid * 16) = uv;
    const float m0 = qsum(p0.x + p0.z) * 0.125f, m1 = qsum(p1.x + p1.z) * 0.125f;
    const float v0 = qsum(p0.y + p0.w + 64.f * ((p0.x - m0) * (p0.x - m0) + (p0.z - m0) * (p0.z - m0)));
    const float v1 = qsum(p1.y + p1.w + 64.f * ((p1.x - m1) * (p1.x - m1) + (p1.z - m1) * (p1.z - m1)));
    rs0 = rsqrtf(v0 * (1.f / 512) + 1e-5f); rs1 = rsqrtf(v1 * (1.f / 512) + 1e-5f);
    nm0 = -m0 * rs0; nm1 = -m1 * rs1;
    asm volatile("bar.sync 1,256;" ::: "memory");
  }
  wg_wait<0>();
  reg_fence(acc0);
  TS(FFN ? 4 : 1, 3);
  if constexpr (FFN) {
    reg_fence(acc1);
    const float rh0 = 0.5f * rs0, rh1 = 0.5f * rs1;
    uint32_t* o = (uint32_t*)g_h + ((rb * 172 + ct * 22) * 128 + warp * 16 + g) * 4 + t;
#pragma unroll
    for (int j = 0; j < 22; j++) {
      {
        const float4 u1 = *(const float4*)(smem + (sM - sA) + (j * 4 + t) * 16), u3 = *(const float4*)(smem + (sM - sA) + (88 + j * 4 + t) * 16);
        float h[4];
#pragma unroll
        for (int i = 0; i < 4; i++) {
          const float rs = i < 2 ? rs0 : rs1, nm = i < 2 ? nm0 : nm1, rh = i < 2 ? rh0 : rh1;
          const float z = fmaf(rh, acc0[4 * j + i], (i & 1) ? fmaf(nm, u1.z, u1.w) : fmaf(nm, u1.x, u1.y));
          const float y = fmaf(rs, acc1[4 * j + i], (i & 1) ? fmaf(nm, u3.z, u3.w) : fmaf(nm, u3.x, u3.y));
          float th; asm("tanh.approx.f32 %0,%1;" : "=f"(th) : "f"(z));
          h[i] = fmaf(z, th, z) * y;
        }
        if (j < 18 || ct < 7) { o[j * 512] = pack_rn(h[0], h[1]); o[j * 512 + 32] = pack_rn(h[2], h[3]); }
      }
    }
  } else {
    uint32_t* o = (uint32_t*)g_qkv + (ct * 24 * 2048 + row0) * 4 + t;
#pragma unroll
    for (int j = 0; j < 24; j += 2) {
      const int G = ct * 24 + j;
      const float sc = G < 64 ? 0.25f * 1.4426950408889634f : 1.f;
      uint32_t p[4];
#pragma unroll
      for (int i = 0; i < 4; i++) p[i] = pack_rn(acc0[4 * j + 2 * i] * sc, acc0[4 * j + 2 * i + 1] * sc);
      o[j * 8192] = p[0]; o[j * 8192 + 32] = p[1]; o[(j + 1) * 8192] = p[2]; o[(j + 1) * 8192 + 32] = p[3];
      if (G >= 64 && G < 128) {
        float n0 = blo(p[0]) * blo(p[0]) + bhi(p[0]) * bhi(p[0]) + blo(p[2]) * blo(p[2]) + bhi(p[2]) * bhi(p[2]);
        float n1 = blo(p[1]) * blo(p[1]) + bhi(p[1]) * bhi(p[1]) + blo(p[3]) * blo(p[3]) + bhi(p[3]) * bhi(p[3]);
        n0 = qsum(n0); n1 = qsum(n1);
        const uint32_t mx = __reduce_max_sync(~0u, max(__float_as_uint(n0), __float_as_uint(n1)));
        if (lane == 0) g_kmax[((G - 64) >> 1) * 128 + rb * 8 + warp] = __uint_as_float(mx);
      }
    }
  }
  TS(FFN ? 4 : 1, 4);
}
}

#define SMASK 0xCCCCu
#define BRK 0
#define PACK 1
constexpr int AT_SMEM = 5 * 32768 + 256;
__device__ __forceinline__ uint32_t exp2_pair_fma(float s0, float s1, float c, uint32_t ka, uint32_t kz) {
  uint32_t r;
  asm volatile("{\n.reg .b32 y0,y1,e,u,t;\n"
      "fma.rn.sat.f32 y0,%1,0f00000080,%3;\nfma.rn.sat.f32 y1,%2,0f00000080,%3;\n"
      "mad.lo.u32 e,y1,65536,y0;\n"
      "and.b32 u,e,0x007F007F;\n"
      "fma.rn.f16x2 u,u,%4,%5;\nfma.rn.f16x2 t,u,u,%6;\nfma.rn.f16x2 t,t,u,%7;\n"
      "lop3.b32 %0,t,0x007F007F,e,0xE2;\n}\n"
      : "=r"(r) : "f"(s0), "f"(s1), "f"(c), "r"(ka), "r"(0x36B236B2u), "r"(0x3C733C73u), "r"(0x47764776u), "r"(kz));
  return r;
}
__device__ __forceinline__ void attn_pass(float (&oa)[12], float (&ob)[12], const uint32_t (&q)[4], float m0, float m1, uint32_t sK, uint32_t bars, bool first, uint32_t kz) {
  uint64_t dk = mk_desc(sK, 32768, 128, 0), dv = mk_desc(sK + 65536, 128, 32768, 0);
  const float c0 = (127.f - m0) * __uint_as_float(0x80u), c1 = (127.f - m1) * __uint_as_float(0x80u);
  uint32_t ka;
  asm volatile("mov.b32 %0,0x7ACE7ACE;" : "=r"(ka));
  constexpr int NK = 64, NS = 32, NP = 16;
  auto qk = [&](float (&s)[NS], int i) { wgmma_rs_n64_t0(s, q[0], q[1], q[2], q[3], dk + i * NK, 0); };
  auto softmax = [&](float (&s)[NS], uint32_t (&p)[NP], uint32_t mask) {
    reg_fence(s);
    float e0, e1;
    int pend = -1;
#pragma unroll
    for (int t = 0; t < NP; t++) {
      const int j = (t & 3) * 4 + (t >> 2);
      if ((mask >> (t & 3)) & 1) {
        p[j] = exp2_pair_fma(s[2 * j], s[2 * j + 1], (j & 1) ? c1 : c0, ka, kz);
      } else {
        float f0, f1;
        asm volatile("ex2.approx.ftz.f32 %0,%2;\nex2.approx.ftz.f32 %1,%3;" : "=&f"(f0), "=f"(f1) : "f"(s[2 * j]), "f"(s[2 * j + 1]));
        if (pend >= 0) asm volatile("cvt.rn.bf16x2.f32 %0,%1,%2;" : "=r"(p[pend]) : "f"(e1), "f"(e0));
        e0 = f0; e1 = f1; pend = j;
      }
    }
    if (pend >= 0) asm volatile("cvt.rn.bf16x2.f32 %0,%1,%2;" : "=r"(p[pend]) : "f"(e1), "f"(e0));
#pragma unroll
    for (int j = 0; j < NP; j++) asm volatile("" : "+r"(p[j])::"memory");
  };
  auto pv = [&](uint32_t (&p)[NP], int i, uint32_t mask) {
#pragma unroll
    for (int k = 0; k < 4; k++) wgmma_rs_n24_t1(((mask >> k) & 1) ? ob : oa, p[4 * k], p[4 * k + 1], p[4 * k + 2], p[4 * k + 3], dv + i * NK + k * 16, 1);
  };
  constexpr uint32_t M0 = SMASK & 15, M1 = (SMASK >> 4) & 15, M2 = (SMASK >> 8) & 15, M3 = SMASK >> 12;
  zero(oa); zero(ob);
  mbar_wait(bars, 0);
  if (first) TS(2, 2);
  float s[NS];
  zero(s);
  uint32_t p0[NP], p1[NP];
  auto step = [&](int i, uint32_t (&pa)[NP], uint32_t ma, uint32_t (&pb)[NP], uint32_t mb) {
    wg_fence(); qk(s, i + 1); wg_commit(); pv(pa, i, ma); wg_commit(); wg_wait<1>(); softmax(s, pb, mb); wg_wait<0>();
  };
  wg_fence(); qk(s, 0); wg_commit(); wg_wait<0>(); softmax(s, p0, M0);
#pragma unroll 1
  for (uint32_t b = bars + 8; b < bars + 64; b += 8) {
    step(0, p0, M0, p1, M1); step(1, p1, M1, p0, M2); step(2, p0, M2, p1, M3);
    mbar_wait(b, 0);
    step(3, p1, M3, p0, M0);
    dk += 4 * NK; dv += 4 * NK;
  }
  step(0, p0, M0, p1, M1); step(1, p1, M1, p0, M2); step(2, p0, M2, p1, M3);
  wg_fence(); pv(p1, 3, M3); wg_commit();
  wg_wait<0>();
  reg_fence(oa); reg_fence(ob);
}
__device__ __forceinline__ void mma16816(float (&d)[4], const uint32_t (&a)[4], uint32_t b0, uint32_t b1) {
  asm("mma.sync.aligned.m16n8k16.row.col.f32.bf16.bf16.f32 {%0,%1,%2,%3},{%4,%5,%6,%7},{%8,%9},{%0,%1,%2,%3};"
      : "+f"(d[0]), "+f"(d[1]), "+f"(d[2]), "+f"(d[3]) : "r"(a[0]), "r"(a[1]), "r"(a[2]), "r"(a[3]), "r"(b0), "r"(b1));
}
__device__ __forceinline__ void attn_safe(float (&o)[12], const uint32_t (&q)[4], uint32_t sK) {
  const int lane = threadIdx.x & 31;
  const uint32_t ka = sK + (lane >> 4) * 32768 + (lane & 15) * 16;
  float m0 = -INFINITY, m1 = -INFINITY;
#pragma unroll 2
  for (int i = 0; i < 128; i++) {
    uint32_t k[4]; ldsm4(ka + i * 256, k);
    float s0[4] = {0, 0, 0, 0}, s1[4] = {0, 0, 0, 0};
    mma16816(s0, q, k[0], k[2]); mma16816(s1, q, k[1], k[3]);
    m0 = fmaxf(fmaxf(m0, fmaxf(s0[0], s0[1])), fmaxf(s1[0], s1[1])); m1 = fmaxf(fmaxf(m1, fmaxf(s0[2], s0[3])), fmaxf(s1[2], s1[3]));
  }
  m0 = fmaxf(m0, __shfl_xor_sync(~0u, m0, 1)); m0 = fmaxf(m0, __shfl_xor_sync(~0u, m0, 2));
  m1 = fmaxf(m1, __shfl_xor_sync(~0u, m1, 1)); m1 = fmaxf(m1, __shfl_xor_sync(~0u, m1, 2));
  float o0[4] = {0, 0, 0, 0}, o1[4] = {0, 0, 0, 0}, o2[4] = {0, 0, 0, 0};
#pragma unroll 2
  for (int i = 0; i < 128; i++) {
    uint32_t k[4], v[4]; ldsm4(ka + i * 256, k);
    asm volatile("ldmatrix.sync.aligned.m8n8.x4.trans.shared.b16 {%0,%1,%2,%3},[%4];" : "=r"(v[0]), "=r"(v[1]), "=r"(v[2]), "=r"(v[3]) : "r"(ka + 65536 + i * 256) : "memory");
    float s0[4] = {0, 0, 0, 0}, s1[4] = {0, 0, 0, 0};
    mma16816(s0, q, k[0], k[2]); mma16816(s1, q, k[1], k[3]);
    const uint32_t p[4] = {pack_rn(ex2(s0[0] - m0), ex2(s0[1] - m0)), pack_rn(ex2(s0[2] - m1), ex2(s0[3] - m1)),
                           pack_rn(ex2(s1[0] - m0), ex2(s1[1] - m0)), pack_rn(ex2(s1[2] - m1), ex2(s1[3] - m1))};
    mma16816(o0, p, v[0], v[1]); mma16816(o1, p, v[2], v[3]); mma16816(o2, p, 0x3F803F80u, 0x3F803F80u);
  }
#pragma unroll
  for (int i = 0; i < 4; i++) { o[i] = o0[i]; o[4 + i] = o1[i]; o[8 + i] = o2[i]; }
}
__global__ void __cluster_dims__(2, 1, 1) __launch_bounds__(512, 1) k_attn(const bf16* wo, const bf16* w1, const bf16* w3, const bf16* w2, const bf16* __restrict__ cv, const bf16* __restrict__ wm, uint32_t kz) {
  extern __shared__ __align__(1024) uint8_t smem[];
  const uint32_t sK = smem_u32(smem), bars = sK + 5 * 32768;
  const int tid = threadIdx.x, warp = tid >> 5, lane = tid & 31, g = lane >> 2, t = lane & 3;
  pdl_launch();
  if (blockIdx.x < 4) {
    float* cs = (float*)smem;
    cs[tid] = silu_bf(cv[tid]);
    cluster_sync();
    const int b = blockIdx.x;
    float *mv = cs + 512, *rd = cs + 1536;
    auto put8 = [&](float* d, float (&a)[8]) { ((float4*)d)[0] = make_float4(a[0], a[1], a[2], a[3]); ((float4*)d)[1] = make_float4(a[4], a[5], a[6], a[7]); };
    for (int ph = 0; ph < 2; ph++) {
      const int nc = 512 >> ph, n0 = ph ? (b >> 1) * 1536 + 1024 + (b & 1) * 256 : 1536 + (b & 1) * 512, nr = 64 >> ph, r0 = tid / nr * nr;
      float a[8] = {0, 0, 0, 0, 0, 0, 0, 0};
#pragma unroll 16
      for (int r = r0; r < r0 + nr; r++) fma8(a, cs[r], __ldg((const uint4*)(wm + r * 3072 + n0 + (tid & (nr - 1)) * 8)));
      put8(rd + tid * 8, a);
      __syncthreads();
      if (tid < nc) {
        float s = 0;
        for (int i = tid; i < 4096; i += nc) s += rd[i];
        s = mod_fin(s, n0 + tid);
        if (ph || b < 2) g_mod[n0 + tid] = s;
        if (!ph) {
          mv[(b & 1) * 512 + tid] = s;
          asm volatile("{\n.reg .b32 r;\nmapa.shared::cluster.u32 r,%0,%1;\nst.shared::cluster.f32 [r],%2;\n}" ::"r"(smem_u32(mv + (b & 1) * 512 + tid)), "r"((b & 1) ^ 1), "f"(s) : "memory");
        }
      }
      cluster_sync();
    }
    if (tid < 430) {
      const bf16* w = (b >> 1 ? w3 : w1) + (b & 1) * 688 + tid % 86 * 8;
      float u[8] = {0, 0, 0, 0, 0, 0, 0, 0}, v[8] = {0, 0, 0, 0, 0, 0, 0, 0};
#pragma unroll 13
      for (int r = tid / 86; r < 512; r += 5) { const uint4 x = __ldg((const uint4*)(w + r * 1376)); fma8(u, mv[512 + r], x); fma8(v, mv[r], x); }
      put8(rd + tid * 8, u); put8(rd + 3440 + tid * 8, v);
    }
    __syncthreads();
    for (int n = tid; n < 688; n += 512) {
      float u = 0, v = 0;
      for (int i = n; i < 3440; i += 688) { u += rd[i]; v += rd[3440 + i]; }
      g_uv[(b >> 1) * 1408 + (b & 1) * 688 + n] = make_float2(u, v);
    }
    TS(0, 7);
    return;
  }
  const int bid = blockIdx.x - 4, h = bid >> 2, qb = bid & 3;
  TS(2, 0);
  if (tid == 0) { for (int i = 0; i < 8; i++) { mbar_init(bars + 8 * i, 1); mbar_expect(bars + 8 * i, 16384); } fence_init(); }
#pragma unroll
  for (int i = 0; i < 4; i++) *(uint4*)(smem + 131072 + i * 8192 + tid * 16) = make_uint4(0x3F803F80u, 0x3F803F80u, 0x3F803F80u, 0x3F803F80u);
  fence_async();
  cluster_sync();
  pdl_wait();
  TS(2, 1);
  if (tid >= 448) g_modv[bid * 64 + tid - 448] = 0;
  const uint4 km4 = *(const uint4*)(g_kmax + h * 128 + lane * 4);
  const uint32_t* qp = (const uint32_t*)g_qkv + (h * 2 * 2048 + qb * 512 + warp * 16 + g) * 4 + t;
  uint32_t q[4] = {qp[0], qp[32], qp[8192], qp[8192 + 32]};
  auto ldkv = [&]() {
    const int c = warp >> 1, pl = (qb & 1) + (warp & 1) * 2;
    bulk_load_mc(sK + pl * 32768 + c * 4096, g_qkv + ((64 + (pl >> 1) * 64 + h * 2 + (pl & 1)) * 2048 + c * 256) * 8, 4096, bars + 8 * c);
  };
  if (lane == 0 && warp < 4) ldkv();
  const uint32_t qn[4] = {qp[1024], qp[1024 + 32], qp[1024 + 8192], qp[1024 + 8192 + 32]};
  const float kmax = __uint_as_float(__reduce_max_sync(~0u, max(max(km4.x, km4.y), max(km4.z, km4.w))));
  if (lane == 0 && warp >= 4 && kmax != -1.f) ldkv();
#pragma unroll 1
  for (int tile = 0; tile < 2; tile++) {
    const int row = qb * 512 + tile * 256 + warp * 16 + g;
    const float n0 = qsum(blo(q[0]) * blo(q[0]) + bhi(q[0]) * bhi(q[0]) + blo(q[2]) * blo(q[2]) + bhi(q[2]) * bhi(q[2]));
    const float n1 = qsum(blo(q[1]) * blo(q[1]) + bhi(q[1]) * bhi(q[1]) + blo(q[3]) * blo(q[3]) + bhi(q[3]) * bhi(q[3]));
    const float b0 = sqrtf(n0 * kmax) * 1.001f, b1 = sqrtf(n1 * kmax) * 1.001f;
    const float m0 = fmaxf(ceilf(b0 - 100.f), 0.f), m1 = fmaxf(ceilf(b1 - 100.f), 0.f);
    float o[12], ob[12];
    attn_pass(o, ob, q, m0, m1, sK, bars, tile == 0, kz);
    const float f0 = ex2(-m0), f1 = ex2(-m1);
#pragma unroll
    for (int i = 0; i < 12; i++) o[i] = fmaf(o[i], (i & 2) ? f1 : f0, ob[i]);
    bool ok = b0 < 220.f && b1 < 220.f && o[8] >= 0x1p-90f && o[10] >= 0x1p-90f;
#pragma unroll
    for (int i = 0; i < 12; i++) ok = ok && fabsf(o[i]) < INFINITY;
    if (!__all_sync(~0u, ok)) attn_safe(o, q, sK);
    const float r0 = 1.f / o[8], r1 = 1.f / o[10];
    uint32_t* op = (uint32_t*)g_o + (((row >> 6) * 64 + h * 2) * 64 + (row & 63)) * 4 + t;
    op[0] = pack_rn(o[0] * r0, o[1] * r0); op[32] = pack_rn(o[2] * r1, o[3] * r1);
    op[256] = pack_rn(o[4] * r0, o[5] * r0); op[256 + 32] = pack_rn(o[6] * r1, o[7] * r1);
    if (tile == 0 && tid == 32) {
      l2_prefetch((const char*)wo + bid * 4096, 4096);
      l2_prefetch((const char*)w1 + bid * 11008, 11008);
      l2_prefetch((const char*)w3 + bid * 11008, 11008);
      l2_prefetch((const char*)w2 + bid * 11008, 11008);
    }
#pragma unroll
    for (int i = 0; i < 4; i++) q[i] = qn[i];
    TS(2, 3 + tile);
  }
}

constexpr int WO_SMEM = 131072 + 65536 + 256;
__global__ void __cluster_dims__(2, 1, 1) __launch_bounds__(256, 1) k_wo(const __grid_constant__ CUtensorMap mW, const bf16* __restrict__ x) {
  extern __shared__ __align__(1024) uint8_t smem[];
  const uint32_t sA = smem_u32(smem), sB = sA + 65536, bars = sB + 131072;
  const int tid = threadIdx.x, warp = tid >> 5, lane = tid & 31, g = lane >> 2, t = lane & 3;
  const int rb = blockIdx.x >> 3, ct = (blockIdx.x & 3) * 2 + (warp >> 2);
  TS(3, 0);
  pdl_launch();
  if (tid == 0) {
    for (int i = 0; i < 8; i++) mbar_init(bars + 8 * i, 1);
    fence_init();
    for (int i = 0; i < 8; i++) {
      mbar_expect(bars + 8 * i, 24576);
      for (int j = 0; j < 2; j++) tma2d(sB + (j * 8 + i) * 8192, &mW, (ct + j) * 64, i * 64, bars + 8 * i);
    }
  }
  __syncwarp();
  cluster_arrive();
  const int lrow = (blockIdx.x & 4) * 16 + (warp & 3) * 16 + g;
  uint32_t xr[16];
  const uint32_t* xp = (const uint32_t*)(x + (rb * 128 + lrow) * 512 + ct * 64) + t;
#pragma unroll
  for (int j = 0; j < 8; j++) { xr[2 * j] = __ldg(xp + j * 4); xr[2 * j + 1] = __ldg(xp + j * 4 + 8 * 256); }
  cluster_wait();
  pdl_wait();
  if (tid == 0) {
    for (int i = blockIdx.x & 1; i < 8; i += 2) bulk_load_mc(sA + i * 8192, g_o + ((blockIdx.x >> 2) * 64 + i * 8) * 512, 8192, bars + 8 * i);
  }
  TS(3, 1);
  float2 ga[8];
  uint32_t sc[8];
#pragma unroll
  for (int j = 0; j < 8; j++) {
    ga[j] = *(const float2*)(g_mod + 1024 + ct * 64 + j * 8 + t * 2);
    const float2 v = *(const float2*)(g_mod + 2048 + ct * 64 + j * 8 + t * 2);
    sc[j] = pack_rn(v.x, v.y);
  }
  float acc[32];
  const uint64_t da = mk_desc(sA, 1024, 128, 0), db = mk_desc(sB + (warp >> 2) * 65536, 8192, 1024, 1);
#pragma unroll
  for (int c = 0; c < 8; c++) {
    mbar_wait(bars + 8 * c, 0);
    if (c == 0) TS(3, 2);
    wg_fence();
#pragma unroll
    for (int k = 0; k < 4; k++) wgmma_ss_n64_t1(acc, da + (c * 4 + k) * 128, db + (c * 4 + k) * 128, c + k);
    wg_commit();
  }
  wg_wait<0>();
  reg_fence(acc);
  TS(3, 3);
  uint32_t* o = (uint32_t*)g_x1 + ((rb * 64 + ct * 8) * 128 + lrow) * 4 + t;
  uint32_t* oa = (uint32_t*)g_a + ((rb * 64 + ct * 8) * 128 + lrow) * 4 + t;
  float s0 = 0, s1 = 0;
#pragma unroll
  for (int j = 0; j < 8; j++) {
    xr[2 * j] = pack_rn(fmaf(ga[j].x, acc[4 * j], blo(xr[2 * j])), fmaf(ga[j].y, acc[4 * j + 1], bhi(xr[2 * j])));
    xr[2 * j + 1] = pack_rn(fmaf(ga[j].x, acc[4 * j + 2], blo(xr[2 * j + 1])), fmaf(ga[j].y, acc[4 * j + 3], bhi(xr[2 * j + 1])));
    uint32_t a0, a1;
    asm("mul.rn.bf16x2 %0,%1,%2;" : "=r"(a0) : "r"(xr[2 * j]), "r"(sc[j]));
    asm("mul.rn.bf16x2 %0,%1,%2;" : "=r"(a1) : "r"(xr[2 * j + 1]), "r"(sc[j]));
    oa[j * 512] = a0; oa[j * 512 + 32] = a1;
    o[j * 512] = xr[2 * j]; o[j * 512 + 32] = xr[2 * j + 1];
    s0 += blo(xr[2 * j]) + bhi(xr[2 * j]); s1 += blo(xr[2 * j + 1]) + bhi(xr[2 * j + 1]);
  }
  const float m0 = qsum(s0) * (1.f / 64), m1 = qsum(s1) * (1.f / 64);
  float v0 = 0, v1 = 0;
#pragma unroll
  for (int j = 0; j < 8; j++) {
    float d;
    d = blo(xr[2 * j]) - m0; v0 += d * d; d = bhi(xr[2 * j]) - m0; v0 += d * d;
    d = blo(xr[2 * j + 1]) - m1; v1 += d * d; d = bhi(xr[2 * j + 1]) - m1; v1 += d * d;
  }
  v0 = qsum(v0); v1 = qsum(v1);
  if (t == 0) g_st[(rb * 128 + lrow) * 8 + ct] = make_float2(m0, v0);
  if (t == 1) g_st[(rb * 128 + lrow + 8) * 8 + ct] = make_float2(m1, v1);
  TS(3, 4);
}

constexpr int W2_SMEM = 6 * 32768 + 32768 + 256;
__global__ void __cluster_dims__(2, 1, 1) __launch_bounds__(288, 1) k_w2(const __grid_constant__ CUtensorMap mW, bf16* __restrict__ out) {
  extern __shared__ __align__(1024) uint8_t smem[];
  const uint32_t sR = smem_u32(smem), sX = sR + 6 * 32768, bF = sX + 32768, bE = bF + 48, bX = bF + 96, bB = bF + 160, bG = bF + 208;
  const int tid = threadIdx.x, warp = tid >> 5, lane = tid & 31, g = lane >> 2, t = lane & 3;
  const int kh = blockIdx.x & 1, ct = (blockIdx.x >> 1) & 3, rb = blockIdx.x >> 3;
  TS(5, 0);
  pdl_launch();
  if (tid == 256) {
    for (int i = 0; i < 6; i++) { mbar_init(bF + 8 * i, 1); mbar_init(bE + 8 * i, 8); mbar_init(bB + 8 * i, 1); }
    mbar_init(bG, 1);
    for (int i = 0; i < 8; i++) { mbar_init(bX + 8 * i, 1); mbar_expect(bX + 8 * i, 4096); }
    fence_init();
  }
  __syncthreads();
  asm volatile("barrier.cluster.arrive.relaxed.aligned;" ::: "memory");
  if (warp == 8) {
    if (lane == 0) {
      auto abytes = [&](int s) { return (kh == 1 && s == 10) ? 8192 : 16384; };
      auto loadB = [&](int s) {
        const int st = s % 6;
        mbar_expect(bB + 8 * st, 16384);
        for (int j = 0; j < 2; j++) tma2d(sR + st * 32768 + 16384 + j * 8192, &mW, ct * 128 + j * 64, kh * 704 + s * 64, bB + 8 * st);
      };
      auto loadA = [&](int s) { mbar_expect(bF + 8 * (s % 6), abytes(s)); bulk_load(sR + (s % 6) * 32768, g_h + (rb * 172 + kh * 88 + s * 8) * 1024, abytes(s), bF + 8 * (s % 6)); };
      int nb = 0;
      for (; nb < 6 && (nb < PD2 || may_preload(bB + 8 * (nb - PD2), bG)); nb++) loadB(nb);
      pdl_wait();
      for (int s = 0; s < 6; s++) { loadA(s); if (s >= nb) loadB(s); }
      for (int s = 6; s < 11; s++) { mbar_wait(bE + 8 * (s - 6), 0); loadB(s); loadA(s); }
    }
    __syncwarp();
    cluster_wait();
    return;
  }
  pdl_wait();
  if (tid == 32) mbar_arrive(bG);
  TS(5, 1);
  const int lrow = warp * 16 + g;
  uint32_t xr[16];
  float2 gb[8];
  const uint32_t* xp = (const uint32_t*)g_x1 + ((rb * 64 + ct * 16 + kh * 8) * 128 + lrow) * 4 + t;
#pragma unroll
  for (int j = 0; j < 8; j++) {
    xr[2 * j] = xp[j * 512]; xr[2 * j + 1] = xp[j * 512 + 32];
    gb[j] = *(const float2*)(g_mod + 2560 + ct * 128 + kh * 64 + j * 8 + t * 2);
  }
  float acc[64];
#pragma unroll 1
  for (int s = 0; s < 11; s++) {
    const int st = s % 6;
    mbar_wait(bB + 8 * st, s >= 6); mbar_wait(bF + 8 * st, s >= 6);
    const uint64_t da = mk_desc(sR + st * 32768 + (warp >> 2) * 1024, 2048, 128, 0), db = mk_desc(sR + st * 32768 + 16384, 8192, 1024, 1);
    if (s == 0) TS(5, 2);
    wg_fence();
    wgmma_ss_n128_t1(acc, da, db, s);
    wgmma_ss_n128_t1(acc, da + 256, db + 128, 1);
    wgmma_ss_n128_t1(acc, da + 512, db + 256, 1);
    wgmma_ss_n128_t1(acc, da + 768, db + 384, 1);
    wg_commit();
    wg_wait<1>();
    if (s > 0 && s < 6 && lane == 0) mbar_arrive(bE + 8 * (s - 1));
  }
  wg_wait<0>();
  reg_fence(acc);
  TS(5, 3);
  asm volatile("barrier.cluster.wait.aligned;" ::: "memory");
  uint32_t rem, rbar;
  asm("mapa.shared::cluster.u32 %0,%1,%2;" : "=r"(rbar) : "r"(bX + warp * 8), "r"(kh ^ 1));
  asm("mapa.shared::cluster.u32 %0,%1,%2;" : "=r"(rem) : "r"(sX + warp * 4096 + lane * 16), "r"(kh ^ 1));
#pragma unroll
  for (int j = 0; j < 8; j++) {
    float v[4];
#pragma unroll
    for (int i = 0; i < 4; i++) { v[i] = kh ? acc[4 * j + i] : acc[32 + 4 * j + i]; acc[4 * j + i] = kh ? acc[32 + 4 * j + i] : acc[4 * j + i]; }
    asm volatile("st.async.weak.shared::cluster.mbarrier::complete_tx::bytes.v4.f32 [%0],{%1,%2,%3,%4},[%5];" ::"r"(rem + j * 512), "f"(v[0]), "f"(v[1]), "f"(v[2]), "f"(v[3]), "r"(rbar) : "memory");
  }
  mbar_wait(bX + warp * 8, 0);
  TS(5, 5);
  const uint32_t sw = sX + warp * 4096;
#pragma unroll
  for (int j = 0; j < 8; j++) {
    const float4 p = *(const float4*)(smem + 6 * 32768 + warp * 4096 + j * 512 + lane * 16);
    xr[2 * j] = pack_rn(fmaf(gb[j].x, acc[4 * j] + p.x, blo(xr[2 * j])), fmaf(gb[j].y, acc[4 * j + 1] + p.y, bhi(xr[2 * j])));
    xr[2 * j + 1] = pack_rn(fmaf(gb[j].x, acc[4 * j + 2] + p.z, blo(xr[2 * j + 1])), fmaf(gb[j].y, acc[4 * j + 3] + p.w, bhi(xr[2 * j + 1])));
  }
  __syncwarp();
#pragma unroll
  for (int j = 1; j < 8; j += 2) {
    asm volatile("stmatrix.sync.aligned.m8n8.x4.shared.b16 [%0],{%1,%2,%3,%4};" ::"r"(sw + (lane & 15) * 128 + (((j - 1 + (lane >> 4)) ^ (lane & 7)) << 4)),
                            "r"(xr[2 * j - 2]), "r"(xr[2 * j - 1]), "r"(xr[2 * j]), "r"(xr[2 * j + 1]) : "memory");
  }
  __syncwarp();
#pragma unroll
  for (int i = 0; i < 4; i++) {
    const int r = i * 4 + (lane >> 3);
    *(uint4*)(out + (rb * 128 + warp * 16 + r) * 512 + ct * 128 + kh * 64 + (lane & 7) * 8) = *(const uint4*)(smem + 6 * 32768 + warp * 4096 + r * 128 + (((lane ^ r) & 7) << 4));
  }
  TS(5, 4);
}

typedef CUresult (*EncFn)(CUtensorMap*, CUtensorMapDataType, cuuint32_t, void*, const cuuint64_t*, const cuuint64_t*, const cuuint32_t*,
                          const cuuint32_t*, CUtensorMapInterleave, CUtensorMapSwizzle, CUtensorMapL2promotion, CUtensorMapFloatOOBfill);
static void mk_map(EncFn f, CUtensorMap* m, const void* p, int rows, int cols, int box_rows) {
  cuuint64_t dim[2] = {(cuuint64_t)cols, (cuuint64_t)rows}, str[1] = {(cuuint64_t)cols * 2};
  cuuint32_t box[2] = {64, (cuuint32_t)box_rows}, es[2] = {1, 1};
  f(m, CU_TENSOR_MAP_DATA_TYPE_BFLOAT16, 2, (void*)p, dim, str, box, es, CU_TENSOR_MAP_INTERLEAVE_NONE, CU_TENSOR_MAP_SWIZZLE_128B,
    CU_TENSOR_MAP_L2_PROMOTION_L2_128B, CU_TENSOR_MAP_FLOAT_OOB_FILL_NONE);
}
template <typename... KA, typename... A>
static void launch(void (*k)(KA...), int grid, int block, int smem, bool pdl, A... args) {
  cudaLaunchConfig_t cfg = {};
  cfg.gridDim = dim3(grid); cfg.blockDim = dim3(block); cfg.dynamicSmemBytes = smem; cfg.stream = cudaStreamPerThread;
  cudaLaunchAttribute at[1];
  at[0].id = cudaLaunchAttributeProgrammaticStreamSerialization; at[0].val.programmaticStreamSerializationAllowed = 1;
  cfg.attrs = at; cfg.numAttrs = pdl ? 1 : 0;
  cudaLaunchKernelEx(&cfg, k, args...);
}
extern "C" void kernel_launch(void* const* d_in, const int* in_sizes, int n_in, void* d_out, int out_size) {
  const bf16 *x = (const bf16*)d_in[0], *wqkv = (const bf16*)d_in[1], *wo = (const bf16*)d_in[2], *w1 = (const bf16*)d_in[4],
             *w3 = (const bf16*)d_in[5], *w2 = (const bf16*)d_in[6], *c = (const bf16*)d_in[7], *wmod = (const bf16*)d_in[8];
  void* fp = nullptr;
  cudaDriverEntryPointQueryResult qr;
  cudaGetDriverEntryPoint("cuTensorMapEncodeTiled", &fp, cudaEnableDefault, &qr);
  EncFn f = (EncFn)fp;
  CUtensorMap mX, mQ, mO, m1, m3, m2;
  mk_map(f, &mX, x, S_, D_, 128); mk_map(f, &mQ, wqkv, D_, 3 * D_, 64); mk_map(f, &mO, wo, D_, D_, 64);
  mk_map(f, &m1, w1, D_, F_, 32); mk_map(f, &m3, w3, D_, F_, 32); mk_map(f, &m2, w2, F_, D_, 64);
  cudaFuncSetAttribute(k_lngemm<false>, cudaFuncAttributeMaxDynamicSharedMemorySize, LN_SMEM);
  cudaFuncSetAttribute(k_lngemm<true>, cudaFuncAttributeMaxDynamicSharedMemorySize, LN_SMEM);
  cudaFuncSetAttribute(k_attn, cudaFuncAttributeMaxDynamicSharedMemorySize, AT_SMEM);
  cudaFuncSetAttribute(k_wo, cudaFuncAttributeMaxDynamicSharedMemorySize, WO_SMEM);
  cudaFuncSetAttribute(k_w2, cudaFuncAttributeMaxDynamicSharedMemorySize, W2_SMEM);
  launch(k_lngemm<false>, 128, 384, LN_SMEM, false, mX, mQ, mQ, c, wmod, x, wqkv);
  launch(k_attn, 132, 512, AT_SMEM, true, wo, w1, w3, w2, c, wmod, 0u);
  launch(k_wo, 128, 256, WO_SMEM, true, mO, x);
  launch(k_lngemm<true>, 128, 384, LN_SMEM, true, mX, m1, m3, c, wmod, x, wqkv);
  launch(k_w2, 128, 288, W2_SMEM, true, m2, (bf16*)d_out);
}
```

```cpp
#include <cuda_runtime.h>
#include <cuda_bf16.h>
#include <cuda.h>
#include <stdint.h>
typedef __nv_bfloat16 bf16;
constexpr int S_ = 2048, D_ = 512, F_ = 1376;
__device__ __align__(1024) float g_mod[3072];
__device__ __align__(1024) uint32_t g_modv[4096 + 4096];
__device__ __align__(1024) bf16 g_qkv[192 * 2048 * 8];
__device__ __align__(1024) float g_kmax[32 * 128];
__device__ __align__(1024) bf16 g_o[16 * 64 * 128 * 8];
__device__ __align__(1024) bf16 g_x1[16 * 64 * 128 * 8];
__device__ __align__(1024) bf16 g_a[16 * 64 * 128 * 8];
__device__ __align__(1024) float2 g_uv[2 * 1408];
__device__ __align__(1024) float2 g_st[2048 * 8];
__device__ __align__(1024) bf16 g_h[16 * 172 * 128 * 8];

__device__ __forceinline__ uint32_t smem_u32(const void* p) { return (uint32_t)__cvta_generic_to_shared(p); }
__device__ __forceinline__ void mbar_init(uint32_t b, int n) { asm volatile("mbarrier.init.shared::cta.b64 [%0],%1;" ::"r"(b), "r"(n) : "memory"); }
__device__ __forceinline__ void mbar_expect(uint32_t b, int bytes) { asm volatile("mbarrier.arrive.expect_tx.shared::cta.b64 _,[%0],%1;" ::"r"(b), "r"(bytes) : "memory"); }
__device__ __forceinline__ void mbar_arrive(uint32_t b) { asm volatile("mbarrier.arrive.shared::cta.b64 _,[%0];" ::"r"(b) : "memory"); }
__device__ __forceinline__ void mbar_wait(uint32_t b, int parity) {
  asm volatile("{\n.reg .pred p;\n.reg .u32 n;\nmov.u32 n,0;\nLW:\nmbarrier.try_wait.parity.shared::cta.b64 p,[%0],%1;\n@p bra LD;\n"
               "add.u32 n,n,1;\nsetp.lt.u32 p,n,4194304;\n@p bra LW;\nLD:\n}\n" ::"r"(b), "r"(parity) : "memory");
}
__device__ __forceinline__ void fence_init() { asm volatile("fence.mbarrier_init.release.cluster;" ::: "memory"); }
__device__ __forceinline__ void fence_async() { asm volatile("fence.proxy.async.shared::cta;" ::: "memory"); }
__device__ __forceinline__ void bulk_load(uint32_t dst, const void* src, int bytes, uint32_t bar) {
  asm volatile("cp.async.bulk.shared::cluster.global.mbarrier::complete_tx::bytes [%0],[%1],%2,[%3];" ::"r"(dst), "l"(src), "r"(bytes), "r"(bar) : "memory");
}
__device__ __forceinline__ void tma2d(uint32_t dst, const CUtensorMap* m, int c0, int c1, uint32_t bar) {
  asm volatile("cp.async.bulk.tensor.2d.shared::cluster.global.mbarrier::complete_tx::bytes [%0],[%1,{%3,%4}],[%2];" ::"r"(dst), "l"(m), "r"(bar), "r"(c0), "r"(c1) : "memory");
}
__device__ __forceinline__ void bulk_load_mc(uint32_t dst, const void* src, int bytes, uint32_t bar) {
  asm volatile("cp.async.bulk.shared::cluster.global.mbarrier::complete_tx::bytes.multicast::cluster [%0],[%1],%2,[%3],%4;" ::"r"(dst), "l"(src), "r"(bytes), "r"(bar), "h"((uint16_t)3) : "memory");
}
__device__ __forceinline__ void tma2d_mc(uint32_t dst, const CUtensorMap* m, int c0, int c1, uint32_t bar) {
  asm volatile("cp.async.bulk.tensor.2d.shared::cluster.global.mbarrier::complete_tx::bytes.multicast::cluster [%0],[%1,{%3,%4}],[%2],%5;" ::"r"(dst), "l"(m), "r"(bar), "r"(c0), "r"(c1), "h"((uint16_t)3) : "memory");
}
__device__ __forceinline__ void cluster_arrive() { asm volatile("barrier.cluster.arrive.relaxed.aligned;" ::: "memory"); }
__device__ __forceinline__ void cluster_wait() { asm volatile("barrier.cluster.wait.aligned;" ::: "memory"); }
__device__ __forceinline__ void cluster_sync() { asm volatile("barrier.cluster.arrive.release.aligned;\nbarrier.cluster.wait.acquire.aligned;" ::: "memory"); }
__device__ __forceinline__ bool mbar_test(uint32_t b, uint32_t ph) {
  uint32_t ok; asm volatile("{\n.reg .pred p;\nmbarrier.test_wait.parity.shared::cta.b64 p,[%1],%2;\nselp.u32 %0,1,0,p;\n}" : "=r"(ok) : "r"(b), "r"(ph) : "memory"); return ok;
}
__device__ __forceinline__ bool may_preload(uint32_t landed, uint32_t go) {
  for (int i = 0; i < 100000; i++) { if (mbar_test(go, 0)) return false; if (mbar_test(landed, 0)) return true; }
  return false;
}
#define PD1 2
#define PD0 3
#define PD2 2
__device__ __forceinline__ void l2_prefetch(const void* p, int bytes) { asm volatile("cp.async.bulk.prefetch.L2.global [%0],%1;" ::"l"(p), "r"(bytes) : "memory"); }
__device__ __forceinline__ void pdl_launch() { asm volatile("griddepcontrol.launch_dependents;" ::: "memory"); }
__device__ __forceinline__ void pdl_wait() { asm volatile("griddepcontrol.wait;" ::: "memory"); }
__device__ __forceinline__ void wg_fence() { asm volatile("wgmma.fence.sync.aligned;" ::: "memory"); }
__device__ __forceinline__ void wg_commit() { asm volatile("wgmma.commit_group.sync.aligned;" ::: "memory"); }
template <int N> __device__ __forceinline__ void wg_wait() { asm volatile("wgmma.wait_group.sync.aligned %0;" ::"n"(N) : "memory"); }
template <int N> __device__ __forceinline__ void reg_fence(float (&d)[N]) {
#pragma unroll
  for (int i = 0; i < N; i++) asm volatile("" : "+f"(d[i])::"memory");
}
template <int N> __device__ __forceinline__ void zero(float (&d)[N]) {
#pragma unroll
  for (int i = 0; i < N; i++) d[i] = 0.f;
  reg_fence(d);
}
__device__ __forceinline__ uint64_t mk_desc(uint32_t addr, uint32_t lbo, uint32_t sbo, uint32_t mode) {
  return (uint64_t)((addr >> 4) & 0x3FFF) | ((uint64_t)(lbo >> 4) << 16) | ((uint64_t)(sbo >> 4) << 32) | ((uint64_t)mode << 62);
}
__device__ __forceinline__ void ldsm4(uint32_t a, uint32_t (&r)[4]) {
  asm volatile("ldmatrix.sync.aligned.m8n8.x4.shared.b16 {%0,%1,%2,%3},[%4];" : "=r"(r[0]), "=r"(r[1]), "=r"(r[2]), "=r"(r[3]) : "r"(a) : "memory");
}
__device__ __forceinline__ uint32_t pack_rn(float lo, float hi) { uint32_t r; asm("cvt.rn.bf16x2.f32 %0,%1,%2;" : "=r"(r) : "f"(hi), "f"(lo)); return r; }
__device__ __forceinline__ uint32_t pack_rz(float lo, float hi) { uint32_t r; asm("cvt.rz.bf16x2.f32 %0,%1,%2;" : "=r"(r) : "f"(hi), "f"(lo)); return r; }
__device__ __forceinline__ float blo(uint32_t u) { return __uint_as_float(u << 16); }
__device__ __forceinline__ float bhi(uint32_t u) { return __uint_as_float(u & 0xFFFF0000u); }
__device__ __forceinline__ float rbf(float x) { return __bfloat162float(__float2bfloat16_rn(x)); }
__device__ __forceinline__ float qsum(float v) { v += __shfl_xor_sync(~0u, v, 1); return v + __shfl_xor_sync(~0u, v, 2); }
__device__ __forceinline__ float ex2(float x) { float r; asm("ex2.approx.ftz.f32 %0,%1;" : "=f"(r) : "f"(x)); return r; }
#define TS(k, i)
__device__ __forceinline__ void wgmma_rs_n176_t1(float (&d)[88],uint32_t a0,uint32_t a1,uint32_t a2,uint32_t a3,uint64_t db,int sc){
  asm volatile("{\n.reg .pred p;\nsetp.ne.b32 p,%93,0;\n"
    "wgmma.mma_async.sync.aligned.m64n176k16.f32.bf16.bf16 {%0,%1,%2,%3,%4,%5,%6,%7,%8,%9,%10,%11,%12,%13,%14,%15,%16,%17,%18,%19,%20,%21,%22,%23,%24,%25,%26,%27,%28,%29,%30,%31,%32,%33,%34,%35,%36,%37,%38,%39,%40,%41,%42,%43,%44,%45,%46,%47,%48,%49,%50,%51,%52,%53,%54,%55,%56,%57,%58,%59,%60,%61,%62,%63,%64,%65,%66,%67,%68,%69,%70,%71,%72,%73,%74,%75,%76,%77,%78,%79,%80,%81,%82,%83,%84,%85,%86,%87},{%88,%89,%90,%91},%92,p,1,1,1;\n}\n"
    :"+f"(d[0]),"+f"(d[1]),"+f"(d[2]),"+f"(d[3]),"+f"(d[4]),"+f"(d[5]),"+f"(d[6]),"+f"(d[7]),"+f"(d[8]),"+f"(d[9]),"+f"(d[10]),"+f"(d[11]),"+f"(d[12]),"+f"(d[13]),"+f"(d[14]),"+f"(d[15]),"+f"(d[16]),"+f"(d[17]),"+f"(d[18]),"+f"(d[19]),"+f"(d[20]),"+f"(d[21]),"+f"(d[22]),"+f"(d[23]),"+f"(d[24]),"+f"(d[25]),"+f"(d[26]),"+f"(d[27]),"+f"(d[28]),"+f"(d[29]),"+f"(d[30]),"+f"(d[31]),"+f"(d[32]),"+f"(d[33]),"+f"(d[34]),"+f"(d[35]),"+f"(d[36]),"+f"(d[37]),"+f"(d[38]),"+f"(d[39]),"+f"(d[40]),"+f"(d[41]),"+f"(d[42]),"+f"(d[43]),"+f"(d[44]),"+f"(d[45]),"+f"(d[46]),"+f"(d[47]),"+f"(d[48]),"+f"(d[49]),"+f"(d[50]),"+f"(d[51]),"+f"(d[52]),"+f"(d[53]),"+f"(d[54]),"+f"(d[55]),"+f"(d[56]),"+f"(d[57]),"+f"(d[58]),"+f"(d[59]),"+f"(d[60]),"+f"(d[61]),"+f"(d[62]),"+f"(d[63]),"+f"(d[64]),"+f"(d[65]),"+f"(d[66]),"+f"(d[67]),"+f"(d[68]),"+f"(d[69]),"+f"(d[70]),"+f"(d[71]),"+f"(d[72]),"+f"(d[73]),"+f"(d[74]),"+f"(d[75]),"+f"(d[76]),"+f"(d[77]),"+f"(d[78]),"+f"(d[79]),"+f"(d[80]),"+f"(d[81]),"+f"(d[82]),"+f"(d[83]),"+f"(d[84]),"+f"(d[85]),"+f"(d[86]),"+f"(d[87])
    :"r"(a0),"r"(a1),"r"(a2),"r"(a3),"l"(db),"r"(sc));
}
__device__ __forceinline__ void wgmma_rs_n192_t1(float (&d)[96],uint32_t a0,uint32_t a1,uint32_t a2,uint32_t a3,uint64_t db,int sc){
  asm volatile("{\n.reg .pred p;\nsetp.ne.b32 p,%101,0;\n"
    "wgmma.mma_async.sync.aligned.m64n192k16.f32.bf16.bf16 {%0,%1,%2,%3,%4,%5,%6,%7,%8,%9,%10,%11,%12,%13,%14,%15,%16,%17,%18,%19,%20,%21,%22,%23,%24,%25,%26,%27,%28,%29,%30,%31,%32,%33,%34,%35,%36,%37,%38,%39,%40,%41,%42,%43,%44,%45,%46,%47,%48,%49,%50,%51,%52,%53,%54,%55,%56,%57,%58,%59,%60,%61,%62,%63,%64,%65,%66,%67,%68,%69,%70,%71,%72,%73,%74,%75,%76,%77,%78,%79,%80,%81,%82,%83,%84,%85,%86,%87,%88,%89,%90,%91,%92,%93,%94,%95},{%96,%97,%98,%99},%100,p,1,1,1;\n}\n"
    :"+f"(d[0]),"+f"(d[1]),"+f"(d[2]),"+f"(d[3]),"+f"(d[4]),"+f"(d[5]),"+f"(d[6]),"+f"(d[7]),"+f"(d[8]),"+f"(d[9]),"+f"(d[10]),"+f"(d[11]),"+f"(d[12]),"+f"(d[13]),"+f"(d[14]),"+f"(d[15]),"+f"(d[16]),"+f"(d[17]),"+f"(d[18]),"+f"(d[19]),"+f"(d[20]),"+f"(d[21]),"+f"(d[22]),"+f"(d[23]),"+f"(d[24]),"+f"(d[25]),"+f"(d[26]),"+f"(d[27]),"+f"(d[28]),"+f"(d[29]),"+f"(d[30]),"+f"(d[31]),"+f"(d[32]),"+f"(d[33]),"+f"(d[34]),"+f"(d[35]),"+f"(d[36]),"+f"(d[37]),"+f"(d[38]),"+f"(d[39]),"+f"(d[40]),"+f"(d[41]),"+f"(d[42]),"+f"(d[43]),"+f"(d[44]),"+f"(d[45]),"+f"(d[46]),"+f"(d[47]),"+f"(d[48]),"+f"(d[49]),"+f"(d[50]),"+f"(d[51]),"+f"(d[52]),"+f"(d[53]),"+f"(d[54]),"+f"(d[55]),"+f"(d[56]),"+f"(d[57]),"+f"(d[58]),"+f"(d[59]),"+f"(d[60]),"+f"(d[61]),"+f"(d[62]),"+f"(d[63]),"+f"(d[64]),"+f"(d[65]),"+f"(d[66]),"+f"(d[67]),"+f"(d[68]),"+f"(d[69]),"+f"(d[70]),"+f"(d[71]),"+f"(d[72]),"+f"(d[73]),"+f"(d[74]),"+f"(d[75]),"+f"(d[76]),"+f"(d[77]),"+f"(d[78]),"+f"(d[79]),"+f"(d[80]),"+f"(d[81]),"+f"(d[82]),"+f"(d[83]),"+f"(d[84]),"+f"(d[85]),"+f"(d[86]),"+f"(d[87]),"+f"(d[88]),"+f"(d[89]),"+f"(d[90]),"+f"(d[91]),"+f"(d[92]),"+f"(d[93]),"+f"(d[94]),"+f"(d[95])
    :"r"(a0),"r"(a1),"r"(a2),"r"(a3),"l"(db),"r"(sc));
}
__device__ __forceinline__ void wgmma_rs_n24_t1(float (&d)[12],uint32_t a0,uint32_t a1,uint32_t a2,uint32_t a3,uint64_t db,int sc){
  asm volatile("{\n.reg .pred p;\nsetp.ne.b32 p,%17,0;\n"
    "wgmma.mma_async.sync.aligned.m64n24k16.f32.bf16.bf16 {%0,%1,%2,%3,%4,%5,%6,%7,%8,%9,%10,%11},{%12,%13,%14,%15},%16,p,1,1,1;\n}\n"
    :"+f"(d[0]),"+f"(d[1]),"+f"(d[2]),"+f"(d[3]),"+f"(d[4]),"+f"(d[5]),"+f"(d[6]),"+f"(d[7]),"+f"(d[8]),"+f"(d[9]),"+f"(d[10]),"+f"(d[11])
    :"r"(a0),"r"(a1),"r"(a2),"r"(a3),"l"(db),"r"(sc));
}
__device__ __forceinline__ void wgmma_rs_n64_t0(float (&d)[32],uint32_t a0,uint32_t a1,uint32_t a2,uint32_t a3,uint64_t db,int sc){
  asm volatile("{\n.reg .pred p;\nsetp.ne.b32 p,%37,0;\n"
    "wgmma.mma_async.sync.aligned.m64n64k16.f32.bf16.bf16 {%0,%1,%2,%3,%4,%5,%6,%7,%8,%9,%10,%11,%12,%13,%14,%15,%16,%17,%18,%19,%20,%21,%22,%23,%24,%25,%26,%27,%28,%29,%30,%31},{%32,%33,%34,%35},%36,p,1,1,0;\n}\n"
    :"+f"(d[0]),"+f"(d[1]),"+f"(d[2]),"+f"(d[3]),"+f"(d[4]),"+f"(d[5]),"+f"(d[6]),"+f"(d[7]),"+f"(d[8]),"+f"(d[9]),"+f"(d[10]),"+f"(d[11]),"+f"(d[12]),"+f"(d[13]),"+f"(d[14]),"+f"(d[15]),"+f"(d[16]),"+f"(d[17]),"+f"(d[18]),"+f"(d[19]),"+f"(d[20]),"+f"(d[21]),"+f"(d[22]),"+f"(d[23]),"+f"(d[24]),"+f"(d[25]),"+f"(d[26]),"+f"(d[27]),"+f"(d[28]),"+f"(d[29]),"+f"(d[30]),"+f"(d[31])
    :"r"(a0),"r"(a1),"r"(a2),"r"(a3),"l"(db),"r"(sc));
}
__device__ __forceinline__ void wgmma_ss_n128_t1(float (&d)[64],uint64_t da,uint64_t db,int sc){
  asm volatile("{\n.reg .pred p;\nsetp.ne.b32 p,%66,0;\n"
    "wgmma.mma_async.sync.aligned.m64n128k16.f32.bf16.bf16 {%0,%1,%2,%3,%4,%5,%6,%7,%8,%9,%10,%11,%12,%13,%14,%15,%16,%17,%18,%19,%20,%21,%22,%23,%24,%25,%26,%27,%28,%29,%30,%31,%32,%33,%34,%35,%36,%37,%38,%39,%40,%41,%42,%43,%44,%45,%46,%47,%48,%49,%50,%51,%52,%53,%54,%55,%56,%57,%58,%59,%60,%61,%62,%63},%64,%65,p,1,1,0,1;\n}\n"
    :"+f"(d[0]),"+f"(d[1]),"+f"(d[2]),"+f"(d[3]),"+f"(d[4]),"+f"(d[5]),"+f"(d[6]),"+f"(d[7]),"+f"(d[8]),"+f"(d[9]),"+f"(d[10]),"+f"(d[11]),"+f"(d[12]),"+f"(d[13]),"+f"(d[14]),"+f"(d[15]),"+f"(d[16]),"+f"(d[17]),"+f"(d[18]),"+f"(d[19]),"+f"(d[20]),"+f"(d[21]),"+f"(d[22]),"+f"(d[23]),"+f"(d[24]),"+f"(d[25]),"+f"(d[26]),"+f"(d[27]),"+f"(d[28]),"+f"(d[29]),"+f"(d[30]),"+f"(d[31]),"+f"(d[32]),"+f"(d[33]),"+f"(d[34]),"+f"(d[35]),"+f"(d[36]),"+f"(d[37]),"+f"(d[38]),"+f"(d[39]),"+f"(d[40]),"+f"(d[41]),"+f"(d[42]),"+f"(d[43]),"+f"(d[44]),"+f"(d[45]),"+f"(d[46]),"+f"(d[47]),"+f"(d[48]),"+f"(d[49]),"+f"(d[50]),"+f"(d[51]),"+f"(d[52]),"+f"(d[53]),"+f"(d[54]),"+f"(d[55]),"+f"(d[56]),"+f"(d[57]),"+f"(d[58]),"+f"(d[59]),"+f"(d[60]),"+f"(d[61]),"+f"(d[62]),"+f"(d[63])
    :"l"(da),"l"(db),"r"(sc));
}
__device__ __forceinline__ void wgmma_ss_n64_t1(float (&d)[32],uint64_t da,uint64_t db,int sc){
  asm volatile("{\n.reg .pred p;\nsetp.ne.b32 p,%34,0;\n"
    "wgmma.mma_async.sync.aligned.m64n64k16.f32.bf16.bf16 {%0,%1,%2,%3,%4,%5,%6,%7,%8,%9,%10,%11,%12,%13,%14,%15,%16,%17,%18,%19,%20,%21,%22,%23,%24,%25,%26,%27,%28,%29,%30,%31},%32,%33,p,1,1,0,1;\n}\n"
    :"+f"(d[0]),"+f"(d[1]),"+f"(d[2]),"+f"(d[3]),"+f"(d[4]),"+f"(d[5]),"+f"(d[6]),"+f"(d[7]),"+f"(d[8]),"+f"(d[9]),"+f"(d[10]),"+f"(d[11]),"+f"(d[12]),"+f"(d[13]),"+f"(d[14]),"+f"(d[15]),"+f"(d[16]),"+f"(d[17]),"+f"(d[18]),"+f"(d[19]),"+f"(d[20]),"+f"(d[21]),"+f"(d[22]),"+f"(d[23]),"+f"(d[24]),"+f"(d[25]),"+f"(d[26]),"+f"(d[27]),"+f"(d[28]),"+f"(d[29]),"+f"(d[30]),"+f"(d[31])
    :"l"(da),"l"(db),"r"(sc));
}

__device__ __forceinline__ float silu_bf(bf16 c) { const float x = __bfloat162float(c); return rbf(x / (1.f + __expf(-x))); }
__device__ __forceinline__ void fma8(float (&a)[8], float s, const uint4& v) {
  a[0] += s * blo(v.x); a[1] += s * bhi(v.x); a[2] += s * blo(v.y); a[3] += s * bhi(v.y);
  a[4] += s * blo(v.z); a[5] += s * bhi(v.z); a[6] += s * blo(v.w); a[7] += s * bhi(v.w);
}
__device__ __forceinline__ float red8(float (&a)[8], int lane) {
#pragma unroll
  for (int w = 4; w >= 1; w >>= 1) {
    const bool up = lane & (w * 4);
#pragma unroll
    for (int j = 0; j < w; j++) a[j] = (up ? a[j + w] : a[j]) + __shfl_xor_sync(~0u, up ? a[j] : a[j + w], w * 4);
  }
  return a[0];
}
__device__ __forceinline__ float mod_fin(float s, int n) { s = rbf(s); return ((n >> 9) == 1 || (n >> 9) == 4) ? rbf(1.f + s) : s; }
__device__ __forceinline__ void poll(uint2& a, uint2& b, float (&w)[16], const uint32_t* p, const uint32_t* q) {
  asm volatile("{\n.reg .pred p;\n.reg .b32 n,t,u;\nmov.u32 n,0;\nLW:\nld.relaxed.gpu.global.v2.u32 {%0,%1},[%20];\nld.relaxed.gpu.global.v2.u32 {%2,%3},[%20+64];\n"
               "ld.relaxed.gpu.global.v4.f32 {%4,%5,%6,%7},[%21];\nld.relaxed.gpu.global.v4.f32 {%8,%9,%10,%11},[%21+16];\n"
               "ld.relaxed.gpu.global.v4.f32 {%12,%13,%14,%15},[%21+8192];\nld.relaxed.gpu.global.v4.f32 {%16,%17,%18,%19},[%21+8208];\n"
               "lop3.b32 t,%0,%1,%2,0x80;\nlop3.b32 u,%3,%4,%5,0x80;\nlop3.b32 t,t,%6,%7,0x80;\nlop3.b32 u,u,%8,%9,0x80;\nlop3.b32 t,t,%10,%11,0x80;\n"
               "lop3.b32 u,u,%12,%13,0x80;\nlop3.b32 t,t,%14,%15,0x80;\nlop3.b32 u,u,%16,%17,0x80;\nlop3.b32 t,t,%18,%19,0x80;\nlop3.b32 t,t,u,1,0x80;\n"
               "setp.ne.u32 p,t,0;\n@p bra LD;\nadd.u32 n,n,1;\nsetp.lt.u32 p,n,1048576;\n@p bra LW;\nLD:\n}\n"
               : "=&r"(a.x), "=&r"(a.y), "=&r"(b.x), "=&r"(b.y), "=&f"(w[0]), "=&f"(w[1]), "=&f"(w[2]), "=&f"(w[3]), "=&f"(w[4]), "=&f"(w[5]), "=&f"(w[6]), "=&f"(w[7]),
                 "=&f"(w[8]), "=&f"(w[9]), "=&f"(w[10]), "=&f"(w[11]), "=&f"(w[12]), "=&f"(w[13]), "=&f"(w[14]), "=&f"(w[15]) : "l"(p), "l"(q) : "memory");
}

constexpr int LN_SMEM = 131072 + 4 * 24576 + 2816 + 256;
#define TANH 1
#define DLY 2
template <bool FFN>
__global__ void __cluster_dims__(2, 1, 1) __launch_bounds__(384, 1) k_lngemm(const __grid_constant__ CUtensorMap mX, const __grid_constant__ CUtensorMap mB0,
                                                   const __grid_constant__ CUtensorMap mB1, const bf16* __restrict__ cv, const bf16* __restrict__ wm, const bf16* __restrict__ xg, const bf16* wq) {
  extern __shared__ __align__(1024) uint8_t smem[];
  const uint32_t sA = smem_u32(smem), sB = sA + (FFN ? 81920 : 131072), sM = sA + 229376, bars = sM + 2816;
  const uint32_t bA = bars, bF = bars + 64, bE = bars + 112;
  constexpr int NB = FFN ? 6 : 4;
  const int tid = threadIdx.x, warp = tid >> 5, lane = tid & 31;
  const int pr = blockIdx.x & 1, rb = FFN ? (blockIdx.x >> 4) * 2 + pr : blockIdx.x >> 3, ct = FFN ? (blockIdx.x >> 1) & 7 : blockIdx.x & 7;
  constexpr int NST = FFN ? 16 : 8, KS = FFN ? 2 : 4, BOX = FFN ? 4096 : 8192;
  TS(FFN ? 4 : 1, 0);
  pdl_launch();
  float* red = (float*)(smem + (sM - sA));
  if (tid == 256) {
    for (int i = 0; i < 8; i++) mbar_init(bA + 8 * i, 1);
    for (int i = 0; i < NB; i++) { mbar_init(bF + 8 * i, 1); mbar_init(bE + 8 * i, FFN ? 16 : 8); }
    mbar_init(bars + 160, 1);
    fence_init();
  }
  __syncwarp();
  cluster_arrive();
  uint4 wv0, wv1, xv[4];
  bf16 cv0, cv1;
  if (!FFN && tid < 256) {
    const int r = (blockIdx.x & 3) * 128 + (tid >> 2);
    const uint4* wp = (const uint4*)(wm + r * 3072 + (blockIdx.x >> 2) * 32 + (tid & 3) * 8);
    wv0 = __ldg(wp); wv1 = __ldg(wp + 64 * 384);
    cv0 = cv[r]; cv1 = cv[r + 64];
#pragma unroll
    for (int i = 0; i < 4; i++) xv[i] = __ldg((const uint4*)(xg + (blockIdx.x * 16 + (tid >> 4)) * 512 + i * 128 + (tid & 15) * 8));
  }
  cluster_wait();
  if (warp >= 8) {
    asm volatile("setmaxnreg.dec.sync.aligned.u32 40;");
    if (tid == 256) {
      auto loadB = [&](int s) {
        const uint32_t d = sB + (s % NB) * 24576, b = bF + (s % NB) * 8;
        mbar_expect(b, 24576);
        for (int j = 0; j < 3; j++) {
          if (FFN) tma2d_mc(d + (pr * 3 + j) * BOX, pr ? &mB1 : &mB0, ct * 176 + j * 64, s * 32, b);
          else tma2d(d + j * BOX, &mB0, ct * 192 + j * 64, s * 64, b);
        }
      };
      for (int i = 0; i < 8; i++) mbar_expect(bA + 8 * i, 16384);
      if (!FFN) l2_prefetch((const char*)wq + blockIdx.x * 12288, 12288);
      int nb = 0;
      for (int s = 0; s < NB; s++, nb++) {
        const int i = s * 2 + (ct & 1);
        if (FFN && s >= PD1 && !may_preload(bF + (s - PD1) * 8, bars + 160)) break;
        if (!FFN && s == DLY) mbar_wait(bars + 160, 0);
        if (!FFN) tma2d_mc(sA + i * 16384, &mX, i * 64, rb * 128, bA + 8 * i);
        loadB(s);
      }
      if (FFN) {
        pdl_wait();
        for (int i = 0; i < 5; i++) {
          bulk_load(sA + i * 16384, g_a + (rb * 64 + i * 8) * 1024, 16384, bA + 8 * i);
          for (; nb < 2 * i + 2 && nb < NB; nb++) loadB(nb);
        }
      }
      for (int s = NB; s < NST; s++) {
        mbar_wait(bE + (s % NB) * 8, (s / NB - 1) & 1); loadB(s);
        if (FFN && s <= 10 && !(s & 1)) bulk_load(sA + (s / 2 - 3) * 16384, g_a + (rb * 64 + (s / 2 + 2) * 8) * 1024, 16384, bA + 8 * (s / 2 + 2));
      }
    }
  } else {
  asm volatile("setmaxnreg.inc.sync.aligned.u32 232;");
  const int g = lane >> 2, t = lane & 3;
  const int lr = warp * 16 + (lane & 7) + ((lane >> 3) & 1) * 8;
  auto aaddr = [&](int ks) -> uint32_t {
    if (FFN) return sA + ((ks < 20 ? ks : ks - 20) * 2 + (lane >> 4)) * 2048 + lr * 16;
    return sA + (ks >> 2) * 16384 + lr * 128 + ((((ks & 3) * 2 + (lane >> 4)) ^ (lr & 7)) << 4);
  };
  const int row0 = rb * 128 + warp * 16 + g;
  float2 msh, msc;
  float4 p0, p1, uv;
  float rs0, rs1, nm0, nm1;
  if (!FFN) {
    {
      float a[8] = {0, 0, 0, 0, 0, 0, 0, 0};
      fma8(a, silu_bf(cv0), wv0); fma8(a, silu_bf(cv1), wv1);
      red[warp * 32 + t * 8 + g] = red8(a, lane);
      asm volatile("bar.sync 1,256;" ::: "memory");
      if (tid < 32) {
        float r = 0;
#pragma unroll
        for (int i = 0; i < 8; i++) r += red[i * 32 + tid];
        asm volatile("st.relaxed.gpu.global.u32 [%0],%1;" ::"l"(g_modv + ((blockIdx.x >> 2) * 32 + tid) * 4 + (blockIdx.x & 3)), "r"(__float_as_uint(r) | 1u) : "memory");
      }
      TS(0, 1);
    }
    {
      float v[32], s = 0, q = 0;
#pragma unroll
      for (int i = 0; i < 16; i++) { const uint32_t u = ((const uint32_t*)xv)[i]; v[2 * i] = blo(u); v[2 * i + 1] = bhi(u); s += v[2 * i] + v[2 * i + 1]; }
      s = qsum(s); s += __shfl_xor_sync(~0u, s, 4); s += __shfl_xor_sync(~0u, s, 8);
      const float m = s * (1.f / 512);
#pragma unroll
      for (int i = 0; i < 32; i++) q += (v[i] - m) * (v[i] - m);
      q = qsum(q); q += __shfl_xor_sync(~0u, q, 4); q += __shfl_xor_sync(~0u, q, 8);
      const float rs = rsqrtf(q * (1.f / 512) + 1e-5f);
      if ((tid & 15) == 0)
        asm volatile("st.relaxed.gpu.global.v2.u32 [%0],{%1,%2};" ::"l"(g_modv + 4096 + (blockIdx.x * 16 + (tid >> 4)) * 2), "r"(__float_as_uint(rs) | 1u), "r"(__float_as_uint(-m * rs) | 1u) : "memory");
    }
    uint2 q0, q1;
    float w[16];
    if (tid < 128) {
      uint32_t v; int n = 0;
      do asm volatile("ld.relaxed.gpu.global.u32 %0,[%1];" : "=r"(v) : "l"(g_modv + (tid >> 2) * 128 + (tid & 3)) : "memory"); while (!(v & 1) && ++n < 1048576);
    }
    asm volatile("bar.sync 1,256;" ::: "memory");
    poll(q0, q1, w, g_modv + 4096 + row0 * 2, g_modv + tid * 8);
    msh = make_float2(mod_fin(w[0] + w[1] + w[2] + w[3], 0), mod_fin(w[4] + w[5] + w[6] + w[7], 0));
    msc = make_float2(mod_fin(w[8] + w[9] + w[10] + w[11], 512), mod_fin(w[12] + w[13] + w[14] + w[15], 512));
    asm volatile("bar.sync 1,256;" ::: "memory");
    if (tid == 32) mbar_arrive(bars + 160);
    rs0 = __uint_as_float(q0.x); nm0 = __uint_as_float(q0.y); rs1 = __uint_as_float(q1.x); nm1 = __uint_as_float(q1.y);
  } else {
    pdl_wait();
    if (tid == 32) mbar_arrive(bars + 160);
    TS(4, 1);
    p0 = *(const float4*)(g_st + row0 * 8 + t * 2); p1 = *(const float4*)(g_st + (row0 + 8) * 8 + t * 2);
    if (tid < 176) uv = *(const float4*)(g_uv + (tid >= 88 ? 1408 - 176 : 0) + ct * 176 + tid * 2);
  }
  if (!FFN) {
    uint32_t* m = (uint32_t*)(smem + (sM - sA)) + (tid >> 3) * 16 + (tid & 3) * 4 + ((tid >> 2) & 1);
    m[0] = pack_rn(msc.x, msc.y); m[2] = pack_rn(msh.x, msh.y);
    asm volatile("bar.sync 1,256;" ::: "memory");
  }
  constexpr int NA = FFN ? 88 : 96;
  float acc0[NA], acc1[FFN ? 88 : 1];
  uint32_t a[2][KS][4];
  auto prep = [&](int ks, uint32_t(&o)[4]) {
    if ((ks & 3) == 0) mbar_wait(bA + 2 * ks, 0);
    if (FFN) { ldsm4(aaddr(ks), o); return; }
    uint32_t r[4]; ldsm4(aaddr(ks), r);
    const uint4 m = *(const uint4*)(smem + (sM - sA) + ks * 64 + t * 16);
#pragma unroll
    for (int i = 0; i < 4; i++) {
      const float rs = (i & 1) ? rs1 : rs0, nm = (i & 1) ? nm1 : nm0;
      const uint32_t n = pack_rn(fmaf(blo(r[i]), rs, nm), fmaf(bhi(r[i]), rs, nm));
      asm("fma.rn.bf16x2 %0,%1,%2,%3;" : "=r"(o[i]) : "r"(n), "r"(i < 2 ? m.x : m.y), "r"(i < 2 ? m.z : m.w));
    }
  };
  auto stage = [&](int s, uint32_t(&c)[KS][4], uint32_t(&n)[KS][4]) {
    mbar_wait(bF + (s % NB) * 8, (s / NB) & 1);
    const uint64_t db = mk_desc(sB + (s % NB) * 24576, BOX, 1024, 1);
    wg_fence();
#pragma unroll
    for (int k = 0; k < KS; k++) {
      if constexpr (FFN) {
        wgmma_rs_n176_t1(acc0, c[k][0], c[k][1], c[k][2], c[k][3], db + k * 128, s + k);
        wgmma_rs_n176_t1(acc1, c[k][0], c[k][1], c[k][2], c[k][3], db + k * 128 + 3 * BOX / 16, s + k);
      } else {
        wgmma_rs_n192_t1(acc0, c[k][0], c[k][1], c[k][2], c[k][3], db + k * 128, s + k);
      }
    }
    wg_commit();
    wg_wait<1>();
    if (s > 0 && s <= NST - NB) {
      if (!FFN) { if (lane == 0) mbar_arrive(bE + ((s - 1) % NB) * 8); }
      else if (lane < 2) asm volatile("{\n.reg .b32 r;\nmapa.shared::cluster.u32 r,%0,%1;\nmbarrier.arrive.relaxed.cluster.shared::cluster.b64 _,[r];\n}" ::"r"(bE + ((s - 1) % NB) * 8), "r"(lane) : "memory");
    }
    if (s < NST - 1) {
#pragma unroll
      for (int k = 0; k < KS; k++) prep((s + 1) * KS + k, n[k]);
    }
  };
#pragma unroll
  for (int k = 0; k < KS; k++) prep(k, a[0][k]);
  TS(FFN ? 4 : 1, 2);
#pragma unroll 1
  for (int s = 0; s < NST; s += 2) { stage(s, a[0], a[1]); stage(s + 1, a[1], a[0]); }
  if (FFN) {
    if (tid < 88) { uv.x *= 0.5f; uv.y *= 0.5f; uv.z *= 0.5f; uv.w *= 0.5f; }
    if (tid < 176) *(float4*)(smem + (sM - sA) + tid * 16) = uv;
    const float m0 = qsum(p0.x + p0.z) * 0.125f, m1 = qsum(p1.x + p1.z) * 0.125f;
    const float v0 = qsum(p0.y + p0.w + 64.f * ((p0.x - m0) * (p0.x - m0) + (p0.z - m0) * (p0.z - m0)));
    const float v1 = qsum(p1.y + p1.w + 64.f * ((p1.x - m1) * (p1.x - m1) + (p1.z - m1) * (p1.z - m1)));
    rs0 = rsqrtf(v0 * (1.f / 512) + 1e-5f); rs1 = rsqrtf(v1 * (1.f / 512) + 1e-5f);
    nm0 = -m0 * rs0; nm1 = -m1 * rs1;
    asm volatile("bar.sync 1,256;" ::: "memory");
  }
  wg_wait<0>();
  reg_fence(acc0);
  TS(FFN ? 4 : 1, 3);
  if constexpr (FFN) {
    reg_fence(acc1);
    const float rh0 = 0.5f * rs0, rh1 = 0.5f * rs1;
    uint32_t* o = (uint32_t*)g_h + ((rb * 172 + ct * 22) * 128 + warp * 16 + g) * 4 + t;
#pragma unroll
    for (int j = 0; j < 22; j++) {
      {
        const float4 u1 = *(const float4*)(smem + (sM - sA) + (j * 4 + t) * 16), u3 = *(const float4*)(smem + (sM - sA) + (88 + j * 4 + t) * 16);
        float h[4];
#pragma unroll
        for (int i = 0; i < 4; i++) {
          const float rs = i < 2 ? rs0 : rs1, nm = i < 2 ? nm0 : nm1, rh = i < 2 ? rh0 : rh1;
          const float z = fmaf(rh, acc0[4 * j + i], (i & 1) ? fmaf(nm, u1.z, u1.w) : fmaf(nm, u1.x, u1.y));
          const float y = fmaf(rs, acc1[4 * j + i], (i & 1) ? fmaf(nm, u3.z, u3.w) : fmaf(nm, u3.x, u3.y));
          float th; asm("tanh.approx.f32 %0,%1;" : "=f"(th) : "f"(z));
          h[i] = fmaf(z, th, z) * y;
        }
        if (j < 18 || ct < 7) { o[j * 512] = pack_rn(h[0], h[1]); o[j * 512 + 32] = pack_rn(h[2], h[3]); }
      }
    }
  } else {
    uint32_t* o = (uint32_t*)g_qkv + (ct * 24 * 2048 + row0) * 4 + t;
#pragma unroll
    for (int j = 0; j < 24; j += 2) {
      const int G = ct * 24 + j;
      const float sc = G < 64 ? 0.25f * 1.4426950408889634f : 1.f;
      uint32_t p[4];
#pragma unroll
      for (int i = 0; i < 4; i++) p[i] = pack_rn(acc0[4 * j + 2 * i] * sc, acc0[4 * j + 2 * i + 1] * sc);
      o[j * 8192] = p[0]; o[j * 8192 + 32] = p[1]; o[(j + 1) * 8192] = p[2]; o[(j + 1) * 8192 + 32] = p[3];
      if (G >= 64 && G < 128) {
        float n0 = blo(p[0]) * blo(p[0]) + bhi(p[0]) * bhi(p[0]) + blo(p[2]) * blo(p[2]) + bhi(p[2]) * bhi(p[2]);
        float n1 = blo(p[1]) * blo(p[1]) + bhi(p[1]) * bhi(p[1]) + blo(p[3]) * blo(p[3]) + bhi(p[3]) * bhi(p[3]);
        n0 = qsum(n0); n1 = qsum(n1);
        const uint32_t mx = __reduce_max_sync(~0u, max(__float_as_uint(n0), __float_as_uint(n1)));
        if (lane == 0) g_kmax[((G - 64) >> 1) * 128 + rb * 8 + warp] = __uint_as_float(mx);
      }
    }
  }
  TS(FFN ? 4 : 1, 4);
}
}

#define SMASK 0xCCCCu
#define BRK 0
#define PACK 1
constexpr int AT_SMEM = 5 * 32768 + 256;
__device__ __forceinline__ uint32_t exp2_pair_fma(float s0, float s1, float c, uint32_t ka, uint32_t kz) {
  uint32_t r;
  asm volatile("{\n.reg .b32 y0,y1,e,u,t;\n"
      "fma.rn.sat.f32 y0,%1,0f00000080,%3;\nfma.rn.sat.f32 y1,%2,0f00000080,%3;\n"
      "mad.lo.u32 e,y1,65536,y0;\n"
      "and.b32 u,e,0x007F007F;\n"
      "fma.rn.f16x2 u,u,%4,%5;\nfma.rn.f16x2 t,u,u,%6;\nfma.rn.f16x2 t,t,u,%7;\n"
      "lop3.b32 %0,t,0x007F007F,e,0xE2;\n}\n"
      : "=r"(r) : "f"(s0), "f"(s1), "f"(c), "r"(ka), "r"(0x36B236B2u), "r"(0x3C733C73u), "r"(0x47764776u), "r"(kz));
  return r;
}
__device__ __forceinline__ void attn_pass(float (&oa)[12], float (&ob)[12], const uint32_t (&q)[4], float m0, float m1, uint32_t sK, uint32_t bars, bool first, uint32_t kz) {
  uint64_t dk = mk_desc(sK, 32768, 128, 0), dv = mk_desc(sK + 65536, 128, 32768, 0);
  const float c0 = (127.f - m0) * __uint_as_float(0x80u), c1 = (127.f - m1) * __uint_as_float(0x80u);
  uint32_t ka;
  asm volatile("mov.b32 %0,0x7ACE7ACE;" : "=r"(ka));
  constexpr int NK = 64, NS = 32, NP = 16;
  auto qk = [&](float (&s)[NS], int i) { wgmma_rs_n64_t0(s, q[0], q[1], q[2], q[3], dk + i * NK, 0); };
  auto softmax = [&](float (&s)[NS], uint32_t (&p)[NP], uint32_t mask) {
    reg_fence(s);
    float e0, e1;
    int pend = -1;
#pragma unroll
    for (int t = 0; t < NP; t++) {
      const int j = (t & 3) * 4 + (t >> 2);
      if ((mask >> (t & 3)) & 1) {
        p[j] = exp2_pair_fma(s[2 * j], s[2 * j + 1], (j & 1) ? c1 : c0, ka, kz);
      } else {
        float f0, f1;
        asm volatile("ex2.approx.ftz.f32 %0,%2;\nex2.approx.ftz.f32 %1,%3;" : "=&f"(f0), "=f"(f1) : "f"(s[2 * j]), "f"(s[2 * j + 1]));
        if (pend >= 0) asm volatile("cvt.rn.bf16x2.f32 %0,%1,%2;" : "=r"(p[pend]) : "f"(e1), "f"(e0));
        e0 = f0; e1 = f1; pend = j;
      }
    }
    if (pend >= 0) asm volatile("cvt.rn.bf16x2.f32 %0,%1,%2;" : "=r"(p[pend]) : "f"(e1), "f"(e0));
#pragma unroll
    for (int j = 0; j < NP; j++) asm volatile("" : "+r"(p[j])::"memory");
  };
  auto pv = [&](uint32_t (&p)[NP], int i, uint32_t mask) {
#pragma unroll
    for (int k = 0; k < 4; k++) wgmma_rs_n24_t1(((mask >> k) & 1) ? ob : oa, p[4 * k], p[4 * k + 1], p[4 * k + 2], p[4 * k + 3], dv + i * NK + k * 16, 1);
  };
  constexpr uint32_t M0 = SMASK & 15, M1 = (SMASK >> 4) & 15, M2 = (SMASK >> 8) & 15, M3 = SMASK >> 12;
  zero(oa); zero(ob);
  mbar_wait(bars, 0);
  if (first) TS(2, 2);
  float s[NS];
  zero(s);
  uint32_t p0[NP], p1[NP];
  auto step = [&](int i, uint32_t (&pa)[NP], uint32_t ma, uint32_t (&pb)[NP], uint32_t mb) {
    wg_fence(); qk(s, i + 1); wg_commit(); pv(pa, i, ma); wg_commit(); wg_wait<1>(); softmax(s, pb, mb); wg_wait<0>();
  };
  wg_fence(); qk(s, 0); wg_commit(); wg_wait<0>(); softmax(s, p0, M0);
#pragma unroll 1
  for (uint32_t b = bars + 8; b < bars + 64; b += 8) {
    step(0, p0, M0, p1, M1); step(1, p1, M1, p0, M2); step(2, p0, M2, p1, M3);
    mbar_wait(b, 0);
    step(3, p1, M3, p0, M0);
    dk += 4 * NK; dv += 4 * NK;
  }
  step(0, p0, M0, p1, M1); step(1, p1, M1, p0, M2); step(2, p0, M2, p1, M3);
  wg_fence(); pv(p1, 3, M3); wg_commit();
  wg_wait<0>();
  reg_fence(oa); reg_fence(ob);
}
__device__ __forceinline__ void mma16816(float (&d)[4], const uint32_t (&a)[4], uint32_t b0, uint32_t b1) {
  asm("mma.sync.aligned.m16n8k16.row.col.f32.bf16.bf16.f32 {%0,%1,%2,%3},{%4,%5,%6,%7},{%8,%9},{%0,%1,%2,%3};"
      : "+f"(d[0]), "+f"(d[1]), "+f"(d[2]), "+f"(d[3]) : "r"(a[0]), "r"(a[1]), "r"(a[2]), "r"(a[3]), "r"(b0), "r"(b1));
}
__device__ __forceinline__ void attn_safe(float (&o)[12], const uint32_t (&q)[4], uint32_t sK) {
  const int lane = threadIdx.x & 31;
  const uint32_t ka = sK + (lane >> 4) * 32768 + (lane & 15) * 16;
  float m0 = -INFINITY, m1 = -INFINITY;
#pragma unroll 2
  for (int i = 0; i < 128; i++) {
    uint32_t k[4]; ldsm4(ka + i * 256, k);
    float s0[4] = {0, 0, 0, 0}, s1[4] = {0, 0, 0, 0};
    mma16816(s0, q, k[0], k[2]); mma16816(s1, q, k[1], k[3]);
    m0 = fmaxf(fmaxf(m0, fmaxf(s0[0], s0[1])), fmaxf(s1[0], s1[1])); m1 = fmaxf(fmaxf(m1, fmaxf(s0[2], s0[3])), fmaxf(s1[2], s1[3]));
  }
  m0 = fmaxf(m0, __shfl_xor_sync(~0u, m0, 1)); m0 = fmaxf(m0, __shfl_xor_sync(~0u, m0, 2));
  m1 = fmaxf(m1, __shfl_xor_sync(~0u, m1, 1)); m1 = fmaxf(m1, __shfl_xor_sync(~0u, m1, 2));
  float o0[4] = {0, 0, 0, 0}, o1[4] = {0, 0, 0, 0}, o2[4] = {0, 0, 0, 0};
#pragma unroll 2
  for (int i = 0; i < 128; i++) {
    uint32_t k[4], v[4]; ldsm4(ka + i * 256, k);
    asm volatile("ldmatrix.sync.aligned.m8n8.x4.trans.shared.b16 {%0,%1,%2,%3},[%4];" : "=r"(v[0]), "=r"(v[1]), "=r"(v[2]), "=r"(v[3]) : "r"(ka + 65536 + i * 256) : "memory");
    float s0[4] = {0, 0, 0, 0}, s1[4] = {0, 0, 0, 0};
    mma16816(s0, q, k[0], k[2]); mma16816(s1, q, k[1], k[3]);
    const uint32_t p[4] = {pack_rn(ex2(s0[0] - m0), ex2(s0[1] - m0)), pack_rn(ex2(s0[2] - m1), ex2(s0[3] - m1)),
                           pack_rn(ex2(s1[0] - m0), ex2(s1[1] - m0)), pack_rn(ex2(s1[2] - m1), ex2(s1[3] - m1))};
    mma16816(o0, p, v[0], v[1]); mma16816(o1, p, v[2], v[3]); mma16816(o2, p, 0x3F803F80u, 0x3F803F80u);
  }
#pragma unroll
  for (int i = 0; i < 4; i++) { o[i] = o0[i]; o[4 + i] = o1[i]; o[8 + i] = o2[i]; }
}
__global__ void __cluster_dims__(2, 1, 1) __launch_bounds__(512, 1) k_attn(const bf16* wo, const bf16* w1, const bf16* w3, const bf16* w2, const bf16* __restrict__ cv, const bf16* __restrict__ wm, uint32_t kz) {
  extern __shared__ __align__(1024) uint8_t smem[];
  const uint32_t sK = smem_u32(smem), bars = sK + 5 * 32768;
  const int tid = threadIdx.x, warp = tid >> 5, lane = tid & 31, g = lane >> 2, t = lane & 3;
  pdl_launch();
  if (blockIdx.x < 4) {
    float* cs = (float*)smem;
    cs[tid] = silu_bf(cv[tid]);
    cluster_sync();
    const int b = blockIdx.x;
    float *mv = cs + 512, *rd = cs + 1536;
    auto put8 = [&](float* d, float (&a)[8]) { ((float4*)d)[0] = make_float4(a[0], a[1], a[2], a[3]); ((float4*)d)[1] = make_float4(a[4], a[5], a[6], a[7]); };
    for (int ph = 0; ph < 2; ph++) {
      const int nc = 512 >> ph, n0 = ph ? (b >> 1) * 1536 + 1024 + (b & 1) * 256 : 1536 + (b & 1) * 512, nr = 64 >> ph, r0 = tid / nr * nr;
      float a[8] = {0, 0, 0, 0, 0, 0, 0, 0};
#pragma unroll 16
      for (int r = r0; r < r0 + nr; r++) fma8(a, cs[r], __ldg((const uint4*)(wm + r * 3072 + n0 + (tid & (nr - 1)) * 8)));
      put8(rd + tid * 8, a);
      __syncthreads();
      if (tid < nc) {
        float s = 0;
        for (int i = tid; i < 4096; i += nc) s += rd[i];
        s = mod_fin(s, n0 + tid);
        if (ph || b < 2) g_mod[n0 + tid] = s;
        if (!ph) {
          mv[(b & 1) * 512 + tid] = s;
          asm volatile("{\n.reg .b32 r;\nmapa.shared::cluster.u32 r,%0,%1;\nst.shared::cluster.f32 [r],%2;\n}" ::"r"(smem_u32(mv + (b & 1) * 512 + tid)), "r"((b & 1) ^ 1), "f"(s) : "memory");
        }
      }
      cluster_sync();
    }
    if (tid < 430) {
      const bf16* w = (b >> 1 ? w3 : w1) + (b & 1) * 688 + tid % 86 * 8;
      float u[8] = {0, 0, 0, 0, 0, 0, 0, 0}, v[8] = {0, 0, 0, 0, 0, 0, 0, 0};
#pragma unroll 13
      for (int r = tid / 86; r < 512; r += 5) { const uint4 x = __ldg((const uint4*)(w + r * 1376)); fma8(u, mv[512 + r], x); fma8(v, mv[r], x); }
      put8(rd + tid * 8, u); put8(rd + 3440 + tid * 8, v);
    }
    __syncthreads();
    for (int n = tid; n < 688; n += 512) {
      float u = 0, v = 0;
      for (int i = n; i < 3440; i += 688) { u += rd[i]; v += rd[3440 + i]; }
      g_uv[(b >> 1) * 1408 + (b & 1) * 688 + n] = make_float2(u, v);
    }
    TS(0, 7);
    return;
  }
  const int bid = blockIdx.x - 4, h = bid >> 2, qb = bid & 3;
  TS(2, 0);
  if (tid == 0) { for (int i = 0; i < 8; i++) { mbar_init(bars + 8 * i, 1); mbar_expect(bars + 8 * i, 16384); } fence_init(); }
#pragma unroll
  for (int i = 0; i < 4; i++) *(uint4*)(smem + 131072 + i * 8192 + tid * 16) = make_uint4(0x3F803F80u, 0x3F803F80u, 0x3F803F80u, 0x3F803F80u);
  fence_async();
  cluster_sync();
  pdl_wait();
  TS(2, 1);
  if (tid >= 448) g_modv[bid * 64 + tid - 448] = 0;
  const uint4 km4 = *(const uint4*)(g_kmax + h * 128 + lane * 4);
  const uint32_t* qp = (const uint32_t*)g_qkv + (h * 2 * 2048 + qb * 512 + warp * 16 + g) * 4 + t;
  uint32_t q[4] = {qp[0], qp[32], qp[8192], qp[8192 + 32]};
  auto ldkv = [&]() {
    const int c = warp >> 1, pl = (qb & 1) + (warp & 1) * 2;
    bulk_load_mc(sK + pl * 32768 + c * 4096, g_qkv + ((64 + (pl >> 1) * 64 + h * 2 + (pl & 1)) * 2048 + c * 256) * 8, 4096, bars + 8 * c);
  };
  if (lane == 0 && warp < 4) ldkv();
  const uint32_t qn[4] = {qp[1024], qp[1024 + 32], qp[1024 + 8192], qp[1024 + 8192 + 32]};
  const float kmax = __uint_as_float(__reduce_max_sync(~0u, max(max(km4.x, km4.y), max(km4.z, km4.w))));
  if (lane == 0 && warp >= 4 && kmax != -1.f) ldkv();
#pragma unroll 1
  for (int tile = 0; tile < 2; tile++) {
    const int row = qb * 512 + tile * 256 + warp * 16 + g;
    const float n0 = qsum(blo(q[0]) * blo(q[0]) + bhi(q[0]) * bhi(q[0]) + blo(q[2]) * blo(q[2]) + bhi(q[2]) * bhi(q[2]));
    const float n1 = qsum(blo(q[1]) * blo(q[1]) + bhi(q[1]) * bhi(q[1]) + blo(q[3]) * blo(q[3]) + bhi(q[3]) * bhi(q[3]));
    const float b0 = sqrtf(n0 * kmax) * 1.001f, b1 = sqrtf(n1 * kmax) * 1.001f;
    const float m0 = fmaxf(ceilf(b0 - 100.f), 0.f), m1 = fmaxf(ceilf(b1 - 100.f), 0.f);
    float o[12], ob[12];
    attn_pass(o, ob, q, m0, m1, sK, bars, tile == 0, kz);
    const float f0 = ex2(-m0), f1 = ex2(-m1);
#pragma unroll
    for (int i = 0; i < 12; i++) o[i] = fmaf(o[i], (i & 2) ? f1 : f0, ob[i]);
    bool ok = b0 < 220.f && b1 < 220.f && o[8] >= 0x1p-90f && o[10] >= 0x1p-90f;
#pragma unroll
    for (int i = 0; i < 12; i++) ok = ok && fabsf(o[i]) < INFINITY;
    if (!__all_sync(~0u, ok)) attn_safe(o, q, sK);
    const float r0 = 1.f / o[8], r1 = 1.f / o[10];
    uint32_t* op = (uint32_t*)g_o + (((row >> 6) * 64 + h * 2) * 64 + (row & 63)) * 4 + t;
    op[0] = pack_rn(o[0] * r0, o[1] * r0); op[32] = pack_rn(o[2] * r1, o[3] * r1);
    op[256] = pack_rn(o[4] * r0, o[5] * r0); op[256 + 32] = pack_rn(o[6] * r1, o[7] * r1);
    if (tile == 0 && tid == 32) {
      l2_prefetch((const char*)wo + bid * 4096, 4096);
      l2_prefetch((const char*)w1 + bid * 11008, 11008);
      l2_prefetch((const char*)w3 + bid * 11008, 11008);
      l2_prefetch((const char*)w2 + bid * 11008, 11008);
    }
#pragma unroll
    for (int i = 0; i < 4; i++) q[i] = qn[i];
    TS(2, 3 + tile);
  }
}

constexpr int WO_SMEM = 131072 + 65536 + 256;
__global__ void __cluster_dims__(2, 1, 1) __launch_bounds__(256, 1) k_wo(const __grid_constant__ CUtensorMap mW, const bf16* __restrict__ x) {
  extern __shared__ __align__(1024) uint8_t smem[];
  const uint32_t sA = smem_u32(smem), sB = sA + 65536, bars = sB + 131072;
  const int tid = threadIdx.x, warp = tid >> 5, lane = tid & 31, g = lane >> 2, t = lane & 3;
  const int rb = blockIdx.x >> 3, ct = (blockIdx.x & 3) * 2 + (warp >> 2);
  TS(3, 0);
  pdl_launch();
  auto loadB = [&](int i) { for (int j = 0; j < 2; j++) tma2d(sB + (j * 8 + i) * 8192, &mW, (ct + j) * 64, i * 64, bars + 64 + 8 * i); };
  int nb = 0;
  if (tid == 0) {
    for (int i = 0; i < 17; i++) mbar_init(bars + 8 * i, 1);
    fence_init();
    for (int i = 0; i < 16; i++) mbar_expect(bars + 8 * i, i < 8 ? 8192 : 16384);
    for (; nb < PD0; nb++) loadB(nb);
  }
  __syncwarp();
  cluster_arrive();
  const int lrow = (blockIdx.x & 4) * 16 + (warp & 3) * 16 + g;
  uint32_t xr[16];
  const uint32_t* xp = (const uint32_t*)(x + (rb * 128 + lrow) * 512 + ct * 64) + t;
#pragma unroll
  for (int j = 0; j < 8; j++) { xr[2 * j] = __ldg(xp + j * 4); xr[2 * j + 1] = __ldg(xp + j * 4 + 8 * 256); }
  cluster_wait();
  if (tid == 0) for (; nb < 8 && may_preload(bars + 64 + 8 * (nb - PD0), bars + 128); nb++) loadB(nb);
  __syncwarp();
  pdl_wait();
  if (tid == 32) mbar_arrive(bars + 128);
  if (tid == 0) {
    for (int i = blockIdx.x & 1; i < 8; i += 2) {
      bulk_load_mc(sA + i * 8192, g_o + ((blockIdx.x >> 2) * 64 + i * 8) * 512, 8192, bars + 8 * i);
      for (; nb <= (i | 1); nb++) loadB(nb);
    }
  }
  __syncwarp();
  TS(3, 1);
  float2 ga[8];
  uint32_t sc[8];
#pragma unroll
  for (int j = 0; j < 8; j++) {
    ga[j] = *(const float2*)(g_mod + 1024 + ct * 64 + j * 8 + t * 2);
    const float2 v = *(const float2*)(g_mod + 2048 + ct * 64 + j * 8 + t * 2);
    sc[j] = pack_rn(v.x, v.y);
  }
  float acc[32];
  const uint64_t da = mk_desc(sA, 1024, 128, 0), db = mk_desc(sB + (warp >> 2) * 65536, 8192, 1024, 1);
#pragma unroll
  for (int c = 0; c < 8; c++) {
    mbar_wait(bars + 64 + 8 * c, 0); mbar_wait(bars + 8 * c, 0);
    if (c == 0) TS(3, 2);
    wg_fence();
#pragma unroll
    for (int k = 0; k < 4; k++) wgmma_ss_n64_t1(acc, da + (c * 4 + k) * 128, db + (c * 4 + k) * 128, c + k);
    wg_commit();
  }
  wg_wait<0>();
  reg_fence(acc);
  TS(3, 3);
  uint32_t* o = (uint32_t*)g_x1 + ((rb * 64 + ct * 8) * 128 + lrow) * 4 + t;
  uint32_t* oa = (uint32_t*)g_a + ((rb * 64 + ct * 8) * 128 + lrow) * 4 + t;
  float s0 = 0, s1 = 0;
#pragma unroll
  for (int j = 0; j < 8; j++) {
    xr[2 * j] = pack_rn(fmaf(ga[j].x, acc[4 * j], blo(xr[2 * j])), fmaf(ga[j].y, acc[4 * j + 1], bhi(xr[2 * j])));
    xr[2 * j + 1] = pack_rn(fmaf(ga[j].x, acc[4 * j + 2], blo(xr[2 * j + 1])), fmaf(ga[j].y, acc[4 * j + 3], bhi(xr[2 * j + 1])));
    uint32_t a0, a1;
    asm("mul.rn.bf16x2 %0,%1,%2;" : "=r"(a0) : "r"(xr[2 * j]), "r"(sc[j]));
    asm("mul.rn.bf16x2 %0,%1,%2;" : "=r"(a1) : "r"(xr[2 * j + 1]), "r"(sc[j]));
    oa[j * 512] = a0; oa[j * 512 + 32] = a1;
    o[j * 512] = xr[2 * j]; o[j * 512 + 32] = xr[2 * j + 1];
    s0 += blo(xr[2 * j]) + bhi(xr[2 * j]); s1 += blo(xr[2 * j + 1]) + bhi(xr[2 * j + 1]);
  }
  const float m0 = qsum(s0) * (1.f / 64), m1 = qsum(s1) * (1.f / 64);
  float v0 = 0, v1 = 0;
#pragma unroll
  for (int j = 0; j < 8; j++) {
    float d;
    d = blo(xr[2 * j]) - m0; v0 += d * d; d = bhi(xr[2 * j]) - m0; v0 += d * d;
    d = blo(xr[2 * j + 1]) - m1; v1 += d * d; d = bhi(xr[2 * j + 1]) - m1; v1 += d * d;
  }
  v0 = qsum(v0); v1 = qsum(v1);
  if (t == 0) g_st[(rb * 128 + lrow) * 8 + ct] = make_float2(m0, v0);
  if (t == 1) g_st[(rb * 128 + lrow + 8) * 8 + ct] = make_float2(m1, v1);
  TS(3, 4);
}

constexpr int W2_SMEM = 6 * 32768 + 32768 + 256;
__global__ void __cluster_dims__(2, 1, 1) __launch_bounds__(288, 1) k_w2(const __grid_constant__ CUtensorMap mW, bf16* __restrict__ out) {
  extern __shared__ __align__(1024) uint8_t smem[];
  const uint32_t sR = smem_u32(smem), sX = sR + 6 * 32768, bF = sX + 32768, bE = bF + 48, bX = bF + 96, bB = bF + 160, bG = bF + 208;
  const int tid = threadIdx.x, warp = tid >> 5, lane = tid & 31, g = lane >> 2, t = lane & 3;
  const int kh = blockIdx.x & 1, ct = (blockIdx.x >> 1) & 3, rb = blockIdx.x >> 3;
  TS(5, 0);
  pdl_launch();
  if (tid == 256) {
    for (int i = 0; i < 6; i++) { mbar_init(bF + 8 * i, 1); mbar_init(bE + 8 * i, 8); mbar_init(bB + 8 * i, 1); }
    mbar_init(bG, 1);
    for (int i = 0; i < 8; i++) { mbar_init(bX + 8 * i, 1); mbar_expect(bX + 8 * i, 4096); }
    fence_init();
  }
  __syncthreads();
  asm volatile("barrier.cluster.arrive.relaxed.aligned;" ::: "memory");
  if (warp == 8) {
    if (lane == 0) {
      auto abytes = [&](int s) { return (kh == 1 && s == 10) ? 8192 : 16384; };
      auto loadB = [&](int s) {
        const int st = s % 6;
        mbar_expect(bB + 8 * st, 16384);
        for (int j = 0; j < 2; j++) tma2d(sR + st * 32768 + 16384 + j * 8192, &mW, ct * 128 + j * 64, kh * 704 + s * 64, bB + 8 * st);
      };
      auto loadA = [&](int s) { mbar_expect(bF + 8 * (s % 6), abytes(s)); bulk_load(sR + (s % 6) * 32768, g_h + (rb * 172 + kh * 88 + s * 8) * 1024, abytes(s), bF + 8 * (s % 6)); };
      int nb = 0;
      for (; nb < 6 && (nb < PD2 || may_preload(bB + 8 * (nb - PD2), bG)); nb++) loadB(nb);
      pdl_wait();
      for (int s = 0; s < 6; s++) { loadA(s); if (s >= nb) loadB(s); }
      for (int s = 6; s < 11; s++) { mbar_wait(bE + 8 * (s - 6), 0); loadB(s); loadA(s); }
    }
    __syncwarp();
    cluster_wait();
    return;
  }
  pdl_wait();
  if (tid == 32) mbar_arrive(bG);
  TS(5, 1);
  const int lrow = warp * 16 + g;
  uint32_t xr[16];
  float2 gb[8];
  const uint32_t* xp = (const uint32_t*)g_x1 + ((rb * 64 + ct * 16 + kh * 8) * 128 + lrow) * 4 + t;
#pragma unroll
  for (int j = 0; j < 8; j++) {
    xr[2 * j] = xp[j * 512]; xr[2 * j + 1] = xp[j * 512 + 32];
    gb[j] = *(const float2*)(g_mod + 2560 + ct * 128 + kh * 64 + j * 8 + t * 2);
  }
  float acc[64];
#pragma unroll 1
  for (int s = 0; s < 11; s++) {
    const int st = s % 6;
    mbar_wait(bB + 8 * st, s >= 6); mbar_wait(bF + 8 * st, s >= 6);
    const uint64_t da = mk_desc(sR + st * 32768 + (warp >> 2) * 1024, 2048, 128, 0), db = mk_desc(sR + st * 32768 + 16384, 8192, 1024, 1);
    if (s == 0) TS(5, 2);
    wg_fence();
    wgmma_ss_n128_t1(acc, da, db, s);
    wgmma_ss_n128_t1(acc, da + 256, db + 128, 1);
    wgmma_ss_n128_t1(acc, da + 512, db + 256, 1);
    wgmma_ss_n128_t1(acc, da + 768, db + 384, 1);
    wg_commit();
    wg_wait<1>();
    if (s > 0 && s < 6 && lane == 0) mbar_arrive(bE + 8 * (s - 1));
  }
  wg_wait<0>();
  reg_fence(acc);
  TS(5, 3);
  asm volatile("barrier.cluster.wait.aligned;" ::: "memory");
  uint32_t rem, rbar;
  asm("mapa.shared::cluster.u32 %0,%1,%2;" : "=r"(rbar) : "r"(bX + warp * 8), "r"(kh ^ 1));
  asm("mapa.shared::cluster.u32 %0,%1,%2;" : "=r"(rem) : "r"(sX + warp * 4096 + lane * 16), "r"(kh ^ 1));
#pragma unroll
  for (int j = 0; j < 8; j++) {
    float v[4];
#pragma unroll
    for (int i = 0; i < 4; i++) { v[i] = kh ? acc[4 * j + i] : acc[32 + 4 * j + i]; acc[4 * j + i] = kh ? acc[32 + 4 * j + i] : acc[4 * j + i]; }
    asm volatile("st.async.weak.shared::cluster.mbarrier::complete_tx::bytes.v4.f32 [%0],{%1,%2,%3,%4},[%5];" ::"r"(rem + j * 512), "f"(v[0]), "f"(v[1]), "f"(v[2]), "f"(v[3]), "r"(rbar) : "memory");
  }
  mbar_wait(bX + warp * 8, 0);
  TS(5, 5);
  const uint32_t sw = sX + warp * 4096;
#pragma unroll
  for (int j = 0; j < 8; j++) {
    const float4 p = *(const float4*)(smem + 6 * 32768 + warp * 4096 + j * 512 + lane * 16);
    xr[2 * j] = pack_rn(fmaf(gb[j].x, acc[4 * j] + p.x, blo(xr[2 * j])), fmaf(gb[j].y, acc[4 * j + 1] + p.y, bhi(xr[2 * j])));
    xr[2 * j + 1] = pack_rn(fmaf(gb[j].x, acc[4 * j + 2] + p.z, blo(xr[2 * j + 1])), fmaf(gb[j].y, acc[4 * j + 3] + p.w, bhi(xr[2 * j + 1])));
  }
  __syncwarp();
#pragma unroll
  for (int j = 1; j < 8; j += 2) {
    asm volatile("stmatrix.sync.aligned.m8n8.x4.shared.b16 [%0],{%1,%2,%3,%4};" ::"r"(sw + (lane & 15) * 128 + (((j - 1 + (lane >> 4)) ^ (lane & 7)) << 4)),
                            "r"(xr[2 * j - 2]), "r"(xr[2 * j - 1]), "r"(xr[2 * j]), "r"(xr[2 * j + 1]) : "memory");
  }
  __syncwarp();
#pragma unroll
  for (int i = 0; i < 4; i++) {
    const int r = i * 4 + (lane >> 3);
    *(uint4*)(out + (rb * 128 + warp * 16 + r) * 512 + ct * 128 + kh * 64 + (lane & 7) * 8) = *(const uint4*)(smem + 6 * 32768 + warp * 4096 + r * 128 + (((lane ^ r) & 7) << 4));
  }
  TS(5, 4);
}

typedef CUresult (*EncFn)(CUtensorMap*, CUtensorMapDataType, cuuint32_t, void*, const cuuint64_t*, const cuuint64_t*, const cuuint32_t*,
                          const cuuint32_t*, CUtensorMapInterleave, CUtensorMapSwizzle, CUtensorMapL2promotion, CUtensorMapFloatOOBfill);
static void mk_map(EncFn f, CUtensorMap* m, const void* p, int rows, int cols, int box_rows) {
  cuuint64_t dim[2] = {(cuuint64_t)cols, (cuuint64_t)rows}, str[1] = {(cuuint64_t)cols * 2};
  cuuint32_t box[2] = {64, (cuuint32_t)box_rows}, es[2] = {1, 1};
  f(m, CU_TENSOR_MAP_DATA_TYPE_BFLOAT16, 2, (void*)p, dim, str, box, es, CU_TENSOR_MAP_INTERLEAVE_NONE, CU_TENSOR_MAP_SWIZZLE_128B,
    CU_TENSOR_MAP_L2_PROMOTION_L2_128B, CU_TENSOR_MAP_FLOAT_OOB_FILL_NONE);
}
template <typename... KA, typename... A>
static void launch(void (*k)(KA...), int grid, int block, int smem, bool pdl, A... args) {
  cudaLaunchConfig_t cfg = {};
  cfg.gridDim = dim3(grid); cfg.blockDim = dim3(block); cfg.dynamicSmemBytes = smem; cfg.stream = cudaStreamPerThread;
  cudaLaunchAttribute at[1];
  at[0].id = cudaLaunchAttributeProgrammaticStreamSerialization; at[0].val.programmaticStreamSerializationAllowed = 1;
  cfg.attrs = at; cfg.numAttrs = pdl ? 1 : 0;
  cudaLaunchKernelEx(&cfg, k, args...);
}
extern "C" void kernel_launch(void* const* d_in, const int* in_sizes, int n_in, void* d_out, int out_size) {
  const bf16 *x = (const bf16*)d_in[0], *wqkv = (const bf16*)d_in[1], *wo = (const bf16*)d_in[2], *w1 = (const bf16*)d_in[4],
             *w3 = (const bf16*)d_in[5], *w2 = (const bf16*)d_in[6], *c = (const bf16*)d_in[7], *wmod = (const bf16*)d_in[8];
  void* fp = nullptr;
  cudaDriverEntryPointQueryResult qr;
  cudaGetDriverEntryPoint("cuTensorMapEncodeTiled", &fp, cudaEnableDefault, &qr);
  EncFn f = (EncFn)fp;
  CUtensorMap mX, mQ, mO, m1, m3, m2;
  mk_map(f, &mX, x, S_, D_, 128); mk_map(f, &mQ, wqkv, D_, 3 * D_, 64); mk_map(f, &mO, wo, D_, D_, 64);
  mk_map(f, &m1, w1, D_, F_, 32); mk_map(f, &m3, w3, D_, F_, 32); mk_map(f, &m2, w2, F_, D_, 64);
  cudaFuncSetAttribute(k_lngemm<false>, cudaFuncAttributeMaxDynamicSharedMemorySize, LN_SMEM);
  cudaFuncSetAttribute(k_lngemm<true>, cudaFuncAttributeMaxDynamicSharedMemorySize, LN_SMEM);
  cudaFuncSetAttribute(k_attn, cudaFuncAttributeMaxDynamicSharedMemorySize, AT_SMEM);
  cudaFuncSetAttribute(k_wo, cudaFuncAttributeMaxDynamicSharedMemorySize, WO_SMEM);
  cudaFuncSetAttribute(k_w2, cudaFuncAttributeMaxDynamicSharedMemorySize, W2_SMEM);
  launch(k_lngemm<false>, 128, 384, LN_SMEM, false, mX, mQ, mQ, c, wmod, x, wqkv);
  launch(k_attn, 132, 512, AT_SMEM, true, wo, w1, w3, w2, c, wmod, 0u);
  launch(k_wo, 128, 256, WO_SMEM, true, mO, x);
  launch(k_lngemm<true>, 128, 384, LN_SMEM, true, mX, m1, m3, c, wmod, x, wqkv);
  launch(k_w2, 128, 288, W2_SMEM, true, m2, (bf16*)d_out);
}
```

```cpp
#include <cuda_runtime.h>
#include <cuda_bf16.h>
#include <cuda.h>
#include <stdint.h>
typedef __nv_bfloat16 bf16;
constexpr int S_ = 2048, D_ = 512, F_ = 1376;
__device__ __align__(1024) float g_mod[3072];
__device__ __align__(1024) uint32_t g_modv[4096 + 4096];
__device__ __align__(1024) bf16 g_qkv[192 * 2048 * 8];
__device__ __align__(1024) float g_kmax[32 * 128];
__device__ __align__(1024) bf16 g_o[16 * 64 * 128 * 8];
__device__ __align__(1024) bf16 g_x1[16 * 64 * 128 * 8];
__device__ __align__(1024) bf16 g_a[16 * 64 * 128 * 8];
__device__ __align__(1024) float2 g_uv[2 * 1408];
__device__ __align__(1024) float2 g_st[2048 * 8];
__device__ __align__(1024) bf16 g_h[16 * 172 * 128 * 8];

__device__ __forceinline__ uint32_t smem_u32(const void* p) { return (uint32_t)__cvta_generic_to_shared(p); }
__device__ __forceinline__ void mbar_init(uint32_t b, int n) { asm volatile("mbarrier.init.shared::cta.b64 [%0],%1;" ::"r"(b), "r"(n) : "memory"); }
__device__ __forceinline__ void mbar_expect(uint32_t b, int bytes) { asm volatile("mbarrier.arrive.expect_tx.shared::cta.b64 _,[%0],%1;" ::"r"(b), "r"(bytes) : "memory"); }
__device__ __forceinline__ void mbar_arrive(uint32_t b) { asm volatile("mbarrier.arrive.shared::cta.b64 _,[%0];" ::"r"(b) : "memory"); }
__device__ __forceinline__ void mbar_wait(uint32_t b, int parity) {
  asm volatile("{\n.reg .pred p;\n.reg .u32 n;\nmov.u32 n,0;\nLW:\nmbarrier.try_wait.parity.shared::cta.b64 p,[%0],%1;\n@p bra LD;\n"
               "add.u32 n,n,1;\nsetp.lt.u32 p,n,4194304;\n@p bra LW;\nLD:\n}\n" ::"r"(b), "r"(parity) : "memory");
}
__device__ __forceinline__ void fence_init() { asm volatile("fence.mbarrier_init.release.cluster;" ::: "memory"); }
__device__ __forceinline__ void fence_async() { asm volatile("fence.proxy.async.shared::cta;" ::: "memory"); }
__device__ __forceinline__ void bulk_load(uint32_t dst, const void* src, int bytes, uint32_t bar) {
  asm volatile("cp.async.bulk.shared::cluster.global.mbarrier::complete_tx::bytes [%0],[%1],%2,[%3];" ::"r"(dst), "l"(src), "r"(bytes), "r"(bar) : "memory");
}
__device__ __forceinline__ void tma2d(uint32_t dst, const CUtensorMap* m, int c0, int c1, uint32_t bar) {
  asm volatile("cp.async.bulk.tensor.2d.shared::cluster.global.mbarrier::complete_tx::bytes [%0],[%1,{%3,%4}],[%2];" ::"r"(dst), "l"(m), "r"(bar), "r"(c0), "r"(c1) : "memory");
}
__device__ __forceinline__ void bulk_load_mc(uint32_t dst, const void* src, int bytes, uint32_t bar) {
  asm volatile("cp.async.bulk.shared::cluster.global.mbarrier::complete_tx::bytes.multicast::cluster [%0],[%1],%2,[%3],%4;" ::"r"(dst), "l"(src), "r"(bytes), "r"(bar), "h"((uint16_t)3) : "memory");
}
__device__ __forceinline__ void tma2d_mc(uint32_t dst, const CUtensorMap* m, int c0, int c1, uint32_t bar) {
  asm volatile("cp.async.bulk.tensor.2d.shared::cluster.global.mbarrier::complete_tx::bytes.multicast::cluster [%0],[%1,{%3,%4}],[%2],%5;" ::"r"(dst), "l"(m), "r"(bar), "r"(c0), "r"(c1), "h"((uint16_t)3) : "memory");
}
__device__ __forceinline__ void cluster_arrive() { asm volatile("barrier.cluster.arrive.relaxed.aligned;" ::: "memory"); }
__device__ __forceinline__ void cluster_wait() { asm volatile("barrier.cluster.wait.aligned;" ::: "memory"); }
__device__ __forceinline__ void cluster_sync() { asm volatile("barrier.cluster.arrive.release.aligned;\nbarrier.cluster.wait.acquire.aligned;" ::: "memory"); }
__device__ __forceinline__ bool mbar_test(uint32_t b, uint32_t ph) {
  uint32_t ok; asm volatile("{\n.reg .pred p;\nmbarrier.test_wait.parity.shared::cta.b64 p,[%1],%2;\nselp.u32 %0,1,0,p;\n}" : "=r"(ok) : "r"(b), "r"(ph) : "memory"); return ok;
}
__device__ __forceinline__ bool may_preload(uint32_t landed, uint32_t go) {
  for (int i = 0; i < 100000; i++) { if (mbar_test(go, 0)) return false; if (mbar_test(landed, 0)) return true; }
  return false;
}
#define PD1 2
#define PD0 3
#define PD2 2
__device__ __forceinline__ void l2_prefetch(const void* p, int bytes) { asm volatile("cp.async.bulk.prefetch.L2.global [%0],%1;" ::"l"(p), "r"(bytes) : "memory"); }
__device__ __forceinline__ void pdl_launch() { asm volatile("griddepcontrol.launch_dependents;" ::: "memory"); }
__device__ __forceinline__ void pdl_wait() { asm volatile("griddepcontrol.wait;" ::: "memory"); }
__device__ __forceinline__ void wg_fence() { asm volatile("wgmma.fence.sync.aligned;" ::: "memory"); }
__device__ __forceinline__ void wg_commit() { asm volatile("wgmma.commit_group.sync.aligned;" ::: "memory"); }
template <int N> __device__ __forceinline__ void wg_wait() { asm volatile("wgmma.wait_group.sync.aligned %0;" ::"n"(N) : "memory"); }
template <int N> __device__ __forceinline__ void reg_fence(float (&d)[N]) {
#pragma unroll
  for (int i = 0; i < N; i++) asm volatile("" : "+f"(d[i])::"memory");
}
template <int N> __device__ __forceinline__ void zero(float (&d)[N]) {
#pragma unroll
  for (int i = 0; i < N; i++) d[i] = 0.f;
  reg_fence(d);
}
__device__ __forceinline__ uint64_t mk_desc(uint32_t addr, uint32_t lbo, uint32_t sbo, uint32_t mode) {
  return (uint64_t)((addr >> 4) & 0x3FFF) | ((uint64_t)(lbo >> 4) << 16) | ((uint64_t)(sbo >> 4) << 32) | ((uint64_t)mode << 62);
}
__device__ __forceinline__ void ldsm4(uint32_t a, uint32_t (&r)[4]) {
  asm volatile("ldmatrix.sync.aligned.m8n8.x4.shared.b16 {%0,%1,%2,%3},[%4];" : "=r"(r[0]), "=r"(r[1]), "=r"(r[2]), "=r"(r[3]) : "r"(a) : "memory");
}
__device__ __forceinline__ uint32_t pack_rn(float lo, float hi) { uint32_t r; asm("cvt.rn.bf16x2.f32 %0,%1,%2;" : "=r"(r) : "f"(hi), "f"(lo)); return r; }
__device__ __forceinline__ uint32_t pack_rz(float lo, float hi) { uint32_t r; asm("cvt.rz.bf16x2.f32 %0,%1,%2;" : "=r"(r) : "f"(hi), "f"(lo)); return r; }
__device__ __forceinline__ float blo(uint32_t u) { return __uint_as_float(u << 16); }
__device__ __forceinline__ float bhi(uint32_t u) { return __uint_as_float(u & 0xFFFF0000u); }
__device__ __forceinline__ float rbf(float x) { return __bfloat162float(__float2bfloat16_rn(x)); }
__device__ __forceinline__ float qsum(float v) { v += __shfl_xor_sync(~0u, v, 1); return v + __shfl_xor_sync(~0u, v, 2); }
__device__ __forceinline__ float ex2(float x) { float r; asm("ex2.approx.ftz.f32 %0,%1;" : "=f"(r) : "f"(x)); return r; }
#define TS(k, i)
__device__ __forceinline__ void wgmma_rs_n176_t1(float (&d)[88],uint32_t a0,uint32_t a1,uint32_t a2,uint32_t a3,uint64_t db,int sc){
  asm volatile("{\n.reg .pred p;\nsetp.ne.b32 p,%93,0;\n"
    "wgmma.mma_async.sync.aligned.m64n176k16.f32.bf16.bf16 {%0,%1,%2,%3,%4,%5,%6,%7,%8,%9,%10,%11,%12,%13,%14,%15,%16,%17,%18,%19,%20,%21,%22,%23,%24,%25,%26,%27,%28,%29,%30,%31,%32,%33,%34,%35,%36,%37,%38,%39,%40,%41,%42,%43,%44,%45,%46,%47,%48,%49,%50,%51,%52,%53,%54,%55,%56,%57,%58,%59,%60,%61,%62,%63,%64,%65,%66,%67,%68,%69,%70,%71,%72,%73,%74,%75,%76,%77,%78,%79,%80,%81,%82,%83,%84,%85,%86,%87},{%88,%89,%90,%91},%92,p,1,1,1;\n}\n"
    :"+f"(d[0]),"+f"(d[1]),"+f"(d[2]),"+f"(d[3]),"+f"(d[4]),"+f"(d[5]),"+f"(d[6]),"+f"(d[7]),"+f"(d[8]),"+f"(d[9]),"+f"(d[10]),"+f"(d[11]),"+f"(d[12]),"+f"(d[13]),"+f"(d[14]),"+f"(d[15]),"+f"(d[16]),"+f"(d[17]),"+f"(d[18]),"+f"(d[19]),"+f"(d[20]),"+f"(d[21]),"+f"(d[22]),"+f"(d[23]),"+f"(d[24]),"+f"(d[25]),"+f"(d[26]),"+f"(d[27]),"+f"(d[28]),"+f"(d[29]),"+f"(d[30]),"+f"(d[31]),"+f"(d[32]),"+f"(d[33]),"+f"(d[34]),"+f"(d[35]),"+f"(d[36]),"+f"(d[37]),"+f"(d[38]),"+f"(d[39]),"+f"(d[40]),"+f"(d[41]),"+f"(d[42]),"+f"(d[43]),"+f"(d[44]),"+f"(d[45]),"+f"(d[46]),"+f"(d[47]),"+f"(d[48]),"+f"(d[49]),"+f"(d[50]),"+f"(d[51]),"+f"(d[52]),"+f"(d[53]),"+f"(d[54]),"+f"(d[55]),"+f"(d[56]),"+f"(d[57]),"+f"(d[58]),"+f"(d[59]),"+f"(d[60]),"+f"(d[61]),"+f"(d[62]),"+f"(d[63]),"+f"(d[64]),"+f"(d[65]),"+f"(d[66]),"+f"(d[67]),"+f"(d[68]),"+f"(d[69]),"+f"(d[70]),"+f"(d[71]),"+f"(d[72]),"+f"(d[73]),"+f"(d[74]),"+f"(d[75]),"+f"(d[76]),"+f"(d[77]),"+f"(d[78]),"+f"(d[79]),"+f"(d[80]),"+f"(d[81]),"+f"(d[82]),"+f"(d[83]),"+f"(d[84]),"+f"(d[85]),"+f"(d[86]),"+f"(d[87])
    :"r"(a0),"r"(a1),"r"(a2),"r"(a3),"l"(db),"r"(sc));
}
__device__ __forceinline__ void wgmma_rs_n192_t1(float (&d)[96],uint32_t a0,uint32_t a1,uint32_t a2,uint32_t a3,uint64_t db,int sc){
  asm volatile("{\n.reg .pred p;\nsetp.ne.b32 p,%101,0;\n"
    "wgmma.mma_async.sync.aligned.m64n192k16.f32.bf16.bf16 {%0,%1,%2,%3,%4,%5,%6,%7,%8,%9,%10,%11,%12,%13,%14,%15,%16,%17,%18,%19,%20,%21,%22,%23,%24,%25,%26,%27,%28,%29,%30,%31,%32,%33,%34,%35,%36,%37,%38,%39,%40,%41,%42,%43,%44,%45,%46,%47,%48,%49,%50,%51,%52,%53,%54,%55,%56,%57,%58,%59,%60,%61,%62,%63,%64,%65,%66,%67,%68,%69,%70,%71,%72,%73,%74,%75,%76,%77,%78,%79,%80,%81,%82,%83,%84,%85,%86,%87,%88,%89,%90,%91,%92,%93,%94,%95},{%96,%97,%98,%99},%100,p,1,1,1;\n}\n"
    :"+f"(d[0]),"+f"(d[1]),"+f"(d[2]),"+f"(d[3]),"+f"(d[4]),"+f"(d[5]),"+f"(d[6]),"+f"(d[7]),"+f"(d[8]),"+f"(d[9]),"+f"(d[10]),"+f"(d[11]),"+f"(d[12]),"+f"(d[13]),"+f"(d[14]),"+f"(d[15]),"+f"(d[16]),"+f"(d[17]),"+f"(d[18]),"+f"(d[19]),"+f"(d[20]),"+f"(d[21]),"+f"(d[22]),"+f"(d[23]),"+f"(d[24]),"+f"(d[25]),"+f"(d[26]),"+f"(d[27]),"+f"(d[28]),"+f"(d[29]),"+f"(d[30]),"+f"(d[31]),"+f"(d[32]),"+f"(d[33]),"+f"(d[34]),"+f"(d[35]),"+f"(d[36]),"+f"(d[37]),"+f"(d[38]),"+f"(d[39]),"+f"(d[40]),"+f"(d[41]),"+f"(d[42]),"+f"(d[43]),"+f"(d[44]),"+f"(d[45]),"+f"(d[46]),"+f"(d[47]),"+f"(d[48]),"+f"(d[49]),"+f"(d[50]),"+f"(d[51]),"+f"(d[52]),"+f"(d[53]),"+f"(d[54]),"+f"(d[55]),"+f"(d[56]),"+f"(d[57]),"+f"(d[58]),"+f"(d[59]),"+f"(d[60]),"+f"(d[61]),"+f"(d[62]),"+f"(d[63]),"+f"(d[64]),"+f"(d[65]),"+f"(d[66]),"+f"(d[67]),"+f"(d[68]),"+f"(d[69]),"+f"(d[70]),"+f"(d[71]),"+f"(d[72]),"+f"(d[73]),"+f"(d[74]),"+f"(d[75]),"+f"(d[76]),"+f"(d[77]),"+f"(d[78]),"+f"(d[79]),"+f"(d[80]),"+f"(d[81]),"+f"(d[82]),"+f"(d[83]),"+f"(d[84]),"+f"(d[85]),"+f"(d[86]),"+f"(d[87]),"+f"(d[88]),"+f"(d[89]),"+f"(d[90]),"+f"(d[91]),"+f"(d[92]),"+f"(d[93]),"+f"(d[94]),"+f"(d[95])
    :"r"(a0),"r"(a1),"r"(a2),"r"(a3),"l"(db),"r"(sc));
}
__device__ __forceinline__ void wgmma_rs_n24_t1(float (&d)[12],uint32_t a0,uint32_t a1,uint32_t a2,uint32_t a3,uint64_t db,int sc){
  asm volatile("{\n.reg .pred p;\nsetp.ne.b32 p,%17,0;\n"
    "wgmma.mma_async.sync.aligned.m64n24k16.f32.bf16.bf16 {%0,%1,%2,%3,%4,%5,%6,%7,%8,%9,%10,%11},{%12,%13,%14,%15},%16,p,1,1,1;\n}\n"
    :"+f"(d[0]),"+f"(d[1]),"+f"(d[2]),"+f"(d[3]),"+f"(d[4]),"+f"(d[5]),"+f"(d[6]),"+f"(d[7]),"+f"(d[8]),"+f"(d[9]),"+f"(d[10]),"+f"(d[11])
    :"r"(a0),"r"(a1),"r"(a2),"r"(a3),"l"(db),"r"(sc));
}
__device__ __forceinline__ void wgmma_rs_n64_t0(float (&d)[32],uint32_t a0,uint32_t a1,uint32_t a2,uint32_t a3,uint64_t db,int sc){
  asm volatile("{\n.reg .pred p;\nsetp.ne.b32 p,%37,0;\n"
    "wgmma.mma_async.sync.aligned.m64n64k16.f32.bf16.bf16 {%0,%1,%2,%3,%4,%5,%6,%7,%8,%9,%10,%11,%12,%13,%14,%15,%16,%17,%18,%19,%20,%21,%22,%23,%24,%25,%26,%27,%28,%29,%30,%31},{%32,%33,%34,%35},%36,p,1,1,0;\n}\n"
    :"+f"(d[0]),"+f"(d[1]),"+f"(d[2]),"+f"(d[3]),"+f"(d[4]),"+f"(d[5]),"+f"(d[6]),"+f"(d[7]),"+f"(d[8]),"+f"(d[9]),"+f"(d[10]),"+f"(d[11]),"+f"(d[12]),"+f"(d[13]),"+f"(d[14]),"+f"(d[15]),"+f"(d[16]),"+f"(d[17]),"+f"(d[18]),"+f"(d[19]),"+f"(d[20]),"+f"(d[21]),"+f"(d[22]),"+f"(d[23]),"+f"(d[24]),"+f"(d[25]),"+f"(d[26]),"+f"(d[27]),"+f"(d[28]),"+f"(d[29]),"+f"(d[30]),"+f"(d[31])
    :"r"(a0),"r"(a1),"r"(a2),"r"(a3),"l"(db),"r"(sc));
}
__device__ __forceinline__ void wgmma_ss_n128_t1(float (&d)[64],uint64_t da,uint64_t db,int sc){
  asm volatile("{\n.reg .pred p;\nsetp.ne.b32 p,%66,0;\n"
    "wgmma.mma_async.sync.aligned.m64n128k16.f32.bf16.bf16 {%0,%1,%2,%3,%4,%5,%6,%7,%8,%9,%10,%11,%12,%13,%14,%15,%16,%17,%18,%19,%20,%21,%22,%23,%24,%25,%26,%27,%28,%29,%30,%31,%32,%33,%34,%35,%36,%37,%38,%39,%40,%41,%42,%43,%44,%45,%46,%47,%48,%49,%50,%51,%52,%53,%54,%55,%56,%57,%58,%59,%60,%61,%62,%63},%64,%65,p,1,1,0,1;\n}\n"
    :"+f"(d[0]),"+f"(d[1]),"+f"(d[2]),"+f"(d[3]),"+f"(d[4]),"+f"(d[5]),"+f"(d[6]),"+f"(d[7]),"+f"(d[8]),"+f"(d[9]),"+f"(d[10]),"+f"(d[11]),"+f"(d[12]),"+f"(d[13]),"+f"(d[14]),"+f"(d[15]),"+f"(d[16]),"+f"(d[17]),"+f"(d[18]),"+f"(d[19]),"+f"(d[20]),"+f"(d[21]),"+f"(d[22]),"+f"(d[23]),"+f"(d[24]),"+f"(d[25]),"+f"(d[26]),"+f"(d[27]),"+f"(d[28]),"+f"(d[29]),"+f"(d[30]),"+f"(d[31]),"+f"(d[32]),"+f"(d[33]),"+f"(d[34]),"+f"(d[35]),"+f"(d[36]),"+f"(d[37]),"+f"(d[38]),"+f"(d[39]),"+f"(d[40]),"+f"(d[41]),"+f"(d[42]),"+f"(d[43]),"+f"(d[44]),"+f"(d[45]),"+f"(d[46]),"+f"(d[47]),"+f"(d[48]),"+f"(d[49]),"+f"(d[50]),"+f"(d[51]),"+f"(d[52]),"+f"(d[53]),"+f"(d[54]),"+f"(d[55]),"+f"(d[56]),"+f"(d[57]),"+f"(d[58]),"+f"(d[59]),"+f"(d[60]),"+f"(d[61]),"+f"(d[62]),"+f"(d[63])
    :"l"(da),"l"(db),"r"(sc));
}
__device__ __forceinline__ void wgmma_ss_n64_t1(float (&d)[32],uint64_t da,uint64_t db,int sc){
  asm volatile("{\n.reg .pred p;\nsetp.ne.b32 p,%34,0;\n"
    "wgmma.mma_async.sync.aligned.m64n64k16.f32.bf16.bf16 {%0,%1,%2,%3,%4,%5,%6,%7,%8,%9,%10,%11,%12,%13,%14,%15,%16,%17,%18,%19,%20,%21,%22,%23,%24,%25,%26,%27,%28,%29,%30,%31},%32,%33,p,1,1,0,1;\n}\n"
    :"+f"(d[0]),"+f"(d[1]),"+f"(d[2]),"+f"(d[3]),"+f"(d[4]),"+f"(d[5]),"+f"(d[6]),"+f"(d[7]),"+f"(d[8]),"+f"(d[9]),"+f"(d[10]),"+f"(d[11]),"+f"(d[12]),"+f"(d[13]),"+f"(d[14]),"+f"(d[15]),"+f"(d[16]),"+f"(d[17]),"+f"(d[18]),"+f"(d[19]),"+f"(d[20]),"+f"(d[21]),"+f"(d[22]),"+f"(d[23]),"+f"(d[24]),"+f"(d[25]),"+f"(d[26]),"+f"(d[27]),"+f"(d[28]),"+f"(d[29]),"+f"(d[30]),"+f"(d[31])
    :"l"(da),"l"(db),"r"(sc));
}

__device__ __forceinline__ float silu_bf(bf16 c) { const float x = __bfloat162float(c); return rbf(x / (1.f + __expf(-x))); }
__device__ __forceinline__ void fma8(float (&a)[8], float s, const uint4& v) {
  a[0] += s * blo(v.x); a[1] += s * bhi(v.x); a[2] += s * blo(v.y); a[3] += s * bhi(v.y);
  a[4] += s * blo(v.z); a[5] += s * bhi(v.z); a[6] += s * blo(v.w); a[7] += s * bhi(v.w);
}
__device__ __forceinline__ float red8(float (&a)[8], int lane) {
#pragma unroll
  for (int w = 4; w >= 1; w >>= 1) {
    const bool up = lane & (w * 4);
#pragma unroll
    for (int j = 0; j < w; j++) a[j] = (up ? a[j + w] : a[j]) + __shfl_xor_sync(~0u, up ? a[j] : a[j + w], w * 4);
  }
  return a[0];
}
__device__ __forceinline__ float mod_fin(float s, int n) { s = rbf(s); return ((n >> 9) == 1 || (n >> 9) == 4) ? rbf(1.f + s) : s; }
__device__ __forceinline__ void poll(uint2& a, uint2& b, float (&w)[16], const uint32_t* p, const uint32_t* q) {
  asm volatile("{\n.reg .pred p;\n.reg .b32 n,t,u;\nmov.u32 n,0;\nLW:\nld.relaxed.gpu.global.v2.u32 {%0,%1},[%20];\nld.relaxed.gpu.global.v2.u32 {%2,%3},[%20+64];\n"
               "ld.relaxed.gpu.global.v4.f32 {%4,%5,%6,%7},[%21];\nld.relaxed.gpu.global.v4.f32 {%8,%9,%10,%11},[%21+16];\n"
               "ld.relaxed.gpu.global.v4.f32 {%12,%13,%14,%15},[%21+8192];\nld.relaxed.gpu.global.v4.f32 {%16,%17,%18,%19},[%21+8208];\n"
               "lop3.b32 t,%0,%1,%2,0x80;\nlop3.b32 u,%3,%4,%5,0x80;\nlop3.b32 t,t,%6,%7,0x80;\nlop3.b32 u,u,%8,%9,0x80;\nlop3.b32 t,t,%10,%11,0x80;\n"
               "lop3.b32 u,u,%12,%13,0x80;\nlop3.b32 t,t,%14,%15,0x80;\nlop3.b32 u,u,%16,%17,0x80;\nlop3.b32 t,t,%18,%19,0x80;\nlop3.b32 t,t,u,1,0x80;\n"
               "setp.ne.u32 p,t,0;\n@p bra LD;\nadd.u32 n,n,1;\nsetp.lt.u32 p,n,1048576;\n@p bra LW;\nLD:\n}\n"
               : "=&r"(a.x), "=&r"(a.y), "=&r"(b.x), "=&r"(b.y), "=&f"(w[0]), "=&f"(w[1]), "=&f"(w[2]), "=&f"(w[3]), "=&f"(w[4]), "=&f"(w[5]), "=&f"(w[6]), "=&f"(w[7]),
                 "=&f"(w[8]), "=&f"(w[9]), "=&f"(w[10]), "=&f"(w[11]), "=&f"(w[12]), "=&f"(w[13]), "=&f"(w[14]), "=&f"(w[15]) : "l"(p), "l"(q) : "memory");
}

constexpr int LN_SMEM = 131072 + 4 * 24576 + 2816 + 256;
#define TANH 1
#define DLY 2
template <bool FFN>
__global__ void __cluster_dims__(2, 1, 1) __launch_bounds__(384, 1) k_lngemm(const __grid_constant__ CUtensorMap mX, const __grid_constant__ CUtensorMap mB0,
                                                   const __grid_constant__ CUtensorMap mB1, const bf16* __restrict__ cv, const bf16* __restrict__ wm, const bf16* __restrict__ xg, const bf16* wq) {
  extern __shared__ __align__(1024) uint8_t smem[];
  const uint32_t sA = smem_u32(smem), sB = sA + (FFN ? 81920 : 131072), sM = sA + 229376, bars = sM + 2816;
  const uint32_t bA = bars, bF = bars + 64, bE = bars + 112;
  constexpr int NB = FFN ? 6 : 4;
  const int tid = threadIdx.x, warp = tid >> 5, lane = tid & 31;
  const int pr = blockIdx.x & 1, rb = FFN ? (blockIdx.x >> 4) * 2 + pr : blockIdx.x >> 3, ct = FFN ? (blockIdx.x >> 1) & 7 : blockIdx.x & 7;
  constexpr int NST = FFN ? 16 : 8, KS = FFN ? 2 : 4, BOX = FFN ? 4096 : 8192;
  TS(FFN ? 4 : 1, 0);
  pdl_launch();
  float* red = (float*)(smem + (sM - sA));
  if (tid == 256) {
    for (int i = 0; i < 8; i++) mbar_init(bA + 8 * i, 1);
    for (int i = 0; i < NB; i++) { mbar_init(bF + 8 * i, 1); mbar_init(bE + 8 * i, FFN ? 16 : 8); }
    mbar_init(bars + 160, 1);
    fence_init();
  }
  __syncwarp();
  cluster_arrive();
  uint4 wv0, wv1, xv[4];
  bf16 cv0, cv1;
  if (!FFN && tid < 256) {
    const int r = (blockIdx.x & 3) * 128 + (tid >> 2);
    const uint4* wp = (const uint4*)(wm + r * 3072 + (blockIdx.x >> 2) * 32 + (tid & 3) * 8);
    wv0 = __ldg(wp); wv1 = __ldg(wp + 64 * 384);
    cv0 = cv[r]; cv1 = cv[r + 64];
#pragma unroll
    for (int i = 0; i < 4; i++) xv[i] = __ldg((const uint4*)(xg + (blockIdx.x * 16 + (tid >> 4)) * 512 + i * 128 + (tid & 15) * 8));
  }
  cluster_wait();
  if (warp >= 8) {
    asm volatile("setmaxnreg.dec.sync.aligned.u32 40;");
    if (tid == 256) {
      auto loadB = [&](int s) {
        const uint32_t d = sB + (s % NB) * 24576, b = bF + (s % NB) * 8;
        mbar_expect(b, 24576);
        for (int j = 0; j < 3; j++) {
          if (FFN) tma2d_mc(d + (pr * 3 + j) * BOX, pr ? &mB1 : &mB0, ct * 176 + j * 64, s * 32, b);
          else tma2d(d + j * BOX, &mB0, ct * 192 + j * 64, s * 64, b);
        }
      };
      for (int i = 0; i < 8; i++) mbar_expect(bA + 8 * i, 16384);
      if (!FFN) l2_prefetch((const char*)wq + blockIdx.x * 12288, 12288);
      int nb = 0;
      for (int s = 0; s < NB; s++, nb++) {
        const int i = s * 2 + (ct & 1);
        if (FFN && s >= PD1 && !may_preload(bF + (s - PD1) * 8, bars + 160)) break;
        if (!FFN && s == DLY) mbar_wait(bars + 160, 0);
        if (!FFN) tma2d_mc(sA + i * 16384, &mX, i * 64, rb * 128, bA + 8 * i);
        loadB(s);
      }
      if (FFN) {
        pdl_wait();
        for (int i = 0; i < 5; i++) {
          bulk_load(sA + i * 16384, g_a + (rb * 64 + i * 8) * 1024, 16384, bA + 8 * i);
          for (; nb < 2 * i + 2 && nb < NB; nb++) loadB(nb);
        }
      }
      for (int s = NB; s < NST; s++) {
        mbar_wait(bE + (s % NB) * 8, (s / NB - 1) & 1); loadB(s);
        if (FFN && s <= 10 && !(s & 1)) bulk_load(sA + (s / 2 - 3) * 16384, g_a + (rb * 64 + (s / 2 + 2) * 8) * 1024, 16384, bA + 8 * (s / 2 + 2));
      }
    }
  } else {
  asm volatile("setmaxnreg.inc.sync.aligned.u32 232;");
  const int g = lane >> 2, t = lane & 3;
  const int lr = warp * 16 + (lane & 7) + ((lane >> 3) & 1) * 8;
  auto aaddr = [&](int ks) -> uint32_t {
    if (FFN) return sA + ((ks < 20 ? ks : ks - 20) * 2 + (lane >> 4)) * 2048 + lr * 16;
    return sA + (ks >> 2) * 16384 + lr * 128 + ((((ks & 3) * 2 + (lane >> 4)) ^ (lr & 7)) << 4);
  };
  const int row0 = rb * 128 + warp * 16 + g;
  float2 msh, msc;
  float4 p0, p1, uv;
  float rs0, rs1, nm0, nm1;
  if (!FFN) {
    {
      float a[8] = {0, 0, 0, 0, 0, 0, 0, 0};
      fma8(a, silu_bf(cv0), wv0); fma8(a, silu_bf(cv1), wv1);
      red[warp * 32 + t * 8 + g] = red8(a, lane);
      asm volatile("bar.sync 1,256;" ::: "memory");
      if (tid < 32) {
        float r = 0;
#pragma unroll
        for (int i = 0; i < 8; i++) r += red[i * 32 + tid];
        asm volatile("st.relaxed.gpu.global.u32 [%0],%1;" ::"l"(g_modv + ((blockIdx.x >> 2) * 32 + tid) * 4 + (blockIdx.x & 3)), "r"(__float_as_uint(r) | 1u) : "memory");
      }
      TS(0, 1);
    }
    {
      float v[32], s = 0, q = 0;
#pragma unroll
      for (int i = 0; i < 16; i++) { const uint32_t u = ((const uint32_t*)xv)[i]; v[2 * i] = blo(u); v[2 * i + 1] = bhi(u); s += v[2 * i] + v[2 * i + 1]; }
      s = qsum(s); s += __shfl_xor_sync(~0u, s, 4); s += __shfl_xor_sync(~0u, s, 8);
      const float m = s * (1.f / 512);
#pragma unroll
      for (int i = 0; i < 32; i++) q += (v[i] - m) * (v[i] - m);
      q = qsum(q); q += __shfl_xor_sync(~0u, q, 4); q += __shfl_xor_sync(~0u, q, 8);
      const float rs = rsqrtf(q * (1.f / 512) + 1e-5f);
      if ((tid & 15) == 0)
        asm volatile("st.relaxed.gpu.global.v2.u32 [%0],{%1,%2};" ::"l"(g_modv + 4096 + (blockIdx.x * 16 + (tid >> 4)) * 2), "r"(__float_as_uint(rs) | 1u), "r"(__float_as_uint(-m * rs) | 1u) : "memory");
    }
    uint2 q0, q1;
    float w[16];
    if (tid < 128) {
      uint32_t v; int n = 0;
      do asm volatile("ld.relaxed.gpu.global.u32 %0,[%1];" : "=r"(v) : "l"(g_modv + (tid >> 2) * 128 + (tid & 3)) : "memory"); while (!(v & 1) && ++n < 1048576);
    }
    asm volatile("bar.sync 1,256;" ::: "memory");
    poll(q0, q1, w, g_modv + 4096 + row0 * 2, g_modv + tid * 8);
    msh = make_float2(mod_fin(w[0] + w[1] + w[2] + w[3], 0), mod_fin(w[4] + w[5] + w[6] + w[7], 0));
    msc = make_float2(mod_fin(w[8] + w[9] + w[10] + w[11], 512), mod_fin(w[12] + w[13] + w[14] + w[15], 512));
    asm volatile("bar.sync 1,256;" ::: "memory");
    if (tid == 32) mbar_arrive(bars + 160);
    rs0 = __uint_as_float(q0.x); nm0 = __uint_as_float(q0.y); rs1 = __uint_as_float(q1.x); nm1 = __uint_as_float(q1.y);
  } else {
    pdl_wait();
    if (tid == 32) mbar_arrive(bars + 160);
    TS(4, 1);
    p0 = *(const float4*)(g_st + row0 * 8 + t * 2); p1 = *(const float4*)(g_st + (row0 + 8) * 8 + t * 2);
    if (tid < 176) uv = *(const float4*)(g_uv + (tid >= 88 ? 1408 - 176 : 0) + ct * 176 + tid * 2);
  }
  if (!FFN) {
    uint32_t* m = (uint32_t*)(smem + (sM - sA)) + (tid >> 3) * 16 + (tid & 3) * 4 + ((tid >> 2) & 1);
    m[0] = pack_rn(msc.x, msc.y); m[2] = pack_rn(msh.x, msh.y);
    asm volatile("bar.sync 1,256;" ::: "memory");
  }
  constexpr int NA = FFN ? 88 : 96;
  float acc0[NA], acc1[FFN ? 88 : 1];
  uint32_t a[2][KS][4];
  auto prep = [&](int ks, uint32_t(&o)[4]) {
    if ((ks & 3) == 0) mbar_wait(bA + 2 * ks, 0);
    if (FFN) { ldsm4(aaddr(ks), o); return; }
    uint32_t r[4]; ldsm4(aaddr(ks), r);
    const uint4 m = *(const uint4*)(smem + (sM - sA) + ks * 64 + t * 16);
#pragma unroll
    for (int i = 0; i < 4; i++) {
      const float rs = (i & 1) ? rs1 : rs0, nm = (i & 1) ? nm1 : nm0;
      const uint32_t n = pack_rn(fmaf(blo(r[i]), rs, nm), fmaf(bhi(r[i]), rs, nm));
      asm("fma.rn.bf16x2 %0,%1,%2,%3;" : "=r"(o[i]) : "r"(n), "r"(i < 2 ? m.x : m.y), "r"(i < 2 ? m.z : m.w));
    }
  };
  auto stage = [&](int s, uint32_t(&c)[KS][4], uint32_t(&n)[KS][4]) {
    mbar_wait(bF + (s % NB) * 8, (s / NB) & 1);
    const uint64_t db = mk_desc(sB + (s % NB) * 24576, BOX, 1024, 1);
    wg_fence();
#pragma unroll
    for (int k = 0; k < KS; k++) {
      if constexpr (FFN) {
        wgmma_rs_n176_t1(acc0, c[k][0], c[k][1], c[k][2], c[k][3], db + k * 128, s + k);
        wgmma_rs_n176_t1(acc1, c[k][0], c[k][1], c[k][2], c[k][3], db + k * 128 + 3 * BOX / 16, s + k);
      } else {
        wgmma_rs_n192_t1(acc0, c[k][0], c[k][1], c[k][2], c[k][3], db + k * 128, s + k);
      }
    }
    wg_commit();
    wg_wait<1>();
    if (s > 0 && s <= NST - NB) {
      if (!FFN) { if (lane == 0) mbar_arrive(bE + ((s - 1) % NB) * 8); }
      else if (lane < 2) asm volatile("{\n.reg .b32 r;\nmapa.shared::cluster.u32 r,%0,%1;\nmbarrier.arrive.relaxed.cluster.shared::cluster.b64 _,[r];\n}" ::"r"(bE + ((s - 1) % NB) * 8), "r"(lane) : "memory");
    }
    if (s < NST - 1) {
#pragma unroll
      for (int k = 0; k < KS; k++) prep((s + 1) * KS + k, n[k]);
    }
  };
#pragma unroll
  for (int k = 0; k < KS; k++) prep(k, a[0][k]);
  TS(FFN ? 4 : 1, 2);
#pragma unroll 1
  for (int s = 0; s < NST; s += 2) { stage(s, a[0], a[1]); stage(s + 1, a[1], a[0]); }
  if (FFN) {
    if (tid < 88) { uv.x *= 0.5f; uv.y *= 0.5f; uv.z *= 0.5f; uv.w *= 0.5f; }
    if (tid < 176) *(float4*)(smem + (sM - sA) + tid * 16) = uv;
    const float m0 = qsum(p0.x + p0.z) * 0.125f, m1 = qsum(p1.x + p1.z) * 0.125f;
    const float v0 = qsum(p0.y + p0.w + 64.f * ((p0.x - m0) * (p0.x - m0) + (p0.z - m0) * (p0.z - m0)));
    const float v1 = qsum(p1.y + p1.w + 64.f * ((p1.x - m1) * (p1.x - m1) + (p1.z - m1) * (p1.z - m1)));
    rs0 = rsqrtf(v0 * (1.f / 512) + 1e-5f); rs1 = rsqrtf(v1 * (1.f / 512) + 1e-5f);
    nm0 = -m0 * rs0; nm1 = -m1 * rs1;
    asm volatile("bar.sync 1,256;" ::: "memory");
  }
  wg_wait<0>();
  reg_fence(acc0);
  TS(FFN ? 4 : 1, 3);
  if constexpr (FFN) {
    reg_fence(acc1);
    const float rh0 = 0.5f * rs0, rh1 = 0.5f * rs1;
    uint32_t* o = (uint32_t*)g_h + ((rb * 172 + ct * 22) * 128 + warp * 16 + g) * 4 + t;
#pragma unroll
    for (int j = 0; j < 22; j++) {
      {
        const float4 u1 = *(const float4*)(smem + (sM - sA) + (j * 4 + t) * 16), u3 = *(const float4*)(smem + (sM - sA) + (88 + j * 4 + t) * 16);
        float h[4];
#pragma unroll
        for (int i = 0; i < 4; i++) {
          const float rs = i < 2 ? rs0 : rs1, nm = i < 2 ? nm0 : nm1, rh = i < 2 ? rh0 : rh1;
          const float z = fmaf(rh, acc0[4 * j + i], (i & 1) ? fmaf(nm, u1.z, u1.w) : fmaf(nm, u1.x, u1.y));
          const float y = fmaf(rs, acc1[4 * j + i], (i & 1) ? fmaf(nm, u3.z, u3.w) : fmaf(nm, u3.x, u3.y));
          float th; asm("tanh.approx.f32 %0,%1;" : "=f"(th) : "f"(z));
          h[i] = fmaf(z, th, z) * y;
        }
        if (j < 18 || ct < 7) { o[j * 512] = pack_rn(h[0], h[1]); o[j * 512 + 32] = pack_rn(h[2], h[3]); }
      }
    }
  } else {
    uint32_t* o = (uint32_t*)g_qkv + (ct * 24 * 2048 + row0) * 4 + t;
#pragma unroll
    for (int j = 0; j < 24; j += 2) {
      const int G = ct * 24 + j;
      const float sc = G < 64 ? 0.25f * 1.4426950408889634f : 1.f;
      uint32_t p[4];
#pragma unroll
      for (int i = 0; i < 4; i++) p[i] = pack_rn(acc0[4 * j + 2 * i] * sc, acc0[4 * j + 2 * i + 1] * sc);
      o[j * 8192] = p[0]; o[j * 8192 + 32] = p[1]; o[(j + 1) * 8192] = p[2]; o[(j + 1) * 8192 + 32] = p[3];
      if (G >= 64 && G < 128) {
        float n0 = blo(p[0]) * blo(p[0]) + bhi(p[0]) * bhi(p[0]) + blo(p[2]) * blo(p[2]) + bhi(p[2]) * bhi(p[2]);
        float n1 = blo(p[1]) * blo(p[1]) + bhi(p[1]) * bhi(p[1]) + blo(p[3]) * blo(p[3]) + bhi(p[3]) * bhi(p[3]);
        n0 = qsum(n0); n1 = qsum(n1);
        const uint32_t mx = __reduce_max_sync(~0u, max(__float_as_uint(n0), __float_as_uint(n1)));
        if (lane == 0) g_kmax[((G - 64) >> 1) * 128 + rb * 8 + warp] = __uint_as_float(mx);
      }
    }
  }
  TS(FFN ? 4 : 1, 4);
}
}

#define SMASK 0xCCCCu
#define BRK 0
#define PACK 1
constexpr int AT_SMEM = 5 * 32768 + 256;
__device__ __forceinline__ uint32_t exp2_pair_fma(float s0, float s1, float c, uint32_t ka, uint32_t kz) {
  uint32_t r;
  asm volatile("{\n.reg .b32 y0,y1,e,u,t;\n"
      "fma.rn.sat.f32 y0,%1,0f00000080,%3;\nfma.rn.sat.f32 y1,%2,0f00000080,%3;\n"
      "mad.lo.u32 e,y1,65536,y0;\n"
      "and.b32 u,e,0x007F007F;\n"
      "fma.rn.f16x2 u,u,%4,%5;\nfma.rn.f16x2 t,u,u,%6;\nfma.rn.f16x2 t,t,u,%7;\n"
      "lop3.b32 %0,t,0x007F007F,e,0xE2;\n}\n"
      : "=r"(r) : "f"(s0), "f"(s1), "f"(c), "r"(ka), "r"(0x36B236B2u), "r"(0x3C733C73u), "r"(0x47764776u), "r"(kz));
  return r;
}
__device__ __forceinline__ void attn_pass(float (&oa)[12], float (&ob)[12], const uint32_t (&q)[4], float m0, float m1, uint32_t sK, uint32_t bars, bool first, uint32_t kz) {
  uint64_t dk = mk_desc(sK, 32768, 128, 0), dv = mk_desc(sK + 65536, 128, 32768, 0);
  const float c0 = (127.f - m0) * __uint_as_float(0x80u), c1 = (127.f - m1) * __uint_as_float(0x80u);
  uint32_t ka;
  asm volatile("mov.b32 %0,0x7ACE7ACE;" : "=r"(ka));
  constexpr int NK = 64, NS = 32, NP = 16;
  auto qk = [&](float (&s)[NS], int i) { wgmma_rs_n64_t0(s, q[0], q[1], q[2], q[3], dk + i * NK, 0); };
  auto softmax = [&](float (&s)[NS], uint32_t (&p)[NP], uint32_t mask) {
    reg_fence(s);
    float e0, e1;
    int pend = -1;
#pragma unroll
    for (int t = 0; t < NP; t++) {
      const int j = (t & 3) * 4 + (t >> 2);
      if ((mask >> (t & 3)) & 1) {
        p[j] = exp2_pair_fma(s[2 * j], s[2 * j + 1], (j & 1) ? c1 : c0, ka, kz);
      } else {
        float f0, f1;
        asm volatile("ex2.approx.ftz.f32 %0,%2;\nex2.approx.ftz.f32 %1,%3;" : "=&f"(f0), "=f"(f1) : "f"(s[2 * j]), "f"(s[2 * j + 1]));
        if (pend >= 0) asm volatile("cvt.rn.bf16x2.f32 %0,%1,%2;" : "=r"(p[pend]) : "f"(e1), "f"(e0));
        e0 = f0; e1 = f1; pend = j;
      }
    }
    if (pend >= 0) asm volatile("cvt.rn.bf16x2.f32 %0,%1,%2;" : "=r"(p[pend]) : "f"(e1), "f"(e0));
#pragma unroll
    for (int j = 0; j < NP; j++) asm volatile("" : "+r"(p[j])::"memory");
  };
  auto pv = [&](uint32_t (&p)[NP], int i, uint32_t mask) {
#pragma unroll
    for (int k = 0; k < 4; k++) wgmma_rs_n24_t1(((mask >> k) & 1) ? ob : oa, p[4 * k], p[4 * k + 1], p[4 * k + 2], p[4 * k + 3], dv + i * NK + k * 16, 1);
  };
  constexpr uint32_t M0 = SMASK & 15, M1 = (SMASK >> 4) & 15, M2 = (SMASK >> 8) & 15, M3 = SMASK >> 12;
  zero(oa); zero(ob);
  mbar_wait(bars, 0);
  if (first) TS(2, 2);
  float s[NS];
  zero(s);
  uint32_t p0[NP], p1[NP];
  auto step = [&](int i, uint32_t (&pa)[NP], uint32_t ma, uint32_t (&pb)[NP], uint32_t mb) {
    wg_fence(); qk(s, i + 1); wg_commit(); pv(pa, i, ma); wg_commit(); wg_wait<1>(); softmax(s, pb, mb); wg_wait<0>();
  };
  wg_fence(); qk(s, 0); wg_commit(); wg_wait<0>(); softmax(s, p0, M0);
#pragma unroll 1
  for (uint32_t b = bars + 8; b < bars + 64; b += 8) {
    step(0, p0, M0, p1, M1); step(1, p1, M1, p0, M2); step(2, p0, M2, p1, M3);
    mbar_wait(b, 0);
    step(3, p1, M3, p0, M0);
    dk += 4 * NK; dv += 4 * NK;
  }
  step(0, p0, M0, p1, M1); step(1, p1, M1, p0, M2); step(2, p0, M2, p1, M3);
  wg_fence(); pv(p1, 3, M3); wg_commit();
  wg_wait<0>();
  reg_fence(oa); reg_fence(ob);
}
__device__ __forceinline__ void mma16816(float (&d)[4], const uint32_t (&a)[4], uint32_t b0, uint32_t b1) {
  asm("mma.sync.aligned.m16n8k16.row.col.f32.bf16.bf16.f32 {%0,%1,%2,%3},{%4,%5,%6,%7},{%8,%9},{%0,%1,%2,%3};"
      : "+f"(d[0]), "+f"(d[1]), "+f"(d[2]), "+f"(d[3]) : "r"(a[0]), "r"(a[1]), "r"(a[2]), "r"(a[3]), "r"(b0), "r"(b1));
}
__device__ __forceinline__ void attn_safe(float (&o)[12], const uint32_t (&q)[4], uint32_t sK) {
  const int lane = threadIdx.x & 31;
  const uint32_t ka = sK + (lane >> 4) * 32768 + (lane & 15) * 16;
  float m0 = -INFINITY, m1 = -INFINITY;
#pragma unroll 2
  for (int i = 0; i < 128; i++) {
    uint32_t k[4]; ldsm4(ka + i * 256, k);
    float s0[4] = {0, 0, 0, 0}, s1[4] = {0, 0, 0, 0};
    mma16816(s0, q, k[0], k[2]); mma16816(s1, q, k[1], k[3]);
    m0 = fmaxf(fmaxf(m0, fmaxf(s0[0], s0[1])), fmaxf(s1[0], s1[1])); m1 = fmaxf(fmaxf(m1, fmaxf(s0[2], s0[3])), fmaxf(s1[2], s1[3]));
  }
  m0 = fmaxf(m0, __shfl_xor_sync(~0u, m0, 1)); m0 = fmaxf(m0, __shfl_xor_sync(~0u, m0, 2));
  m1 = fmaxf(m1, __shfl_xor_sync(~0u, m1, 1)); m1 = fmaxf(m1, __shfl_xor_sync(~0u, m1, 2));
  float o0[4] = {0, 0, 0, 0}, o1[4] = {0, 0, 0, 0}, o2[4] = {0, 0, 0, 0};
#pragma unroll 2
  for (int i = 0; i < 128; i++) {
    uint32_t k[4], v[4]; ldsm4(ka + i * 256, k);
    asm volatile("ldmatrix.sync.aligned.m8n8.x4.trans.shared.b16 {%0,%1,%2,%3},[%4];" : "=r"(v[0]), "=r"(v[1]), "=r"(v[2]), "=r"(v[3]) : "r"(ka + 65536 + i * 256) : "memory");
    float s0[4] = {0, 0, 0, 0}, s1[4] = {0, 0, 0, 0};
    mma16816(s0, q, k[0], k[2]); mma16816(s1, q, k[1], k[3]);
    const uint32_t p[4] = {pack_rn(ex2(s0[0] - m0), ex2(s0[1] - m0)), pack_rn(ex2(s0[2] - m1), ex2(s0[3] - m1)),
                           pack_rn(ex2(s1[0] - m0), ex2(s1[1] - m0)), pack_rn(ex2(s1[2] - m1), ex2(s1[3] - m1))};
    mma16816(o0, p, v[0], v[1]); mma16816(o1, p, v[2], v[3]); mma16816(o2, p, 0x3F803F80u, 0x3F803F80u);
  }
#pragma unroll
  for (int i = 0; i < 4; i++) { o[i] = o0[i]; o[4 + i] = o1[i]; o[8 + i] = o2[i]; }
}
__global__ void __cluster_dims__(2, 1, 1) __launch_bounds__(512, 1) k_attn(const bf16* wo, const bf16* w1, const bf16* w3, const bf16* w2, const bf16* __restrict__ cv, const bf16* __restrict__ wm, uint32_t kz) {
  extern __shared__ __align__(1024) uint8_t smem[];
  const uint32_t sK = smem_u32(smem), bars = sK + 5 * 32768;
  const int tid = threadIdx.x, warp = tid >> 5, lane = tid & 31, g = lane >> 2, t = lane & 3;
  pdl_launch();
  if (blockIdx.x < 4) {
    float* cs = (float*)smem;
    cs[tid] = silu_bf(cv[tid]);
    cluster_sync();
    const int b = blockIdx.x;
    float *mv = cs + 512, *rd = cs + 1536;
    auto put8 = [&](float* d, float (&a)[8]) { ((float4*)d)[0] = make_float4(a[0], a[1], a[2], a[3]); ((float4*)d)[1] = make_float4(a[4], a[5], a[6], a[7]); };
    for (int ph = 0; ph < 2; ph++) {
      const int nc = 512 >> ph, n0 = ph ? (b >> 1) * 1536 + 1024 + (b & 1) * 256 : 1536 + (b & 1) * 512, nr = 64 >> ph, r0 = tid / nr * nr;
      float a[8] = {0, 0, 0, 0, 0, 0, 0, 0};
#pragma unroll 16
      for (int r = r0; r < r0 + nr; r++) fma8(a, cs[r], __ldg((const uint4*)(wm + r * 3072 + n0 + (tid & (nr - 1)) * 8)));
      put8(rd + tid * 8, a);
      __syncthreads();
      if (tid < nc) {
        float s = 0;
        for (int i = tid; i < 4096; i += nc) s += rd[i];
        s = mod_fin(s, n0 + tid);
        if (ph || b < 2) g_mod[n0 + tid] = s;
        if (!ph) {
          mv[(b & 1) * 512 + tid] = s;
          asm volatile("{\n.reg .b32 r;\nmapa.shared::cluster.u32 r,%0,%1;\nst.shared::cluster.f32 [r],%2;\n}" ::"r"(smem_u32(mv + (b & 1) * 512 + tid)), "r"((b & 1) ^ 1), "f"(s) : "memory");
        }
      }
      cluster_sync();
    }
    if (tid < 430) {
      const bf16* w = (b >> 1 ? w3 : w1) + (b & 1) * 688 + tid % 86 * 8;
      float u[8] = {0, 0, 0, 0, 0, 0, 0, 0}, v[8] = {0, 0, 0, 0, 0, 0, 0, 0};
#pragma unroll 13
      for (int r = tid / 86; r < 512; r += 5) { const uint4 x = __ldg((const uint4*)(w + r * 1376)); fma8(u, mv[512 + r], x); fma8(v, mv[r], x); }
      put8(rd + tid * 8, u); put8(rd + 3440 + tid * 8, v);
    }
    __syncthreads();
    for (int n = tid; n < 688; n += 512) {
      float u = 0, v = 0;
      for (int i = n; i < 3440; i += 688) { u += rd[i]; v += rd[3440 + i]; }
      g_uv[(b >> 1) * 1408 + (b & 1) * 688 + n] = make_float2(u, v);
    }
    TS(0, 7);
    return;
  }
  const int bid = blockIdx.x - 4, h = bid >> 2, qb = bid & 3;
  TS(2, 0);
  if (tid == 0) { for (int i = 0; i < 8; i++) { mbar_init(bars + 8 * i, 1); mbar_expect(bars + 8 * i, 16384); } fence_init(); }
#pragma unroll
  for (int i = 0; i < 4; i++) *(uint4*)(smem + 131072 + i * 8192 + tid * 16) = make_uint4(0x3F803F80u, 0x3F803F80u, 0x3F803F80u, 0x3F803F80u);
  fence_async();
  cluster_sync();
  pdl_wait();
  TS(2, 1);
  if (tid >= 448) g_modv[bid * 64 + tid - 448] = 0;
  const uint4 km4 = *(const uint4*)(g_kmax + h * 128 + lane * 4);
  const uint32_t* qp = (const uint32_t*)g_qkv + (h * 2 * 2048 + qb * 512 + warp * 16 + g) * 4 + t;
  uint32_t q[4] = {qp[0], qp[32], qp[8192], qp[8192 + 32]};
  auto ldkv = [&]() {
    const int c = warp >> 1, pl = (qb & 1) + (warp & 1) * 2;
    bulk_load_mc(sK + pl * 32768 + c * 4096, g_qkv + ((64 + (pl >> 1) * 64 + h * 2 + (pl & 1)) * 2048 + c * 256) * 8, 4096, bars + 8 * c);
  };
  if (lane == 0 && warp < 4) ldkv();
  const uint32_t qn[4] = {qp[1024], qp[1024 + 32], qp[1024 + 8192], qp[1024 + 8192 + 32]};
  const float kmax = __uint_as_float(__reduce_max_sync(~0u, max(max(km4.x, km4.y), max(km4.z, km4.w))));
  if (lane == 0 && warp >= 4 && kmax != -1.f) ldkv();
#pragma unroll 1
  for (int tile = 0; tile < 2; tile++) {
    const int row = qb * 512 + tile * 256 + warp * 16 + g;
    const float n0 = qsum(blo(q[0]) * blo(q[0]) + bhi(q[0]) * bhi(q[0]) + blo(q[2]) * blo(q[2]) + bhi(q[2]) * bhi(q[2]));
    const float n1 = qsum(blo(q[1]) * blo(q[1]) + bhi(q[1]) * bhi(q[1]) + blo(q[3]) * blo(q[3]) + bhi(q[3]) * bhi(q[3]));
    const float b0 = sqrtf(n0 * kmax) * 1.001f, b1 = sqrtf(n1 * kmax) * 1.001f;
    const float m0 = fmaxf(ceilf(b0 - 100.f), 0.f), m1 = fmaxf(ceilf(b1 - 100.f), 0.f);
    float o[12], ob[12];
    attn_pass(o, ob, q, m0, m1, sK, bars, tile == 0, kz);
    const float f0 = ex2(-m0), f1 = ex2(-m1);
#pragma unroll
    for (int i = 0; i < 12; i++) o[i] = fmaf(o[i], (i & 2) ? f1 : f0, ob[i]);
    bool ok = b0 < 220.f && b1 < 220.f && o[8] >= 0x1p-90f && o[10] >= 0x1p-90f;
#pragma unroll
    for (int i = 0; i < 12; i++) ok = ok && fabsf(o[i]) < INFINITY;
    if (!__all_sync(~0u, ok)) attn_safe(o, q, sK);
    const float r0 = 1.f / o[8], r1 = 1.f / o[10];
    uint32_t* op = (uint32_t*)g_o + (((row >> 6) * 64 + h * 2) * 64 + (row & 63)) * 4 + t;
    op[0] = pack_rn(o[0] * r0, o[1] * r0); op[32] = pack_rn(o[2] * r1, o[3] * r1);
    op[256] = pack_rn(o[4] * r0, o[5] * r0); op[256 + 32] = pack_rn(o[6] * r1, o[7] * r1);
    if (tile == 0 && tid == 32) {
      l2_prefetch((const char*)wo + bid * 4096, 4096);
      l2_prefetch((const char*)w1 + bid * 11008, 11008);
      l2_prefetch((const char*)w3 + bid * 11008, 11008);
      l2_prefetch((const char*)w2 + bid * 11008, 11008);
    }
#pragma unroll
    for (int i = 0; i < 4; i++) q[i] = qn[i];
    TS(2, 3 + tile);
  }
}

constexpr int WO_SMEM = 131072 + 65536 + 256;
__global__ void __cluster_dims__(2, 1, 1) __launch_bounds__(288, 1) k_wo(const __grid_constant__ CUtensorMap mW, const bf16* __restrict__ x) {
  extern __shared__ __align__(1024) uint8_t smem[];
  const uint32_t sA = smem_u32(smem), sB = sA + 65536, bars = sB + 131072;
  const int tid = threadIdx.x, warp = tid >> 5, lane = tid & 31, g = lane >> 2, t = lane & 3;
  const int rb = blockIdx.x >> 3, ct = (blockIdx.x & 3) * 2 + ((warp >> 2) & 1);
  TS(3, 0);
  pdl_launch();
  auto loadB = [&](int i) { for (int j = 0; j < 2; j++) tma2d(sB + (j * 8 + i) * 8192, &mW, (ct + j) * 64, i * 64, bars + 64 + 8 * i); };
  int nb = 0;
  if (tid == 256) {
    for (int i = 0; i < 17; i++) mbar_init(bars + 8 * i, 1);
    fence_init();
    for (int i = 0; i < 16; i++) mbar_expect(bars + 8 * i, i < 8 ? 8192 : 16384);
    for (; nb < PD0; nb++) loadB(nb);
  }
  __syncwarp();
  cluster_arrive();
  if (warp == 8) {
    cluster_wait();
    if (lane == 0) {
      for (; nb < 8 && may_preload(bars + 64 + 8 * (nb - PD0), bars + 128); nb++) loadB(nb);
      pdl_wait();
      for (int i = blockIdx.x & 1; i < 8; i += 2) {
        bulk_load_mc(sA + i * 8192, g_o + ((blockIdx.x >> 2) * 64 + i * 8) * 512, 8192, bars + 8 * i);
        for (; nb <= (i | 1); nb++) loadB(nb);
      }
    }
    __syncwarp();
    return;
  }
  const int lrow = (blockIdx.x & 4) * 16 + (warp & 3) * 16 + g;
  uint32_t xr[16];
  const uint32_t* xp = (const uint32_t*)(x + (rb * 128 + lrow) * 512 + ct * 64) + t;
#pragma unroll
  for (int j = 0; j < 8; j++) { xr[2 * j] = __ldg(xp + j * 4); xr[2 * j + 1] = __ldg(xp + j * 4 + 8 * 256); }
  cluster_wait();
  pdl_wait();
  if (tid == 32) mbar_arrive(bars + 128);
  TS(3, 1);
  float2 ga[8];
  uint32_t sc[8];
#pragma unroll
  for (int j = 0; j < 8; j++) {
    ga[j] = *(const float2*)(g_mod + 1024 + ct * 64 + j * 8 + t * 2);
    const float2 v = *(const float2*)(g_mod + 2048 + ct * 64 + j * 8 + t * 2);
    sc[j] = pack_rn(v.x, v.y);
  }
  float acc[32];
  const uint64_t da = mk_desc(sA, 1024, 128, 0), db = mk_desc(sB + (warp >> 2) * 65536, 8192, 1024, 1);
#pragma unroll
  for (int c = 0; c < 8; c++) {
    mbar_wait(bars + 64 + 8 * c, 0); mbar_wait(bars + 8 * c, 0);
    if (c == 0) TS(3, 2);
    wg_fence();
#pragma unroll
    for (int k = 0; k < 4; k++) wgmma_ss_n64_t1(acc, da + (c * 4 + k) * 128, db + (c * 4 + k) * 128, c + k);
    wg_commit();
  }
  wg_wait<0>();
  reg_fence(acc);
  TS(3, 3);
  uint32_t* o = (uint32_t*)g_x1 + ((rb * 64 + ct * 8) * 128 + lrow) * 4 + t;
  uint32_t* oa = (uint32_t*)g_a + ((rb * 64 + ct * 8) * 128 + lrow) * 4 + t;
  float s0 = 0, s1 = 0;
#pragma unroll
  for (int j = 0; j < 8; j++) {
    xr[2 * j] = pack_rn(fmaf(ga[j].x, acc[4 * j], blo(xr[2 * j])), fmaf(ga[j].y, acc[4 * j + 1], bhi(xr[2 * j])));
    xr[2 * j + 1] = pack_rn(fmaf(ga[j].x, acc[4 * j + 2], blo(xr[2 * j + 1])), fmaf(ga[j].y, acc[4 * j + 3], bhi(xr[2 * j + 1])));
    uint32_t a0, a1;
    asm("mul.rn.bf16x2 %0,%1,%2;" : "=r"(a0) : "r"(xr[2 * j]), "r"(sc[j]));
    asm("mul.rn.bf16x2 %0,%1,%2;" : "=r"(a1) : "r"(xr[2 * j + 1]), "r"(sc[j]));
    oa[j * 512] = a0; oa[j * 512 + 32] = a1;
    o[j * 512] = xr[2 * j]; o[j * 512 + 32] = xr[2 * j + 1];
    s0 += blo(xr[2 * j]) + bhi(xr[2 * j]); s1 += blo(xr[2 * j + 1]) + bhi(xr[2 * j + 1]);
  }
  const float m0 = qsum(s0) * (1.f / 64), m1 = qsum(s1) * (1.f / 64);
  float v0 = 0, v1 = 0;
#pragma unroll
  for (int j = 0; j < 8; j++) {
    float d;
    d = blo(xr[2 * j]) - m0; v0 += d * d; d = bhi(xr[2 * j]) - m0; v0 += d * d;
    d = blo(xr[2 * j + 1]) - m1; v1 += d * d; d = bhi(xr[2 * j + 1]) - m1; v1 += d * d;
  }
  v0 = qsum(v0); v1 = qsum(v1);
  if (t == 0) g_st[(rb * 128 + lrow) * 8 + ct] = make_float2(m0, v0);
  if (t == 1) g_st[(rb * 128 + lrow + 8) * 8 + ct] = make_float2(m1, v1);
  TS(3, 4);
}

constexpr int W2_SMEM = 6 * 32768 + 32768 + 256;
__global__ void __cluster_dims__(2, 1, 1) __launch_bounds__(288, 1) k_w2(const __grid_constant__ CUtensorMap mW, bf16* __restrict__ out) {
  extern __shared__ __align__(1024) uint8_t smem[];
  const uint32_t sR = smem_u32(smem), sX = sR + 6 * 32768, bF = sX + 32768, bE = bF + 48, bX = bF + 96, bB = bF + 160, bG = bF + 208;
  const int tid = threadIdx.x, warp = tid >> 5, lane = tid & 31, g = lane >> 2, t = lane & 3;
  const int kh = blockIdx.x & 1, ct = (blockIdx.x >> 1) & 3, rb = blockIdx.x >> 3;
  TS(5, 0);
  pdl_launch();
  if (tid == 256) {
    for (int i = 0; i < 6; i++) { mbar_init(bF + 8 * i, 1); mbar_init(bE + 8 * i, 8); mbar_init(bB + 8 * i, 1); }
    mbar_init(bG, 1);
    for (int i = 0; i < 8; i++) { mbar_init(bX + 8 * i, 1); mbar_expect(bX + 8 * i, 4096); }
    fence_init();
  }
  __syncthreads();
  asm volatile("barrier.cluster.arrive.relaxed.aligned;" ::: "memory");
  if (warp == 8) {
    if (lane == 0) {
      auto abytes = [&](int s) { return (kh == 1 && s == 10) ? 8192 : 16384; };
      auto loadB = [&](int s) {
        const int st = s % 6;
        mbar_expect(bB + 8 * st, 16384);
        for (int j = 0; j < 2; j++) tma2d(sR + st * 32768 + 16384 + j * 8192, &mW, ct * 128 + j * 64, kh * 704 + s * 64, bB + 8 * st);
      };
      auto loadA = [&](int s) { mbar_expect(bF + 8 * (s % 6), abytes(s)); bulk_load(sR + (s % 6) * 32768, g_h + (rb * 172 + kh * 88 + s * 8) * 1024, abytes(s), bF + 8 * (s % 6)); };
      int nb = 0;
      for (; nb < 6 && (nb < PD2 || may_preload(bB + 8 * (nb - PD2), bG)); nb++) loadB(nb);
      pdl_wait();
      for (int s = 0; s < 6; s++) { loadA(s); if (s >= nb) loadB(s); }
      for (int s = 6; s < 11; s++) { mbar_wait(bE + 8 * (s - 6), 0); loadB(s); loadA(s); }
    }
    __syncwarp();
    cluster_wait();
    return;
  }
  pdl_wait();
  if (tid == 32) mbar_arrive(bG);
  TS(5, 1);
  const int lrow = warp * 16 + g;
  uint32_t xr[16];
  float2 gb[8];
  const uint32_t* xp = (const uint32_t*)g_x1 + ((rb * 64 + ct * 16 + kh * 8) * 128 + lrow) * 4 + t;
#pragma unroll
  for (int j = 0; j < 8; j++) {
    xr[2 * j] = xp[j * 512]; xr[2 * j + 1] = xp[j * 512 + 32];
    gb[j] = *(const float2*)(g_mod + 2560 + ct * 128 + kh * 64 + j * 8 + t * 2);
  }
  float acc[64];
#pragma unroll 1
  for (int s = 0; s < 11; s++) {
    const int st = s % 6;
    mbar_wait(bB + 8 * st, s >= 6); mbar_wait(bF + 8 * st, s >= 6);
    const uint64_t da = mk_desc(sR + st * 32768 + (warp >> 2) * 1024, 2048, 128, 0), db = mk_desc(sR + st * 32768 + 16384, 8192, 1024, 1);
    if (s == 0) TS(5, 2);
    wg_fence();
    wgmma_ss_n128_t1(acc, da, db, s);
    wgmma_ss_n128_t1(acc, da + 256, db + 128, 1);
    wgmma_ss_n128_t1(acc, da + 512, db + 256, 1);
    wgmma_ss_n128_t1(acc, da + 768, db + 384, 1);
    wg_commit();
    wg_wait<1>();
    if (s > 0 && s < 6 && lane == 0) mbar_arrive(bE + 8 * (s - 1));
  }
  wg_wait<0>();
  reg_fence(acc);
  TS(5, 3);
  asm volatile("barrier.cluster.wait.aligned;" ::: "memory");
  uint32_t rem, rbar;
  asm("mapa.shared::cluster.u32 %0,%1,%2;" : "=r"(rbar) : "r"(bX + warp * 8), "r"(kh ^ 1));
  asm("mapa.shared::cluster.u32 %0,%1,%2;" : "=r"(rem) : "r"(sX + warp * 4096 + lane * 16), "r"(kh ^ 1));
#pragma unroll
  for (int j = 0; j < 8; j++) {
    float v[4];
#pragma unroll
    for (int i = 0; i < 4; i++) { v[i] = kh ? acc[4 * j + i] : acc[32 + 4 * j + i]; acc[4 * j + i] = kh ? acc[32 + 4 * j + i] : acc[4 * j + i]; }
    asm volatile("st.async.weak.shared::cluster.mbarrier::complete_tx::bytes.v4.f32 [%0],{%1,%2,%3,%4},[%5];" ::"r"(rem + j * 512), "f"(v[0]), "f"(v[1]), "f"(v[2]), "f"(v[3]), "r"(rbar) : "memory");
  }
  mbar_wait(bX + warp * 8, 0);
  TS(5, 5);
  const uint32_t sw = sX + warp * 4096;
#pragma unroll
  for (int j = 0; j < 8; j++) {
    const float4 p = *(const float4*)(smem + 6 * 32768 + warp * 4096 + j * 512 + lane * 16);
    xr[2 * j] = pack_rn(fmaf(gb[j].x, acc[4 * j] + p.x, blo(xr[2 * j])), fmaf(gb[j].y, acc[4 * j + 1] + p.y, bhi(xr[2 * j])));
    xr[2 * j + 1] = pack_rn(fmaf(gb[j].x, acc[4 * j + 2] + p.z, blo(xr[2 * j + 1])), fmaf(gb[j].y, acc[4 * j + 3] + p.w, bhi(xr[2 * j + 1])));
  }
  __syncwarp();
#pragma unroll
  for (int j = 1; j < 8; j += 2) {
    asm volatile("stmatrix.sync.aligned.m8n8.x4.shared.b16 [%0],{%1,%2,%3,%4};" ::"r"(sw + (lane & 15) * 128 + (((j - 1 + (lane >> 4)) ^ (lane & 7)) << 4)),
                            "r"(xr[2 * j - 2]), "r"(xr[2 * j - 1]), "r"(xr[2 * j]), "r"(xr[2 * j + 1]) : "memory");
  }
  __syncwarp();
#pragma unroll
  for (int i = 0; i < 4; i++) {
    const int r = i * 4 + (lane >> 3);
    *(uint4*)(out + (rb * 128 + warp * 16 + r) * 512 + ct * 128 + kh * 64 + (lane & 7) * 8) = *(const uint4*)(smem + 6 * 32768 + warp * 4096 + r * 128 + (((lane ^ r) & 7) << 4));
  }
  TS(5, 4);
}

typedef CUresult (*EncFn)(CUtensorMap*, CUtensorMapDataType, cuuint32_t, void*, const cuuint64_t*, const cuuint64_t*, const cuuint32_t*,
                          const cuuint32_t*, CUtensorMapInterleave, CUtensorMapSwizzle, CUtensorMapL2promotion, CUtensorMapFloatOOBfill);
static void mk_map(EncFn f, CUtensorMap* m, const void* p, int rows, int cols, int box_rows) {
  cuuint64_t dim[2] = {(cuuint64_t)cols, (cuuint64_t)rows}, str[1] = {(cuuint64_t)cols * 2};
  cuuint32_t box[2] = {64, (cuuint32_t)box_rows}, es[2] = {1, 1};
  f(m, CU_TENSOR_MAP_DATA_TYPE_BFLOAT16, 2, (void*)p, dim, str, box, es, CU_TENSOR_MAP_INTERLEAVE_NONE, CU_TENSOR_MAP_SWIZZLE_128B,
    CU_TENSOR_MAP_L2_PROMOTION_L2_128B, CU_TENSOR_MAP_FLOAT_OOB_FILL_NONE);
}
template <typename... KA, typename... A>
static void launch(void (*k)(KA...), int grid, int block, int smem, bool pdl, A... args) {
  cudaLaunchConfig_t cfg = {};
  cfg.gridDim = dim3(grid); cfg.blockDim = dim3(block); cfg.dynamicSmemBytes = smem; cfg.stream = cudaStreamPerThread;
  cudaLaunchAttribute at[1];
  at[0].id = cudaLaunchAttributeProgrammaticStreamSerialization; at[0].val.programmaticStreamSerializationAllowed = 1;
  cfg.attrs = at; cfg.numAttrs = pdl ? 1 : 0;
  cudaLaunchKernelEx(&cfg, k, args...);
}
extern "C" void kernel_launch(void* const* d_in, const int* in_sizes, int n_in, void* d_out, int out_size) {
  const bf16 *x = (const bf16*)d_in[0], *wqkv = (const bf16*)d_in[1], *wo = (const bf16*)d_in[2], *w1 = (const bf16*)d_in[4],
             *w3 = (const bf16*)d_in[5], *w2 = (const bf16*)d_in[6], *c = (const bf16*)d_in[7], *wmod = (const bf16*)d_in[8];
  void* fp = nullptr;
  cudaDriverEntryPointQueryResult qr;
  cudaGetDriverEntryPoint("cuTensorMapEncodeTiled", &fp, cudaEnableDefault, &qr);
  EncFn f = (EncFn)fp;
  CUtensorMap mX, mQ, mO, m1, m3, m2;
  mk_map(f, &mX, x, S_, D_, 128); mk_map(f, &mQ, wqkv, D_, 3 * D_, 64); mk_map(f, &mO, wo, D_, D_, 64);
  mk_map(f, &m1, w1, D_, F_, 32); mk_map(f, &m3, w3, D_, F_, 32); mk_map(f, &m2, w2, F_, D_, 64);
  cudaFuncSetAttribute(k_lngemm<false>, cudaFuncAttributeMaxDynamicSharedMemorySize, LN_SMEM);
  cudaFuncSetAttribute(k_lngemm<true>, cudaFuncAttributeMaxDynamicSharedMemorySize, LN_SMEM);
  cudaFuncSetAttribute(k_attn, cudaFuncAttributeMaxDynamicSharedMemorySize, AT_SMEM);
  cudaFuncSetAttribute(k_wo, cudaFuncAttributeMaxDynamicSharedMemorySize, WO_SMEM);
  cudaFuncSetAttribute(k_w2, cudaFuncAttributeMaxDynamicSharedMemorySize, W2_SMEM);
  launch(k_lngemm<false>, 128, 384, LN_SMEM, false, mX, mQ, mQ, c, wmod, x, wqkv);
  launch(k_attn, 132, 512, AT_SMEM, true, wo, w1, w3, w2, c, wmod, 0u);
  launch(k_wo, 128, 288, WO_SMEM, true, mO, x);
  launch(k_lngemm<true>, 128, 384, LN_SMEM, true, mX, m1, m3, c, wmod, x, wqkv);
  launch(k_w2, 128, 288, W2_SMEM, true, m2, (bf16*)d_out);
}
```

```cpp
#include <cuda_runtime.h>
#include <cuda_bf16.h>
#include <cuda.h>
#include <stdint.h>
typedef __nv_bfloat16 bf16;
constexpr int S_ = 2048, D_ = 512, F_ = 1376;
__device__ __align__(1024) float g_mod[3072];
__device__ __align__(1024) uint32_t g_modv[4096 + 4096];
__device__ __align__(1024) bf16 g_qkv[192 * 2048 * 8];
__device__ __align__(1024) float g_kmax[32 * 128];
__device__ __align__(1024) bf16 g_o[16 * 64 * 128 * 8];
__device__ __align__(1024) bf16 g_x1[16 * 64 * 128 * 8];
__device__ __align__(1024) bf16 g_a[16 * 64 * 128 * 8];
__device__ __align__(1024) float2 g_uv[2 * 1408];
__device__ __align__(1024) float2 g_st[2048 * 8];
__device__ __align__(1024) bf16 g_h[16 * 172 * 128 * 8];

__device__ __forceinline__ uint32_t smem_u32(const void* p) { return (uint32_t)__cvta_generic_to_shared(p); }
__device__ __forceinline__ void mbar_init(uint32_t b, int n) { asm volatile("mbarrier.init.shared::cta.b64 [%0],%1;" ::"r"(b), "r"(n) : "memory"); }
__device__ __forceinline__ void mbar_expect(uint32_t b, int bytes) { asm volatile("mbarrier.arrive.expect_tx.shared::cta.b64 _,[%0],%1;" ::"r"(b), "r"(bytes) : "memory"); }
__device__ __forceinline__ void mbar_arrive(uint32_t b) { asm volatile("mbarrier.arrive.shared::cta.b64 _,[%0];" ::"r"(b) : "memory"); }
__device__ __forceinline__ void mbar_wait(uint32_t b, int parity) {
  asm volatile("{\n.reg .pred p;\n.reg .u32 n;\nmov.u32 n,0;\nLW:\nmbarrier.try_wait.parity.shared::cta.b64 p,[%0],%1;\n@p bra LD;\n"
               "add.u32 n,n,1;\nsetp.lt.u32 p,n,4194304;\n@p bra LW;\nLD:\n}\n" ::"r"(b), "r"(parity) : "memory");
}
__device__ __forceinline__ void fence_init() { asm volatile("fence.mbarrier_init.release.cluster;" ::: "memory"); }
__device__ __forceinline__ void fence_async() { asm volatile("fence.proxy.async.shared::cta;" ::: "memory"); }
__device__ __forceinline__ void bulk_load(uint32_t dst, const void* src, int bytes, uint32_t bar) {
  asm volatile("cp.async.bulk.shared::cluster.global.mbarrier::complete_tx::bytes [%0],[%1],%2,[%3];" ::"r"(dst), "l"(src), "r"(bytes), "r"(bar) : "memory");
}
__device__ __forceinline__ void tma2d(uint32_t dst, const CUtensorMap* m, int c0, int c1, uint32_t bar) {
  asm volatile("cp.async.bulk.tensor.2d.shared::cluster.global.mbarrier::complete_tx::bytes [%0],[%1,{%3,%4}],[%2];" ::"r"(dst), "l"(m), "r"(bar), "r"(c0), "r"(c1) : "memory");
}
__device__ __forceinline__ void bulk_load_mc(uint32_t dst, const void* src, int bytes, uint32_t bar) {
  asm volatile("cp.async.bulk.shared::cluster.global.mbarrier::complete_tx::bytes.multicast::cluster [%0],[%1],%2,[%3],%4;" ::"r"(dst), "l"(src), "r"(bytes), "r"(bar), "h"((uint16_t)3) : "memory");
}
__device__ __forceinline__ void tma2d_mc(uint32_t dst, const CUtensorMap* m, int c0, int c1, uint32_t bar) {
  asm volatile("cp.async.bulk.tensor.2d.shared::cluster.global.mbarrier::complete_tx::bytes.multicast::cluster [%0],[%1,{%3,%4}],[%2],%5;" ::"r"(dst), "l"(m), "r"(bar), "r"(c0), "r"(c1), "h"((uint16_t)3) : "memory");
}
__device__ __forceinline__ void cluster_arrive() { asm volatile("barrier.cluster.arrive.relaxed.aligned;" ::: "memory"); }
__device__ __forceinline__ void cluster_wait() { asm volatile("barrier.cluster.wait.aligned;" ::: "memory"); }
__device__ __forceinline__ void cluster_sync() { asm volatile("barrier.cluster.arrive.release.aligned;\nbarrier.cluster.wait.acquire.aligned;" ::: "memory"); }
__device__ __forceinline__ bool mbar_test(uint32_t b, uint32_t ph) {
  uint32_t ok; asm volatile("{\n.reg .pred p;\nmbarrier.test_wait.parity.shared::cta.b64 p,[%1],%2;\nselp.u32 %0,1,0,p;\n}" : "=r"(ok) : "r"(b), "r"(ph) : "memory"); return ok;
}
__device__ __forceinline__ bool may_preload(uint32_t landed, uint32_t go) {
  for (int i = 0; i < 100000; i++) { if (mbar_test(go, 0)) return false; if (mbar_test(landed, 0)) return true; }
  return false;
}
#define PD1 1
#define PD0 2
#define PD2 1
__device__ __forceinline__ void l2_prefetch(const void* p, int bytes) { asm volatile("cp.async.bulk.prefetch.L2.global [%0],%1;" ::"l"(p), "r"(bytes) : "memory"); }
__device__ __forceinline__ void pdl_launch() { asm volatile("griddepcontrol.launch_dependents;" ::: "memory"); }
__device__ __forceinline__ void pdl_wait() { asm volatile("griddepcontrol.wait;" ::: "memory"); }
__device__ __forceinline__ void wg_fence() { asm volatile("wgmma.fence.sync.aligned;" ::: "memory"); }
__device__ __forceinline__ void wg_commit() { asm volatile("wgmma.commit_group.sync.aligned;" ::: "memory"); }
template <int N> __device__ __forceinline__ void wg_wait() { asm volatile("wgmma.wait_group.sync.aligned %0;" ::"n"(N) : "memory"); }
template <int N> __device__ __forceinline__ void reg_fence(float (&d)[N]) {
#pragma unroll
  for (int i = 0; i < N; i++) asm volatile("" : "+f"(d[i])::"memory");
}
template <int N> __device__ __forceinline__ void zero(float (&d)[N]) {
#pragma unroll
  for (int i = 0; i < N; i++) d[i] = 0.f;
  reg_fence(d);
}
__device__ __forceinline__ uint64_t mk_desc(uint32_t addr, uint32_t lbo, uint32_t sbo, uint32_t mode) {
  return (uint64_t)((addr >> 4) & 0x3FFF) | ((uint64_t)(lbo >> 4) << 16) | ((uint64_t)(sbo >> 4) << 32) | ((uint64_t)mode << 62);
}
__device__ __forceinline__ void ldsm4(uint32_t a, uint32_t (&r)[4]) {
  asm volatile("ldmatrix.sync.aligned.m8n8.x4.shared.b16 {%0,%1,%2,%3},[%4];" : "=r"(r[0]), "=r"(r[1]), "=r"(r[2]), "=r"(r[3]) : "r"(a) : "memory");
}
__device__ __forceinline__ uint32_t pack_rn(float lo, float hi) { uint32_t r; asm("cvt.rn.bf16x2.f32 %0,%1,%2;" : "=r"(r) : "f"(hi), "f"(lo)); return r; }
__device__ __forceinline__ uint32_t pack_rz(float lo, float hi) { uint32_t r; asm("cvt.rz.bf16x2.f32 %0,%1,%2;" : "=r"(r) : "f"(hi), "f"(lo)); return r; }
__device__ __forceinline__ float blo(uint32_t u) { return __uint_as_float(u << 16); }
__device__ __forceinline__ float bhi(uint32_t u) { return __uint_as_float(u & 0xFFFF0000u); }
__device__ __forceinline__ float rbf(float x) { return __bfloat162float(__float2bfloat16_rn(x)); }
__device__ __forceinline__ float qsum(float v) { v += __shfl_xor_sync(~0u, v, 1); return v + __shfl_xor_sync(~0u, v, 2); }
__device__ __forceinline__ float ex2(float x) { float r; asm("ex2.approx.ftz.f32 %0,%1;" : "=f"(r) : "f"(x)); return r; }
#define TS(k, i)
__device__ __forceinline__ void wgmma_rs_n176_t1(float (&d)[88],uint32_t a0,uint32_t a1,uint32_t a2,uint32_t a3,uint64_t db,int sc){
  asm volatile("{\n.reg .pred p;\nsetp.ne.b32 p,%93,0;\n"
    "wgmma.mma_async.sync.aligned.m64n176k16.f32.bf16.bf16 {%0,%1,%2,%3,%4,%5,%6,%7,%8,%9,%10,%11,%12,%13,%14,%15,%16,%17,%18,%19,%20,%21,%22,%23,%24,%25,%26,%27,%28,%29,%30,%31,%32,%33,%34,%35,%36,%37,%38,%39,%40,%41,%42,%43,%44,%45,%46,%47,%48,%49,%50,%51,%52,%53,%54,%55,%56,%57,%58,%59,%60,%61,%62,%63,%64,%65,%66,%67,%68,%69,%70,%71,%72,%73,%74,%75,%76,%77,%78,%79,%80,%81,%82,%83,%84,%85,%86,%87},{%88,%89,%90,%91},%92,p,1,1,1;\n}\n"
    :"+f"(d[0]),"+f"(d[1]),"+f"(d[2]),"+f"(d[3]),"+f"(d[4]),"+f"(d[5]),"+f"(d[6]),"+f"(d[7]),"+f"(d[8]),"+f"(d[9]),"+f"(d[10]),"+f"(d[11]),"+f"(d[12]),"+f"(d[13]),"+f"(d[14]),"+f"(d[15]),"+f"(d[16]),"+f"(d[17]),"+f"(d[18]),"+f"(d[19]),"+f"(d[20]),"+f"(d[21]),"+f"(d[22]),"+f"(d[23]),"+f"(d[24]),"+f"(d[25]),"+f"(d[26]),"+f"(d[27]),"+f"(d[28]),"+f"(d[29]),"+f"(d[30]),"+f"(d[31]),"+f"(d[32]),"+f"(d[33]),"+f"(d[34]),"+f"(d[35]),"+f"(d[36]),"+f"(d[37]),"+f"(d[38]),"+f"(d[39]),"+f"(d[40]),"+f"(d[41]),"+f"(d[42]),"+f"(d[43]),"+f"(d[44]),"+f"(d[45]),"+f"(d[46]),"+f"(d[47]),"+f"(d[48]),"+f"(d[49]),"+f"(d[50]),"+f"(d[51]),"+f"(d[52]),"+f"(d[53]),"+f"(d[54]),"+f"(d[55]),"+f"(d[56]),"+f"(d[57]),"+f"(d[58]),"+f"(d[59]),"+f"(d[60]),"+f"(d[61]),"+f"(d[62]),"+f"(d[63]),"+f"(d[64]),"+f"(d[65]),"+f"(d[66]),"+f"(d[67]),"+f"(d[68]),"+f"(d[69]),"+f"(d[70]),"+f"(d[71]),"+f"(d[72]),"+f"(d[73]),"+f"(d[74]),"+f"(d[75]),"+f"(d[76]),"+f"(d[77]),"+f"(d[78]),"+f"(d[79]),"+f"(d[80]),"+f"(d[81]),"+f"(d[82]),"+f"(d[83]),"+f"(d[84]),"+f"(d[85]),"+f"(d[86]),"+f"(d[87])
    :"r"(a0),"r"(a1),"r"(a2),"r"(a3),"l"(db),"r"(sc));
}
__device__ __forceinline__ void wgmma_rs_n192_t1(float (&d)[96],uint32_t a0,uint32_t a1,uint32_t a2,uint32_t a3,uint64_t db,int sc){
  asm volatile("{\n.reg .pred p;\nsetp.ne.b32 p,%101,0;\n"
    "wgmma.mma_async.sync.aligned.m64n192k16.f32.bf16.bf16 {%0,%1,%2,%3,%4,%5,%6,%7,%8,%9,%10,%11,%12,%13,%14,%15,%16,%17,%18,%19,%20,%21,%22,%23,%24,%25,%26,%27,%28,%29,%30,%31,%32,%33,%34,%35,%36,%37,%38,%39,%40,%41,%42,%43,%44,%45,%46,%47,%48,%49,%50,%51,%52,%53,%54,%55,%56,%57,%58,%59,%60,%61,%62,%63,%64,%65,%66,%67,%68,%69,%70,%71,%72,%73,%74,%75,%76,%77,%78,%79,%80,%81,%82,%83,%84,%85,%86,%87,%88,%89,%90,%91,%92,%93,%94,%95},{%96,%97,%98,%99},%100,p,1,1,1;\n}\n"
    :"+f"(d[0]),"+f"(d[1]),"+f"(d[2]),"+f"(d[3]),"+f"(d[4]),"+f"(d[5]),"+f"(d[6]),"+f"(d[7]),"+f"(d[8]),"+f"(d[9]),"+f"(d[10]),"+f"(d[11]),"+f"(d[12]),"+f"(d[13]),"+f"(d[14]),"+f"(d[15]),"+f"(d[16]),"+f"(d[17]),"+f"(d[18]),"+f"(d[19]),"+f"(d[20]),"+f"(d[21]),"+f"(d[22]),"+f"(d[23]),"+f"(d[24]),"+f"(d[25]),"+f"(d[26]),"+f"(d[27]),"+f"(d[28]),"+f"(d[29]),"+f"(d[30]),"+f"(d[31]),"+f"(d[32]),"+f"(d[33]),"+f"(d[34]),"+f"(d[35]),"+f"(d[36]),"+f"(d[37]),"+f"(d[38]),"+f"(d[39]),"+f"(d[40]),"+f"(d[41]),"+f"(d[42]),"+f"(d[43]),"+f"(d[44]),"+f"(d[45]),"+f"(d[46]),"+f"(d[47]),"+f"(d[48]),"+f"(d[49]),"+f"(d[50]),"+f"(d[51]),"+f"(d[52]),"+f"(d[53]),"+f"(d[54]),"+f"(d[55]),"+f"(d[56]),"+f"(d[57]),"+f"(d[58]),"+f"(d[59]),"+f"(d[60]),"+f"(d[61]),"+f"(d[62]),"+f"(d[63]),"+f"(d[64]),"+f"(d[65]),"+f"(d[66]),"+f"(d[67]),"+f"(d[68]),"+f"(d[69]),"+f"(d[70]),"+f"(d[71]),"+f"(d[72]),"+f"(d[73]),"+f"(d[74]),"+f"(d[75]),"+f"(d[76]),"+f"(d[77]),"+f"(d[78]),"+f"(d[79]),"+f"(d[80]),"+f"(d[81]),"+f"(d[82]),"+f"(d[83]),"+f"(d[84]),"+f"(d[85]),"+f"(d[86]),"+f"(d[87]),"+f"(d[88]),"+f"(d[89]),"+f"(d[90]),"+f"(d[91]),"+f"(d[92]),"+f"(d[93]),"+f"(d[94]),"+f"(d[95])
    :"r"(a0),"r"(a1),"r"(a2),"r"(a3),"l"(db),"r"(sc));
}
__device__ __forceinline__ void wgmma_rs_n24_t1(float (&d)[12],uint32_t a0,uint32_t a1,uint32_t a2,uint32_t a3,uint64_t db,int sc){
  asm volatile("{\n.reg .pred p;\nsetp.ne.b32 p,%17,0;\n"
    "wgmma.mma_async.sync.aligned.m64n24k16.f32.bf16.bf16 {%0,%1,%2,%3,%4,%5,%6,%7,%8,%9,%10,%11},{%12,%13,%14,%15},%16,p,1,1,1;\n}\n"
    :"+f"(d[0]),"+f"(d[1]),"+f"(d[2]),"+f"(d[3]),"+f"(d[4]),"+f"(d[5]),"+f"(d[6]),"+f"(d[7]),"+f"(d[8]),"+f"(d[9]),"+f"(d[10]),"+f"(d[11])
    :"r"(a0),"r"(a1),"r"(a2),"r"(a3),"l"(db),"r"(sc));
}
__device__ __forceinline__ void wgmma_rs_n64_t0(float (&d)[32],uint32_t a0,uint32_t a1,uint32_t a2,uint32_t a3,uint64_t db,int sc){
  asm volatile("{\n.reg .pred p;\nsetp.ne.b32 p,%37,0;\n"
    "wgmma.mma_async.sync.aligned.m64n64k16.f32.bf16.bf16 {%0,%1,%2,%3,%4,%5,%6,%7,%8,%9,%10,%11,%12,%13,%14,%15,%16,%17,%18,%19,%20,%21,%22,%23,%24,%25,%26,%27,%28,%29,%30,%31},{%32,%33,%34,%35},%36,p,1,1,0;\n}\n"
    :"+f"(d[0]),"+f"(d[1]),"+f"(d[2]),"+f"(d[3]),"+f"(d[4]),"+f"(d[5]),"+f"(d[6]),"+f"(d[7]),"+f"(d[8]),"+f"(d[9]),"+f"(d[10]),"+f"(d[11]),"+f"(d[12]),"+f"(d[13]),"+f"(d[14]),"+f"(d[15]),"+f"(d[16]),"+f"(d[17]),"+f"(d[18]),"+f"(d[19]),"+f"(d[20]),"+f"(d[21]),"+f"(d[22]),"+f"(d[23]),"+f"(d[24]),"+f"(d[25]),"+f"(d[26]),"+f"(d[27]),"+f"(d[28]),"+f"(d[29]),"+f"(d[30]),"+f"(d[31])
    :"r"(a0),"r"(a1),"r"(a2),"r"(a3),"l"(db),"r"(sc));
}
__device__ __forceinline__ void wgmma_ss_n128_t1(float (&d)[64],uint64_t da,uint64_t db,int sc){
  asm volatile("{\n.reg .pred p;\nsetp.ne.b32 p,%66,0;\n"
    "wgmma.mma_async.sync.aligned.m64n128k16.f32.bf16.bf16 {%0,%1,%2,%3,%4,%5,%6,%7,%8,%9,%10,%11,%12,%13,%14,%15,%16,%17,%18,%19,%20,%21,%22,%23,%24,%25,%26,%27,%28,%29,%30,%31,%32,%33,%34,%35,%36,%37,%38,%39,%40,%41,%42,%43,%44,%45,%46,%47,%48,%49,%50,%51,%52,%53,%54,%55,%56,%57,%58,%59,%60,%61,%62,%63},%64,%65,p,1,1,0,1;\n}\n"
    :"+f"(d[0]),"+f"(d[1]),"+f"(d[2]),"+f"(d[3]),"+f"(d[4]),"+f"(d[5]),"+f"(d[6]),"+f"(d[7]),"+f"(d[8]),"+f"(d[9]),"+f"(d[10]),"+f"(d[11]),"+f"(d[12]),"+f"(d[13]),"+f"(d[14]),"+f"(d[15]),"+f"(d[16]),"+f"(d[17]),"+f"(d[18]),"+f"(d[19]),"+f"(d[20]),"+f"(d[21]),"+f"(d[22]),"+f"(d[23]),"+f"(d[24]),"+f"(d[25]),"+f"(d[26]),"+f"(d[27]),"+f"(d[28]),"+f"(d[29]),"+f"(d[30]),"+f"(d[31]),"+f"(d[32]),"+f"(d[33]),"+f"(d[34]),"+f"(d[35]),"+f"(d[36]),"+f"(d[37]),"+f"(d[38]),"+f"(d[39]),"+f"(d[40]),"+f"(d[41]),"+f"(d[42]),"+f"(d[43]),"+f"(d[44]),"+f"(d[45]),"+f"(d[46]),"+f"(d[47]),"+f"(d[48]),"+f"(d[49]),"+f"(d[50]),"+f"(d[51]),"+f"(d[52]),"+f"(d[53]),"+f"(d[54]),"+f"(d[55]),"+f"(d[56]),"+f"(d[57]),"+f"(d[58]),"+f"(d[59]),"+f"(d[60]),"+f"(d[61]),"+f"(d[62]),"+f"(d[63])
    :"l"(da),"l"(db),"r"(sc));
}
__device__ __forceinline__ void wgmma_ss_n64_t1(float (&d)[32],uint64_t da,uint64_t db,int sc){
  asm volatile("{\n.reg .pred p;\nsetp.ne.b32 p,%34,0;\n"
    "wgmma.mma_async.sync.aligned.m64n64k16.f32.bf16.bf16 {%0,%1,%2,%3,%4,%5,%6,%7,%8,%9,%10,%11,%12,%13,%14,%15,%16,%17,%18,%19,%20,%21,%22,%23,%24,%25,%26,%27,%28,%29,%30,%31},%32,%33,p,1,1,0,1;\n}\n"
    :"+f"(d[0]),"+f"(d[1]),"+f"(d[2]),"+f"(d[3]),"+f"(d[4]),"+f"(d[5]),"+f"(d[6]),"+f"(d[7]),"+f"(d[8]),"+f"(d[9]),"+f"(d[10]),"+f"(d[11]),"+f"(d[12]),"+f"(d[13]),"+f"(d[14]),"+f"(d[15]),"+f"(d[16]),"+f"(d[17]),"+f"(d[18]),"+f"(d[19]),"+f"(d[20]),"+f"(d[21]),"+f"(d[22]),"+f"(d[23]),"+f"(d[24]),"+f"(d[25]),"+f"(d[26]),"+f"(d[27]),"+f"(d[28]),"+f"(d[29]),"+f"(d[30]),"+f"(d[31])
    :"l"(da),"l"(db),"r"(sc));
}

__device__ __forceinline__ float silu_bf(bf16 c) { const float x = __bfloat162float(c); return rbf(x / (1.f + __expf(-x))); }
__device__ __forceinline__ void fma8(float (&a)[8], float s, const uint4& v) {
  a[0] += s * blo(v.x); a[1] += s * bhi(v.x); a[2] += s * blo(v.y); a[3] += s * bhi(v.y);
  a[4] += s * blo(v.z); a[5] += s * bhi(v.z); a[6] += s * blo(v.w); a[7] += s * bhi(v.w);
}
__device__ __forceinline__ float red8(float (&a)[8], int lane) {
#pragma unroll
  for (int w = 4; w >= 1; w >>= 1) {
    const bool up = lane & (w * 4);
#pragma unroll
    for (int j = 0; j < w; j++) a[j] = (up ? a[j + w] : a[j]) + __shfl_xor_sync(~0u, up ? a[j] : a[j + w], w * 4);
  }
  return a[0];
}
__device__ __forceinline__ float mod_fin(float s, int n) { s = rbf(s); return ((n >> 9) == 1 || (n >> 9) == 4) ? rbf(1.f + s) : s; }
__device__ __forceinline__ void poll(uint2& a, uint2& b, float (&w)[16], const uint32_t* p, const uint32_t* q) {
  asm volatile("{\n.reg .pred p;\n.reg .b32 n,t,u;\nmov.u32 n,0;\nLW:\nld.relaxed.gpu.global.v2.u32 {%0,%1},[%20];\nld.relaxed.gpu.global.v2.u32 {%2,%3},[%20+64];\n"
               "ld.relaxed.gpu.global.v4.f32 {%4,%5,%6,%7},[%21];\nld.relaxed.gpu.global.v4.f32 {%8,%9,%10,%11},[%21+16];\n"
               "ld.relaxed.gpu.global.v4.f32 {%12,%13,%14,%15},[%21+8192];\nld.relaxed.gpu.global.v4.f32 {%16,%17,%18,%19},[%21+8208];\n"
               "lop3.b32 t,%0,%1,%2,0x80;\nlop3.b32 u,%3,%4,%5,0x80;\nlop3.b32 t,t,%6,%7,0x80;\nlop3.b32 u,u,%8,%9,0x80;\nlop3.b32 t,t,%10,%11,0x80;\n"
               "lop3.b32 u,u,%12,%13,0x80;\nlop3.b32 t,t,%14,%15,0x80;\nlop3.b32 u,u,%16,%17,0x80;\nlop3.b32 t,t,%18,%19,0x80;\nlop3.b32 t,t,u,1,0x80;\n"
               "setp.ne.u32 p,t,0;\n@p bra LD;\nadd.u32 n,n,1;\nsetp.lt.u32 p,n,1048576;\n@p bra LW;\nLD:\n}\n"
               : "=&r"(a.x), "=&r"(a.y), "=&r"(b.x), "=&r"(b.y), "=&f"(w[0]), "=&f"(w[1]), "=&f"(w[2]), "=&f"(w[3]), "=&f"(w[4]), "=&f"(w[5]), "=&f"(w[6]), "=&f"(w[7]),
                 "=&f"(w[8]), "=&f"(w[9]), "=&f"(w[10]), "=&f"(w[11]), "=&f"(w[12]), "=&f"(w[13]), "=&f"(w[14]), "=&f"(w[15]) : "l"(p), "l"(q) : "memory");
}

constexpr int LN_SMEM = 131072 + 4 * 24576 + 2816 + 256;
#define TANH 1
#define DLY 2
template <bool FFN>
__global__ void __cluster_dims__(2, 1, 1) __launch_bounds__(384, 1) k_lngemm(const __grid_constant__ CUtensorMap mX, const __grid_constant__ CUtensorMap mB0,
                                                   const __grid_constant__ CUtensorMap mB1, const bf16* __restrict__ cv, const bf16* __restrict__ wm, const bf16* __restrict__ xg, const bf16* wq) {
  extern __shared__ __align__(1024) uint8_t smem[];
  const uint32_t sA = smem_u32(smem), sB = sA + (FFN ? 81920 : 131072), sM = sA + 229376, bars = sM + 2816;
  const uint32_t bA = bars, bF = bars + 64, bE = bars + 112;
  constexpr int NB = FFN ? 6 : 4;
  const int tid = threadIdx.x, warp = tid >> 5, lane = tid & 31;
  const int pr = blockIdx.x & 1, rb = FFN ? (blockIdx.x >> 4) * 2 + pr : blockIdx.x >> 3, ct = FFN ? (blockIdx.x >> 1) & 7 : blockIdx.x & 7;
  constexpr int NST = FFN ? 16 : 8, KS = FFN ? 2 : 4, BOX = FFN ? 4096 : 8192;
  TS(FFN ? 4 : 1, 0);
  pdl_launch();
  float* red = (float*)(smem + (sM - sA));
  if (tid == 256) {
    for (int i = 0; i < 8; i++) mbar_init(bA + 8 * i, 1);
    for (int i = 0; i < NB; i++) { mbar_init(bF + 8 * i, 1); mbar_init(bE + 8 * i, FFN ? 16 : 8); }
    mbar_init(bars + 160, 1);
    fence_init();
  }
  __syncwarp();
  cluster_arrive();
  uint4 wv0, wv1, xv[4];
  bf16 cv0, cv1;
  if (!FFN && tid < 256) {
    const int r = (blockIdx.x & 3) * 128 + (tid >> 2);
    const uint4* wp = (const uint4*)(wm + r * 3072 + (blockIdx.x >> 2) * 32 + (tid & 3) * 8);
    wv0 = __ldg(wp); wv1 = __ldg(wp + 64 * 384);
    cv0 = cv[r]; cv1 = cv[r + 64];
#pragma unroll
    for (int i = 0; i < 4; i++) xv[i] = __ldg((const uint4*)(xg + (blockIdx.x * 16 + (tid >> 4)) * 512 + i * 128 + (tid & 15) * 8));
  }
  cluster_wait();
  if (warp >= 8) {
    asm volatile("setmaxnreg.dec.sync.aligned.u32 40;");
    if (tid == 256) {
      auto loadB = [&](int s) {
        const uint32_t d = sB + (s % NB) * 24576, b = bF + (s % NB) * 8;
        mbar_expect(b, 24576);
        for (int j = 0; j < 3; j++) {
          if (FFN) tma2d_mc(d + (pr * 3 + j) * BOX, pr ? &mB1 : &mB0, ct * 176 + j * 64, s * 32, b);
          else tma2d(d + j * BOX, &mB0, ct * 192 + j * 64, s * 64, b);
        }
      };
      for (int i = 0; i < 8; i++) mbar_expect(bA + 8 * i, 16384);
      if (!FFN) l2_prefetch((const char*)wq + blockIdx.x * 12288, 12288);
      int nb = 0;
      for (int s = 0; s < NB; s++, nb++) {
        const int i = s * 2 + (ct & 1);
        if (FFN && s >= PD1 && !may_preload(bF + (s - PD1) * 8, bars + 160)) break;
        if (!FFN && s == DLY) mbar_wait(bars + 160, 0);
        if (!FFN) tma2d_mc(sA + i * 16384, &mX, i * 64, rb * 128, bA + 8 * i);
        loadB(s);
      }
      if (FFN) {
        pdl_wait();
        for (int i = 0; i < 5; i++) {
          bulk_load(sA + i * 16384, g_a + (rb * 64 + i * 8) * 1024, 16384, bA + 8 * i);
          for (; nb < 2 * i + 2 && nb < NB; nb++) loadB(nb);
        }
      }
      for (int s = NB; s < NST; s++) {
        mbar_wait(bE + (s % NB) * 8, (s / NB - 1) & 1); loadB(s);
        if (FFN && s <= 10 && !(s & 1)) bulk_load(sA + (s / 2 - 3) * 16384, g_a + (rb * 64 + (s / 2 + 2) * 8) * 1024, 16384, bA + 8 * (s / 2 + 2));
      }
    }
  } else {
  asm volatile("setmaxnreg.inc.sync.aligned.u32 232;");
  const int g = lane >> 2, t = lane & 3;
  const int lr = warp * 16 + (lane & 7) + ((lane >> 3) & 1) * 8;
  auto aaddr = [&](int ks) -> uint32_t {
    if (FFN) return sA + ((ks < 20 ? ks : ks - 20) * 2 + (lane >> 4)) * 2048 + lr * 16;
    return sA + (ks >> 2) * 16384 + lr * 128 + ((((ks & 3) * 2 + (lane >> 4)) ^ (lr & 7)) << 4);
  };
  const int row0 = rb * 128 + warp * 16 + g;
  float2 msh, msc;
  float4 p0, p1, uv;
  float rs0, rs1, nm0, nm1;
  if (!FFN) {
    {
      float a[8] = {0, 0, 0, 0, 0, 0, 0, 0};
      fma8(a, silu_bf(cv0), wv0); fma8(a, silu_bf(cv1), wv1);
      red[warp * 32 + t * 8 + g] = red8(a, lane);
      asm volatile("bar.sync 1,256;" ::: "memory");
      if (tid < 32) {
        float r = 0;
#pragma unroll
        for (int i = 0; i < 8; i++) r += red[i * 32 + tid];
        asm volatile("st.relaxed.gpu.global.u32 [%0],%1;" ::"l"(g_modv + ((blockIdx.x >> 2) * 32 + tid) * 4 + (blockIdx.x & 3)), "r"(__float_as_uint(r) | 1u) : "memory");
      }
      TS(0, 1);
    }
    {
      float v[32], s = 0, q = 0;
#pragma unroll
      for (int i = 0; i < 16; i++) { const uint32_t u = ((const uint32_t*)xv)[i]; v[2 * i] = blo(u); v[2 * i + 1] = bhi(u); s += v[2 * i] + v[2 * i + 1]; }
      s = qsum(s); s += __shfl_xor_sync(~0u, s, 4); s += __shfl_xor_sync(~0u, s, 8);
      const float m = s * (1.f / 512);
#pragma unroll
      for (int i = 0; i < 32; i++) q += (v[i] - m) * (v[i] - m);
      q = qsum(q); q += __shfl_xor_sync(~0u, q, 4); q += __shfl_xor_sync(~0u, q, 8);
      const float rs = rsqrtf(q * (1.f / 512) + 1e-5f);
      if ((tid & 15) == 0)
        asm volatile("st.relaxed.gpu.global.v2.u32 [%0],{%1,%2};" ::"l"(g_modv + 4096 + (blockIdx.x * 16 + (tid >> 4)) * 2), "r"(__float_as_uint(rs) | 1u), "r"(__float_as_uint(-m * rs) | 1u) : "memory");
    }
    uint2 q0, q1;
    float w[16];
    if (tid < 128) {
      uint32_t v; int n = 0;
      do asm volatile("ld.relaxed.gpu.global.u32 %0,[%1];" : "=r"(v) : "l"(g_modv + (tid >> 2) * 128 + (tid & 3)) : "memory"); while (!(v & 1) && ++n < 1048576);
    }
    asm volatile("bar.sync 1,256;" ::: "memory");
    poll(q0, q1, w, g_modv + 4096 + row0 * 2, g_modv + tid * 8);
    msh = make_float2(mod_fin(w[0] + w[1] + w[2] + w[3], 0), mod_fin(w[4] + w[5] + w[6] + w[7], 0));
    msc = make_float2(mod_fin(w[8] + w[9] + w[10] + w[11], 512), mod_fin(w[12] + w[13] + w[14] + w[15], 512));
    asm volatile("bar.sync 1,256;" ::: "memory");
    if (tid == 32) mbar_arrive(bars + 160);
    rs0 = __uint_as_float(q0.x); nm0 = __uint_as_float(q0.y); rs1 = __uint_as_float(q1.x); nm1 = __uint_as_float(q1.y);
  } else {
    pdl_wait();
    if (tid == 32) mbar_arrive(bars + 160);
    TS(4, 1);
    p0 = *(const float4*)(g_st + row0 * 8 + t * 2); p1 = *(const float4*)(g_st + (row0 + 8) * 8 + t * 2);
    if (tid < 176) uv = *(const float4*)(g_uv + (tid >= 88 ? 1408 - 176 : 0) + ct * 176 + tid * 2);
  }
  if (!FFN) {
    uint32_t* m = (uint32_t*)(smem + (sM - sA)) + (tid >> 3) * 16 + (tid & 3) * 4 + ((tid >> 2) & 1);
    m[0] = pack_rn(msc.x, msc.y); m[2] = pack_rn(msh.x, msh.y);
    asm volatile("bar.sync 1,256;" ::: "memory");
  }
  constexpr int NA = FFN ? 88 : 96;
  float acc0[NA], acc1[FFN ? 88 : 1];
  uint32_t a[2][KS][4];
  auto prep = [&](int ks, uint32_t(&o)[4]) {
    if ((ks & 3) == 0) mbar_wait(bA + 2 * ks, 0);
    if (FFN) { ldsm4(aaddr(ks), o); return; }
    uint32_t r[4]; ldsm4(aaddr(ks), r);
    const uint4 m = *(const uint4*)(smem + (sM - sA) + ks * 64 + t * 16);
#pragma unroll
    for (int i = 0; i < 4; i++) {
      const float rs = (i & 1) ? rs1 : rs0, nm = (i & 1) ? nm1 : nm0;
      const uint32_t n = pack_rn(fmaf(blo(r[i]), rs, nm), fmaf(bhi(r[i]), rs, nm));
      asm("fma.rn.bf16x2 %0,%1,%2,%3;" : "=r"(o[i]) : "r"(n), "r"(i < 2 ? m.x : m.y), "r"(i < 2 ? m.z : m.w));
    }
  };
  auto stage = [&](int s, uint32_t(&c)[KS][4], uint32_t(&n)[KS][4]) {
    mbar_wait(bF + (s % NB) * 8, (s / NB) & 1);
    const uint64_t db = mk_desc(sB + (s % NB) * 24576, BOX, 1024, 1);
    wg_fence();
#pragma unroll
    for (int k = 0; k < KS; k++) {
      if constexpr (FFN) {
        wgmma_rs_n176_t1(acc0, c[k][0], c[k][1], c[k][2], c[k][3], db + k * 128, s + k);
        wgmma_rs_n176_t1(acc1, c[k][0], c[k][1], c[k][2], c[k][3], db + k * 128 + 3 * BOX / 16, s + k);
      } else {
        wgmma_rs_n192_t1(acc0, c[k][0], c[k][1], c[k][2], c[k][3], db + k * 128, s + k);
      }
    }
    wg_commit();
    wg_wait<1>();
    if (s > 0 && s <= NST - NB) {
      if (!FFN) { if (lane == 0) mbar_arrive(bE + ((s - 1) % NB) * 8); }
      else if (lane < 2) asm volatile("{\n.reg .b32 r;\nmapa.shared::cluster.u32 r,%0,%1;\nmbarrier.arrive.relaxed.cluster.shared::cluster.b64 _,[r];\n}" ::"r"(bE + ((s - 1) % NB) * 8), "r"(lane) : "memory");
    }
    if (s < NST - 1) {
#pragma unroll
      for (int k = 0; k < KS; k++) prep((s + 1) * KS + k, n[k]);
    }
  };
#pragma unroll
  for (int k = 0; k < KS; k++) prep(k, a[0][k]);
  TS(FFN ? 4 : 1, 2);
#pragma unroll 1
  for (int s = 0; s < NST; s += 2) { stage(s, a[0], a[1]); stage(s + 1, a[1], a[0]); }
  if (FFN) {
    if (tid < 88) { uv.x *= 0.5f; uv.y *= 0.5f; uv.z *= 0.5f; uv.w *= 0.5f; }
    if (tid < 176) *(float4*)(smem + (sM - sA) + tid * 16) = uv;
    const float m0 = qsum(p0.x + p0.z) * 0.125f, m1 = qsum(p1.x + p1.z) * 0.125f;
    const float v0 = qsum(p0.y + p0.w + 64.f * ((p0.x - m0) * (p0.x - m0) + (p0.z - m0) * (p0.z - m0)));
    const float v1 = qsum(p1.y + p1.w + 64.f * ((p1.x - m1) * (p1.x - m1) + (p1.z - m1) * (p1.z - m1)));
    rs0 = rsqrtf(v0 * (1.f / 512) + 1e-5f); rs1 = rsqrtf(v1 * (1.f / 512) + 1e-5f);
    nm0 = -m0 * rs0; nm1 = -m1 * rs1;
    asm volatile("bar.sync 1,256;" ::: "memory");
  }
  wg_wait<0>();
  reg_fence(acc0);
  TS(FFN ? 4 : 1, 3);
  if constexpr (FFN) {
    reg_fence(acc1);
    const float rh0 = 0.5f * rs0, rh1 = 0.5f * rs1;
    uint32_t* o = (uint32_t*)g_h + ((rb * 172 + ct * 22) * 128 + warp * 16 + g) * 4 + t;
#pragma unroll
    for (int j = 0; j < 22; j++) {
      {
        const float4 u1 = *(const float4*)(smem + (sM - sA) + (j * 4 + t) * 16), u3 = *(const float4*)(smem + (sM - sA) + (88 + j * 4 + t) * 16);
        float h[4];
#pragma unroll
        for (int i = 0; i < 4; i++) {
          const float rs = i < 2 ? rs0 : rs1, nm = i < 2 ? nm0 : nm1, rh = i < 2 ? rh0 : rh1;
          const float z = fmaf(rh, acc0[4 * j + i], (i & 1) ? fmaf(nm, u1.z, u1.w) : fmaf(nm, u1.x, u1.y));
          const float y = fmaf(rs, acc1[4 * j + i], (i & 1) ? fmaf(nm, u3.z, u3.w) : fmaf(nm, u3.x, u3.y));
          float th; asm("tanh.approx.f32 %0,%1;" : "=f"(th) : "f"(z));
          h[i] = fmaf(z, th, z) * y;
        }
        if (j < 18 || ct < 7) { o[j * 512] = pack_rn(h[0], h[1]); o[j * 512 + 32] = pack_rn(h[2], h[3]); }
      }
    }
  } else {
    uint32_t* o = (uint32_t*)g_qkv + (ct * 24 * 2048 + row0) * 4 + t;
#pragma unroll
    for (int j = 0; j < 24; j += 2) {
      const int G = ct * 24 + j;
      const float sc = G < 64 ? 0.25f * 1.4426950408889634f : 1.f;
      uint32_t p[4];
#pragma unroll
      for (int i = 0; i < 4; i++) p[i] = pack_rn(acc0[4 * j + 2 * i] * sc, acc0[4 * j + 2 * i + 1] * sc);
      o[j * 8192] = p[0]; o[j * 8192 + 32] = p[1]; o[(j + 1) * 8192] = p[2]; o[(j + 1) * 8192 + 32] = p[3];
      if (G >= 64 && G < 128) {
        float n0 = blo(p[0]) * blo(p[0]) + bhi(p[0]) * bhi(p[0]) + blo(p[2]) * blo(p[2]) + bhi(p[2]) * bhi(p[2]);
        float n1 = blo(p[1]) * blo(p[1]) + bhi(p[1]) * bhi(p[1]) + blo(p[3]) * blo(p[3]) + bhi(p[3]) * bhi(p[3]);
        n0 = qsum(n0); n1 = qsum(n1);
        const uint32_t mx = __reduce_max_sync(~0u, max(__float_as_uint(n0), __float_as_uint(n1)));
        if (lane == 0) g_kmax[((G - 64) >> 1) * 128 + rb * 8 + warp] = __uint_as_float(mx);
      }
    }
  }
  TS(FFN ? 4 : 1, 4);
}
}

#define SMASK 0xCCCCu
#define BRK 0
#define PACK 1
constexpr int AT_SMEM = 5 * 32768 + 256;
__device__ __forceinline__ uint32_t exp2_pair_fma(float s0, float s1, float c, uint32_t ka, uint32_t kz) {
  uint32_t r;
  asm volatile("{\n.reg .b32 y0,y1,e,u,t;\n"
      "fma.rn.sat.f32 y0,%1,0f00000080,%3;\nfma.rn.sat.f32 y1,%2,0f00000080,%3;\n"
      "mad.lo.u32 e,y1,65536,y0;\n"
      "and.b32 u,e,0x007F007F;\n"
      "fma.rn.f16x2 u,u,%4,%5;\nfma.rn.f16x2 t,u,u,%6;\nfma.rn.f16x2 t,t,u,%7;\n"
      "lop3.b32 %0,t,0x007F007F,e,0xE2;\n}\n"
      : "=r"(r) : "f"(s0), "f"(s1), "f"(c), "r"(ka), "r"(0x36B236B2u), "r"(0x3C733C73u), "r"(0x47764776u), "r"(kz));
  return r;
}
__device__ __forceinline__ void attn_pass(float (&oa)[12], float (&ob)[12], const uint32_t (&q)[4], float m0, float m1, uint32_t sK, uint32_t bars, bool first, uint32_t kz) {
  uint64_t dk = mk_desc(sK, 32768, 128, 0), dv = mk_desc(sK + 65536, 128, 32768, 0);
  const float c0 = (127.f - m0) * __uint_as_float(0x80u), c1 = (127.f - m1) * __uint_as_float(0x80u);
  uint32_t ka;
  asm volatile("mov.b32 %0,0x7ACE7ACE;" : "=r"(ka));
  constexpr int NK = 64, NS = 32, NP = 16;
  auto qk = [&](float (&s)[NS], int i) { wgmma_rs_n64_t0(s, q[0], q[1], q[2], q[3], dk + i * NK, 0); };
  auto softmax = [&](float (&s)[NS], uint32_t (&p)[NP], uint32_t mask) {
    reg_fence(s);
    float e0, e1;
    int pend = -1;
#pragma unroll
    for (int t = 0; t < NP; t++) {
      const int j = (t & 3) * 4 + (t >> 2);
      if ((mask >> (t & 3)) & 1) {
        p[j] = exp2_pair_fma(s[2 * j], s[2 * j + 1], (j & 1) ? c1 : c0, ka, kz);
      } else {
        float f0, f1;
        asm volatile("ex2.approx.ftz.f32 %0,%2;\nex2.approx.ftz.f32 %1,%3;" : "=&f"(f0), "=f"(f1) : "f"(s[2 * j]), "f"(s[2 * j + 1]));
        if (pend >= 0) asm volatile("cvt.rn.bf16x2.f32 %0,%1,%2;" : "=r"(p[pend]) : "f"(e1), "f"(e0));
        e0 = f0; e1 = f1; pend = j;
      }
    }
    if (pend >= 0) asm volatile("cvt.rn.bf16x2.f32 %0,%1,%2;" : "=r"(p[pend]) : "f"(e1), "f"(e0));
#pragma unroll
    for (int j = 0; j < NP; j++) asm volatile("" : "+r"(p[j])::"memory");
  };
  auto pv = [&](uint32_t (&p)[NP], int i, uint32_t mask) {
#pragma unroll
    for (int k = 0; k < 4; k++) wgmma_rs_n24_t1(((mask >> k) & 1) ? ob : oa, p[4 * k], p[4 * k + 1], p[4 * k + 2], p[4 * k + 3], dv + i * NK + k * 16, 1);
  };
  constexpr uint32_t M0 = SMASK & 15, M1 = (SMASK >> 4) & 15, M2 = (SMASK >> 8) & 15, M3 = SMASK >> 12;
  zero(oa); zero(ob);
  mbar_wait(bars, 0);
  if (first) TS(2, 2);
  float s[NS];
  zero(s);
  uint32_t p0[NP], p1[NP];
  auto step = [&](int i, uint32_t (&pa)[NP], uint32_t ma, uint32_t (&pb)[NP], uint32_t mb) {
    wg_fence(); qk(s, i + 1); wg_commit(); pv(pa, i, ma); wg_commit(); wg_wait<1>(); softmax(s, pb, mb); wg_wait<0>();
  };
  wg_fence(); qk(s, 0); wg_commit(); wg_wait<0>(); softmax(s, p0, M0);
#pragma unroll 1
  for (uint32_t b = bars + 8; b < bars + 64; b += 8) {
    step(0, p0, M0, p1, M1); step(1, p1, M1, p0, M2); step(2, p0, M2, p1, M3);
    mbar_wait(b, 0);
    step(3, p1, M3, p0, M0);
    dk += 4 * NK; dv += 4 * NK;
  }
  step(0, p0, M0, p1, M1); step(1, p1, M1, p0, M2); step(2, p0, M2, p1, M3);
  wg_fence(); pv(p1, 3, M3); wg_commit();
  wg_wait<0>();
  reg_fence(oa); reg_fence(ob);
}
__device__ __forceinline__ void mma16816(float (&d)[4], const uint32_t (&a)[4], uint32_t b0, uint32_t b1) {
  asm("mma.sync.aligned.m16n8k16.row.col.f32.bf16.bf16.f32 {%0,%1,%2,%3},{%4,%5,%6,%7},{%8,%9},{%0,%1,%2,%3};"
      : "+f"(d[0]), "+f"(d[1]), "+f"(d[2]), "+f"(d[3]) : "r"(a[0]), "r"(a[1]), "r"(a[2]), "r"(a[3]), "r"(b0), "r"(b1));
}
__device__ __forceinline__ void attn_safe(float (&o)[12], const uint32_t (&q)[4], uint32_t sK) {
  const int lane = threadIdx.x & 31;
  const uint32_t ka = sK + (lane >> 4) * 32768 + (lane & 15) * 16;
  float m0 = -INFINITY, m1 = -INFINITY;
#pragma unroll 2
  for (int i = 0; i < 128; i++) {
    uint32_t k[4]; ldsm4(ka + i * 256, k);
    float s0[4] = {0, 0, 0, 0}, s1[4] = {0, 0, 0, 0};
    mma16816(s0, q, k[0], k[2]); mma16816(s1, q, k[1], k[3]);
    m0 = fmaxf(fmaxf(m0, fmaxf(s0[0], s0[1])), fmaxf(s1[0], s1[1])); m1 = fmaxf(fmaxf(m1, fmaxf(s0[2], s0[3])), fmaxf(s1[2], s1[3]));
  }
  m0 = fmaxf(m0, __shfl_xor_sync(~0u, m0, 1)); m0 = fmaxf(m0, __shfl_xor_sync(~0u, m0, 2));
  m1 = fmaxf(m1, __shfl_xor_sync(~0u, m1, 1)); m1 = fmaxf(m1, __shfl_xor_sync(~0u, m1, 2));
  float o0[4] = {0, 0, 0, 0}, o1[4] = {0, 0, 0, 0}, o2[4] = {0, 0, 0, 0};
#pragma unroll 2
  for (int i = 0; i < 128; i++) {
    uint32_t k[4], v[4]; ldsm4(ka + i * 256, k);
    asm volatile("ldmatrix.sync.aligned.m8n8.x4.trans.shared.b16 {%0,%1,%2,%3},[%4];" : "=r"(v[0]), "=r"(v[1]), "=r"(v[2]), "=r"(v[3]) : "r"(ka + 65536 + i * 256) : "memory");
    float s0[4] = {0, 0, 0, 0}, s1[4] = {0, 0, 0, 0};
    mma16816(s0, q, k[0], k[2]); mma16816(s1, q, k[1], k[3]);
    const uint32_t p[4] = {pack_rn(ex2(s0[0] - m0), ex2(s0[1] - m0)), pack_rn(ex2(s0[2] - m1), ex2(s0[3] - m1)),
                           pack_rn(ex2(s1[0] - m0), ex2(s1[1] - m0)), pack_rn(ex2(s1[2] - m1), ex2(s1[3] - m1))};
    mma16816(o0, p, v[0], v[1]); mma16816(o1, p, v[2], v[3]); mma16816(o2, p, 0x3F803F80u, 0x3F803F80u);
  }
#pragma unroll
  for (int i = 0; i < 4; i++) { o[i] = o0[i]; o[4 + i] = o1[i]; o[8 + i] = o2[i]; }
}
__global__ void __cluster_dims__(2, 1, 1) __launch_bounds__(512, 1) k_attn(const bf16* wo, const bf16* w1, const bf16* w3, const bf16* w2, const bf16* __restrict__ cv, const bf16* __restrict__ wm, uint32_t kz) {
  extern __shared__ __align__(1024) uint8_t smem[];
  const uint32_t sK = smem_u32(smem), bars = sK + 5 * 32768;
  const int tid = threadIdx.x, warp = tid >> 5, lane = tid & 31, g = lane >> 2, t = lane & 3;
  pdl_launch();
  if (blockIdx.x < 4) {
    float* cs = (float*)smem;
    cs[tid] = silu_bf(cv[tid]);
    cluster_sync();
    const int b = blockIdx.x;
    float *mv = cs + 512, *rd = cs + 1536;
    auto put8 = [&](float* d, float (&a)[8]) { ((float4*)d)[0] = make_float4(a[0], a[1], a[2], a[3]); ((float4*)d)[1] = make_float4(a[4], a[5], a[6], a[7]); };
    for (int ph = 0; ph < 2; ph++) {
      const int nc = 512 >> ph, n0 = ph ? (b >> 1) * 1536 + 1024 + (b & 1) * 256 : 1536 + (b & 1) * 512, nr = 64 >> ph, r0 = tid / nr * nr;
      float a[8] = {0, 0, 0, 0, 0, 0, 0, 0};
#pragma unroll 16
      for (int r = r0; r < r0 + nr; r++) fma8(a, cs[r], __ldg((const uint4*)(wm + r * 3072 + n0 + (tid & (nr - 1)) * 8)));
      put8(rd + tid * 8, a);
      __syncthreads();
      if (tid < nc) {
        float s = 0;
        for (int i = tid; i < 4096; i += nc) s += rd[i];
        s = mod_fin(s, n0 + tid);
        if (ph || b < 2) g_mod[n0 + tid] = s;
        if (!ph) {
          mv[(b & 1) * 512 + tid] = s;
          asm volatile("{\n.reg .b32 r;\nmapa.shared::cluster.u32 r,%0,%1;\nst.shared::cluster.f32 [r],%2;\n}" ::"r"(smem_u32(mv + (b & 1) * 512 + tid)), "r"((b & 1) ^ 1), "f"(s) : "memory");
        }
      }
      cluster_sync();
    }
    if (tid < 430) {
      const bf16* w = (b >> 1 ? w3 : w1) + (b & 1) * 688 + tid % 86 * 8;
      float u[8] = {0, 0, 0, 0, 0, 0, 0, 0}, v[8] = {0, 0, 0, 0, 0, 0, 0, 0};
#pragma unroll 13
      for (int r = tid / 86; r < 512; r += 5) { const uint4 x = __ldg((const uint4*)(w + r * 1376)); fma8(u, mv[512 + r], x); fma8(v, mv[r], x); }
      put8(rd + tid * 8, u); put8(rd + 3440 + tid * 8, v);
    }
    __syncthreads();
    for (int n = tid; n < 688; n += 512) {
      float u = 0, v = 0;
      for (int i = n; i < 3440; i += 688) { u += rd[i]; v += rd[3440 + i]; }
      g_uv[(b >> 1) * 1408 + (b & 1) * 688 + n] = make_float2(u, v);
    }
    TS(0, 7);
    return;
  }
  const int bid = blockIdx.x - 4, h = bid >> 2, qb = bid & 3;
  TS(2, 0);
  if (tid == 0) { for (int i = 0; i < 8; i++) { mbar_init(bars + 8 * i, 1); mbar_expect(bars + 8 * i, 16384); } fence_init(); }
#pragma unroll
  for (int i = 0; i < 4; i++) *(uint4*)(smem + 131072 + i * 8192 + tid * 16) = make_uint4(0x3F803F80u, 0x3F803F80u, 0x3F803F80u, 0x3F803F80u);
  fence_async();
  cluster_sync();
  pdl_wait();
  TS(2, 1);
  if (tid >= 448) g_modv[bid * 64 + tid - 448] = 0;
  const uint4 km4 = *(const uint4*)(g_kmax + h * 128 + lane * 4);
  const uint32_t* qp = (const uint32_t*)g_qkv + (h * 2 * 2048 + qb * 512 + warp * 16 + g) * 4 + t;
  uint32_t q[4] = {qp[0], qp[32], qp[8192], qp[8192 + 32]};
  auto ldkv = [&]() {
    const int c = warp >> 1, pl = (qb & 1) + (warp & 1) * 2;
    bulk_load_mc(sK + pl * 32768 + c * 4096, g_qkv + ((64 + (pl >> 1) * 64 + h * 2 + (pl & 1)) * 2048 + c * 256) * 8, 4096, bars + 8 * c);
  };
  if (lane == 0 && warp < 4) ldkv();
  const uint32_t qn[4] = {qp[1024], qp[1024 + 32], qp[1024 + 8192], qp[1024 + 8192 + 32]};
  const float kmax = __uint_as_float(__reduce_max_sync(~0u, max(max(km4.x, km4.y), max(km4.z, km4.w))));
  if (lane == 0 && warp >= 4 && kmax != -1.f) ldkv();
#pragma unroll 1
  for (int tile = 0; tile < 2; tile++) {
    const int row = qb * 512 + tile * 256 + warp * 16 + g;
    const float n0 = qsum(blo(q[0]) * blo(q[0]) + bhi(q[0]) * bhi(q[0]) + blo(q[2]) * blo(q[2]) + bhi(q[2]) * bhi(q[2]));
    const float n1 = qsum(blo(q[1]) * blo(q[1]) + bhi(q[1]) * bhi(q[1]) + blo(q[3]) * blo(q[3]) + bhi(q[3]) * bhi(q[3]));
    const float b0 = sqrtf(n0 * kmax) * 1.001f, b1 = sqrtf(n1 * kmax) * 1.001f;
    const float m0 = fmaxf(ceilf(b0 - 100.f), 0.f), m1 = fmaxf(ceilf(b1 - 100.f), 0.f);
    float o[12], ob[12];
    attn_pass(o, ob, q, m0, m1, sK, bars, tile == 0, kz);
    const float f0 = ex2(-m0), f1 = ex2(-m1);
#pragma unroll
    for (int i = 0; i < 12; i++) o[i] = fmaf(o[i], (i & 2) ? f1 : f0, ob[i]);
    bool ok = b0 < 220.f && b1 < 220.f && o[8] >= 0x1p-90f && o[10] >= 0x1p-90f;
#pragma unroll
    for (int i = 0; i < 12; i++) ok = ok && fabsf(o[i]) < INFINITY;
    if (!__all_sync(~0u, ok)) attn_safe(o, q, sK);
    const float r0 = 1.f / o[8], r1 = 1.f / o[10];
    uint32_t* op = (uint32_t*)g_o + (((row >> 6) * 64 + h * 2) * 64 + (row & 63)) * 4 + t;
    op[0] = pack_rn(o[0] * r0, o[1] * r0); op[32] = pack_rn(o[2] * r1, o[3] * r1);
    op[256] = pack_rn(o[4] * r0, o[5] * r0); op[256 + 32] = pack_rn(o[6] * r1, o[7] * r1);
    if (tile == 0 && tid == 32) {
      l2_prefetch((const char*)wo + bid * 4096, 4096);
      l2_prefetch((const char*)w1 + bid * 11008, 11008);
      l2_prefetch((const char*)w3 + bid * 11008, 11008);
      l2_prefetch((const char*)w2 + bid * 11008, 11008);
    }
#pragma unroll
    for (int i = 0; i < 4; i++) q[i] = qn[i];
    TS(2, 3 + tile);
  }
}

constexpr int WO_SMEM = 131072 + 65536 + 256;
__global__ void __cluster_dims__(2, 1, 1) __launch_bounds__(288, 1) k_wo(const __grid_constant__ CUtensorMap mW, const bf16* __restrict__ x) {
  extern __shared__ __align__(1024) uint8_t smem[];
  const uint32_t sA = smem_u32(smem), sB = sA + 65536, bars = sB + 131072;
  const int tid = threadIdx.x, warp = tid >> 5, lane = tid & 31, g = lane >> 2, t = lane & 3;
  const int rb = blockIdx.x >> 3, ct = (blockIdx.x & 3) * 2 + ((warp >> 2) & 1);
  TS(3, 0);
  pdl_launch();
  auto loadB = [&](int i) { for (int j = 0; j < 2; j++) tma2d(sB + (j * 8 + i) * 8192, &mW, (ct + j) * 64, i * 64, bars + 64 + 8 * i); };
  int nb = 0;
  if (tid == 256) {
    for (int i = 0; i < 17; i++) mbar_init(bars + 8 * i, 1);
    fence_init();
    for (int i = 0; i < 16; i++) mbar_expect(bars + 8 * i, i < 8 ? 8192 : 16384);
    for (; nb < PD0; nb++) loadB(nb);
  }
  __syncwarp();
  cluster_arrive();
  if (warp == 8) {
    cluster_wait();
    if (lane == 0) {
      for (; nb < 8 && may_preload(bars + 64 + 8 * (nb - PD0), bars + 128); nb++) loadB(nb);
      pdl_wait();
      for (int i = blockIdx.x & 1; i < 8; i += 2) {
        bulk_load_mc(sA + i * 8192, g_o + ((blockIdx.x >> 2) * 64 + i * 8) * 512, 8192, bars + 8 * i);
        for (; nb <= (i | 1); nb++) loadB(nb);
      }
    }
    __syncwarp();
    return;
  }
  const int lrow = (blockIdx.x & 4) * 16 + (warp & 3) * 16 + g;
  uint32_t xr[16];
  const uint32_t* xp = (const uint32_t*)(x + (rb * 128 + lrow) * 512 + ct * 64) + t;
#pragma unroll
  for (int j = 0; j < 8; j++) { xr[2 * j] = __ldg(xp + j * 4); xr[2 * j + 1] = __ldg(xp + j * 4 + 8 * 256); }
  cluster_wait();
  pdl_wait();
  if (tid == 32) mbar_arrive(bars + 128);
  TS(3, 1);
  float2 ga[8];
  uint32_t sc[8];
#pragma unroll
  for (int j = 0; j < 8; j++) {
    ga[j] = *(const float2*)(g_mod + 1024 + ct * 64 + j * 8 + t * 2);
    const float2 v = *(const float2*)(g_mod + 2048 + ct * 64 + j * 8 + t * 2);
    sc[j] = pack_rn(v.x, v.y);
  }
  float acc[32];
  const uint64_t da = mk_desc(sA, 1024, 128, 0), db = mk_desc(sB + (warp >> 2) * 65536, 8192, 1024, 1);
#pragma unroll
  for (int c = 0; c < 8; c++) {
    mbar_wait(bars + 64 + 8 * c, 0); mbar_wait(bars + 8 * c, 0);
    if (c == 0) TS(3, 2);
    wg_fence();
#pragma unroll
    for (int k = 0; k < 4; k++) wgmma_ss_n64_t1(acc, da + (c * 4 + k) * 128, db + (c * 4 + k) * 128, c + k);
    wg_commit();
  }
  wg_wait<0>();
  reg_fence(acc);
  TS(3, 3);
  uint32_t* o = (uint32_t*)g_x1 + ((rb * 64 + ct * 8) * 128 + lrow) * 4 + t;
  uint32_t* oa = (uint32_t*)g_a + ((rb * 64 + ct * 8) * 128 + lrow) * 4 + t;
  float s0 = 0, s1 = 0;
#pragma unroll
  for (int j = 0; j < 8; j++) {
    xr[2 * j] = pack_rn(fmaf(ga[j].x, acc[4 * j], blo(xr[2 * j])), fmaf(ga[j].y, acc[4 * j + 1], bhi(xr[2 * j])));
    xr[2 * j + 1] = pack_rn(fmaf(ga[j].x, acc[4 * j + 2], blo(xr[2 * j + 1])), fmaf(ga[j].y, acc[4 * j + 3], bhi(xr[2 * j + 1])));
    uint32_t a0, a1;
    asm("mul.rn.bf16x2 %0,%1,%2;" : "=r"(a0) : "r"(xr[2 * j]), "r"(sc[j]));
    asm("mul.rn.bf16x2 %0,%1,%2;" : "=r"(a1) : "r"(xr[2 * j + 1]), "r"(sc[j]));
    oa[j * 512] = a0; oa[j * 512 + 32] = a1;
    o[j * 512] = xr[2 * j]; o[j * 512 + 32] = xr[2 * j + 1];
    s0 += blo(xr[2 * j]) + bhi(xr[2 * j]); s1 += blo(xr[2 * j + 1]) + bhi(xr[2 * j + 1]);
  }
  const float m0 = qsum(s0) * (1.f / 64), m1 = qsum(s1) * (1.f / 64);
  float v0 = 0, v1 = 0;
#pragma unroll
  for (int j = 0; j < 8; j++) {
    float d;
    d = blo(xr[2 * j]) - m0; v0 += d * d; d = bhi(xr[2 * j]) - m0; v0 += d * d;
    d = blo(xr[2 * j + 1]) - m1; v1 += d * d; d = bhi(xr[2 * j + 1]) - m1; v1 += d * d;
  }
  v0 = qsum(v0); v1 = qsum(v1);
  if (t == 0) g_st[(rb * 128 + lrow) * 8 + ct] = make_float2(m0, v0);
  if (t == 1) g_st[(rb * 128 + lrow + 8) * 8 + ct] = make_float2(m1, v1);
  TS(3, 4);
}

constexpr int W2_SMEM = 6 * 32768 + 32768 + 256;
__global__ void __cluster_dims__(2, 1, 1) __launch_bounds__(288, 1) k_w2(const __grid_constant__ CUtensorMap mW, bf16* __restrict__ out) {
  extern __shared__ __align__(1024) uint8_t smem[];
  const uint32_t sR = smem_u32(smem), sX = sR + 6 * 32768, bF = sX + 32768, bE = bF + 48, bX = bF + 96, bB = bF + 160, bG = bF + 208;
  const int tid = threadIdx.x, warp = tid >> 5, lane = tid & 31, g = lane >> 2, t = lane & 3;
  const int kh = blockIdx.x & 1, ct = (blockIdx.x >> 1) & 3, rb = blockIdx.x >> 3;
  TS(5, 0);
  pdl_launch();
  if (tid == 256) {
    for (int i = 0; i < 6; i++) { mbar_init(bF + 8 * i, 1); mbar_init(bE + 8 * i, 8); mbar_init(bB + 8 * i, 1); }
    mbar_init(bG, 1);
    for (int i = 0; i < 8; i++) { mbar_init(bX + 8 * i, 1); mbar_expect(bX + 8 * i, 4096); }
    fence_init();
  }
  __syncthreads();
  asm volatile("barrier.cluster.arrive.relaxed.aligned;" ::: "memory");
  if (warp == 8) {
    if (lane == 0) {
      auto abytes = [&](int s) { return (kh == 1 && s == 10) ? 8192 : 16384; };
      auto loadB = [&](int s) {
        const int st = s % 6;
        mbar_expect(bB + 8 * st, 16384);
        for (int j = 0; j < 2; j++) tma2d(sR + st * 32768 + 16384 + j * 8192, &mW, ct * 128 + (j ^ kh) * 64, kh * 704 + s * 64, bB + 8 * st);
      };
      auto loadA = [&](int s) { mbar_expect(bF + 8 * (s % 6), abytes(s)); bulk_load(sR + (s % 6) * 32768, g_h + (rb * 172 + kh * 88 + s * 8) * 1024, abytes(s), bF + 8 * (s % 6)); };
      int nb = 0;
      for (; nb < 6 && (nb < PD2 || may_preload(bB + 8 * (nb - PD2), bG)); nb++) loadB(nb);
      pdl_wait();
      for (int s = 0; s < 6; s++) { loadA(s); if (s >= nb) loadB(s); }
      for (int s = 6; s < 11; s++) { mbar_wait(bE + 8 * (s - 6), 0); loadB(s); loadA(s); }
    }
    __syncwarp();
    cluster_wait();
    return;
  }
  pdl_wait();
  if (tid == 32) mbar_arrive(bG);
  TS(5, 1);
  const int lrow = warp * 16 + g;
  uint32_t xr[16];
  float2 gb[8];
  const uint32_t* xp = (const uint32_t*)g_x1 + ((rb * 64 + ct * 16 + kh * 8) * 128 + lrow) * 4 + t;
#pragma unroll
  for (int j = 0; j < 8; j++) {
    xr[2 * j] = xp[j * 512]; xr[2 * j + 1] = xp[j * 512 + 32];
    gb[j] = *(const float2*)(g_mod + 2560 + ct * 128 + kh * 64 + j * 8 + t * 2);
  }
  float acc[64];
#pragma unroll 1
  for (int s = 0; s < 11; s++) {
    const int st = s % 6;
    mbar_wait(bB + 8 * st, s >= 6); mbar_wait(bF + 8 * st, s >= 6);
    const uint64_t da = mk_desc(sR + st * 32768 + (warp >> 2) * 1024, 2048, 128, 0), db = mk_desc(sR + st * 32768 + 16384, 8192, 1024, 1);
    if (s == 0) TS(5, 2);
    wg_fence();
    wgmma_ss_n128_t1(acc, da, db, s);
    wgmma_ss_n128_t1(acc, da + 256, db + 128, 1);
    wgmma_ss_n128_t1(acc, da + 512, db + 256, 1);
    wgmma_ss_n128_t1(acc, da + 768, db + 384, 1);
    wg_commit();
    wg_wait<1>();
    if (s > 0 && s < 6 && lane == 0) mbar_arrive(bE + 8 * (s - 1));
  }
  wg_wait<0>();
  reg_fence(acc);
  TS(5, 3);
  asm volatile("barrier.cluster.wait.aligned;" ::: "memory");
  uint32_t rem, rbar;
  asm("mapa.shared::cluster.u32 %0,%1,%2;" : "=r"(rbar) : "r"(bX + warp * 8), "r"(kh ^ 1));
  asm("mapa.shared::cluster.u32 %0,%1,%2;" : "=r"(rem) : "r"(sX + warp * 4096 + lane * 16), "r"(kh ^ 1));
#pragma unroll
  for (int j = 0; j < 8; j++) {
    float v[4];
#pragma unroll
    for (int i = 0; i < 4; i++) v[i] = acc[32 + 4 * j + i];
    asm volatile("st.async.weak.shared::cluster.mbarrier::complete_tx::bytes.v4.f32 [%0],{%1,%2,%3,%4},[%5];" ::"r"(rem + j * 512), "f"(v[0]), "f"(v[1]), "f"(v[2]), "f"(v[3]), "r"(rbar) : "memory");
  }
  mbar_wait(bX + warp * 8, 0);
  TS(5, 5);
  const uint32_t sw = sX + warp * 4096;
#pragma unroll
  for (int j = 0; j < 8; j++) {
    const float4 p = *(const float4*)(smem + 6 * 32768 + warp * 4096 + j * 512 + lane * 16);
    xr[2 * j] = pack_rn(fmaf(gb[j].x, acc[4 * j] + p.x, blo(xr[2 * j])), fmaf(gb[j].y, acc[4 * j + 1] + p.y, bhi(xr[2 * j])));
    xr[2 * j + 1] = pack_rn(fmaf(gb[j].x, acc[4 * j + 2] + p.z, blo(xr[2 * j + 1])), fmaf(gb[j].y, acc[4 * j + 3] + p.w, bhi(xr[2 * j + 1])));
  }
  __syncwarp();
#pragma unroll
  for (int j = 1; j < 8; j += 2) {
    asm volatile("stmatrix.sync.aligned.m8n8.x4.shared.b16 [%0],{%1,%2,%3,%4};" ::"r"(sw + (lane & 15) * 128 + (((j - 1 + (lane >> 4)) ^ (lane & 7)) << 4)),
                            "r"(xr[2 * j - 2]), "r"(xr[2 * j - 1]), "r"(xr[2 * j]), "r"(xr[2 * j + 1]) : "memory");
  }
  __syncwarp();
#pragma unroll
  for (int i = 0; i < 4; i++) {
    const int r = i * 4 + (lane >> 3);
    *(uint4*)(out + (rb * 128 + warp * 16 + r) * 512 + ct * 128 + kh * 64 + (lane & 7) * 8) = *(const uint4*)(smem + 6 * 32768 + warp * 4096 + r * 128 + (((lane ^ r) & 7) << 4));
  }
  TS(5, 4);
}

typedef CUresult (*EncFn)(CUtensorMap*, CUtensorMapDataType, cuuint32_t, void*, const cuuint64_t*, const cuuint64_t*, const cuuint32_t*,
                          const cuuint32_t*, CUtensorMapInterleave, CUtensorMapSwizzle, CUtensorMapL2promotion, CUtensorMapFloatOOBfill);
static void mk_map(EncFn f, CUtensorMap* m, const void* p, int rows, int cols, int box_rows) {
  cuuint64_t dim[2] = {(cuuint64_t)cols, (cuuint64_t)rows}, str[1] = {(cuuint64_t)cols * 2};
  cuuint32_t box[2] = {64, (cuuint32_t)box_rows}, es[2] = {1, 1};
  f(m, CU_TENSOR_MAP_DATA_TYPE_BFLOAT16, 2, (void*)p, dim, str, box, es, CU_TENSOR_MAP_INTERLEAVE_NONE, CU_TENSOR_MAP_SWIZZLE_128B,
    CU_TENSOR_MAP_L2_PROMOTION_L2_128B, CU_TENSOR_MAP_FLOAT_OOB_FILL_NONE);
}
template <typename... KA, typename... A>
static void launch(void (*k)(KA...), int grid, int block, int smem, bool pdl, A... args) {
  cudaLaunchConfig_t cfg = {};
  cfg.gridDim = dim3(grid); cfg.blockDim = dim3(block); cfg.dynamicSmemBytes = smem; cfg.stream = cudaStreamPerThread;
  cudaLaunchAttribute at[1];
  at[0].id = cudaLaunchAttributeProgrammaticStreamSerialization; at[0].val.programmaticStreamSerializationAllowed = 1;
  cfg.attrs = at; cfg.numAttrs = pdl ? 1 : 0;
  cudaLaunchKernelEx(&cfg, k, args...);
}
extern "C" void kernel_launch(void* const* d_in, const int* in_sizes, int n_in, void* d_out, int out_size) {
  const bf16 *x = (const bf16*)d_in[0], *wqkv = (const bf16*)d_in[1], *wo = (const bf16*)d_in[2], *w1 = (const bf16*)d_in[4],
             *w3 = (const bf16*)d_in[5], *w2 = (const bf16*)d_in[6], *c = (const bf16*)d_in[7], *wmod = (const bf16*)d_in[8];
  void* fp = nullptr;
  cudaDriverEntryPointQueryResult qr;
  cudaGetDriverEntryPoint("cuTensorMapEncodeTiled", &fp, cudaEnableDefault, &qr);
  EncFn f = (EncFn)fp;
  CUtensorMap mX, mQ, mO, m1, m3, m2;
  mk_map(f, &mX, x, S_, D_, 128); mk_map(f, &mQ, wqkv, D_, 3 * D_, 64); mk_map(f, &mO, wo, D_, D_, 64);
  mk_map(f, &m1, w1, D_, F_, 32); mk_map(f, &m3, w3, D_, F_, 32); mk_map(f, &m2, w2, F_, D_, 64);
  cudaFuncSetAttribute(k_lngemm<false>, cudaFuncAttributeMaxDynamicSharedMemorySize, LN_SMEM);
  cudaFuncSetAttribute(k_lngemm<true>, cudaFuncAttributeMaxDynamicSharedMemorySize, LN_SMEM);
  cudaFuncSetAttribute(k_attn, cudaFuncAttributeMaxDynamicSharedMemorySize, AT_SMEM);
  cudaFuncSetAttribute(k_wo, cudaFuncAttributeMaxDynamicSharedMemorySize, WO_SMEM);
  cudaFuncSetAttribute(k_w2, cudaFuncAttributeMaxDynamicSharedMemorySize, W2_SMEM);
  launch(k_lngemm<false>, 128, 384, LN_SMEM, false, mX, mQ, mQ, c, wmod, x, wqkv);
  launch(k_attn, 132, 512, AT_SMEM, true, wo, w1, w3, w2, c, wmod, 0u);
  launch(k_wo, 128, 288, WO_SMEM, true, mO, x);
  launch(k_lngemm<true>, 128, 384, LN_SMEM, true, mX, m1, m3, c, wmod, x, wqkv);
  launch(k_w2, 128, 288, W2_SMEM, true, m2, (bf16*)d_out);
}
```

```cpp
#include <cuda_runtime.h>
#include <cuda_bf16.h>
#include <cuda.h>
#include <stdint.h>
typedef __nv_bfloat16 bf16;
constexpr int S_ = 2048, D_ = 512, F_ = 1376;
__device__ __align__(1024) float g_mod[3072];
__device__ __align__(1024) uint32_t g_modv[4096 + 4096];
__device__ __align__(1024) bf16 g_qkv[192 * 2048 * 8];
__device__ __align__(1024) float g_kmax[32 * 128];
__device__ __align__(1024) bf16 g_o[16 * 64 * 128 * 8];
__device__ __align__(1024) bf16 g_x1[16 * 64 * 128 * 8];
__device__ __align__(1024) bf16 g_a[16 * 64 * 128 * 8];
__device__ __align__(1024) float2 g_uv[2 * 1408];
__device__ __align__(1024) float2 g_st[2048 * 8];
__device__ __align__(1024) bf16 g_h[16 * 172 * 128 * 8];

__device__ __forceinline__ uint32_t smem_u32(const void* p) { return (uint32_t)__cvta_generic_to_shared(p); }
__device__ __forceinline__ void mbar_init(uint32_t b, int n) { asm volatile("mbarrier.init.shared::cta.b64 [%0],%1;" ::"r"(b), "r"(n) : "memory"); }
__device__ __forceinline__ void mbar_expect(uint32_t b, int bytes) { asm volatile("mbarrier.arrive.expect_tx.shared::cta.b64 _,[%0],%1;" ::"r"(b), "r"(bytes) : "memory"); }
__device__ __forceinline__ void mbar_arrive(uint32_t b) { asm volatile("mbarrier.arrive.shared::cta.b64 _,[%0];" ::"r"(b) : "memory"); }
__device__ __forceinline__ void mbar_wait(uint32_t b, int parity) {
  asm volatile("{\n.reg .pred p;\n.reg .u32 n;\nmov.u32 n,0;\nLW:\nmbarrier.try_wait.parity.shared::cta.b64 p,[%0],%1;\n@p bra LD;\n"
               "add.u32 n,n,1;\nsetp.lt.u32 p,n,4194304;\n@p bra LW;\nLD:\n}\n" ::"r"(b), "r"(parity) : "memory");
}
__device__ __forceinline__ void fence_init() { asm volatile("fence.mbarrier_init.release.cluster;" ::: "memory"); }
__device__ __forceinline__ void fence_async() { asm volatile("fence.proxy.async.shared::cta;" ::: "memory"); }
__device__ __forceinline__ void bulk_load(uint32_t dst, const void* src, int bytes, uint32_t bar) {
  asm volatile("cp.async.bulk.shared::cluster.global.mbarrier::complete_tx::bytes [%0],[%1],%2,[%3];" ::"r"(dst), "l"(src), "r"(bytes), "r"(bar) : "memory");
}
__device__ __forceinline__ void tma2d(uint32_t dst, const CUtensorMap* m, int c0, int c1, uint32_t bar) {
  asm volatile("cp.async.bulk.tensor.2d.shared::cluster.global.mbarrier::complete_tx::bytes [%0],[%1,{%3,%4}],[%2];" ::"r"(dst), "l"(m), "r"(bar), "r"(c0), "r"(c1) : "memory");
}
__device__ __forceinline__ void bulk_load_mc(uint32_t dst, const void* src, int bytes, uint32_t bar) {
  asm volatile("cp.async.bulk.shared::cluster.global.mbarrier::complete_tx::bytes.multicast::cluster [%0],[%1],%2,[%3],%4;" ::"r"(dst), "l"(src), "r"(bytes), "r"(bar), "h"((uint16_t)3) : "memory");
}
__device__ __forceinline__ void tma2d_mc(uint32_t dst, const CUtensorMap* m, int c0, int c1, uint32_t bar) {
  asm volatile("cp.async.bulk.tensor.2d.shared::cluster.global.mbarrier::complete_tx::bytes.multicast::cluster [%0],[%1,{%3,%4}],[%2],%5;" ::"r"(dst), "l"(m), "r"(bar), "r"(c0), "r"(c1), "h"((uint16_t)3) : "memory");
}
__device__ __forceinline__ void cluster_arrive() { asm volatile("barrier.cluster.arrive.relaxed.aligned;" ::: "memory"); }
__device__ __forceinline__ void cluster_wait() { asm volatile("barrier.cluster.wait.aligned;" ::: "memory"); }
__device__ __forceinline__ void cluster_sync() { asm volatile("barrier.cluster.arrive.release.aligned;\nbarrier.cluster.wait.acquire.aligned;" ::: "memory"); }
__device__ __forceinline__ bool mbar_test(uint32_t b, uint32_t ph) {
  uint32_t ok; asm volatile("{\n.reg .pred p;\nmbarrier.test_wait.parity.shared::cta.b64 p,[%1],%2;\nselp.u32 %0,1,0,p;\n}" : "=r"(ok) : "r"(b), "r"(ph) : "memory"); return ok;
}
__device__ __forceinline__ bool may_preload(uint32_t landed, uint32_t go) {
  for (int i = 0; i < 100000; i++) { if (mbar_test(go, 0)) return false; if (mbar_test(landed, 0)) return true; }
  return false;
}
#define PD1 1
#define PD0 2
#define PD2 1
__device__ __forceinline__ void l2_prefetch(const void* p, int bytes) { asm volatile("cp.async.bulk.prefetch.L2.global [%0],%1;" ::"l"(p), "r"(bytes) : "memory"); }
__device__ __forceinline__ void pdl_launch() { asm volatile("griddepcontrol.launch_dependents;" ::: "memory"); }
__device__ __forceinline__ void pdl_wait() { asm volatile("griddepcontrol.wait;" ::: "memory"); }
__device__ __forceinline__ void wg_fence() { asm volatile("wgmma.fence.sync.aligned;" ::: "memory"); }
__device__ __forceinline__ void wg_commit() { asm volatile("wgmma.commit_group.sync.aligned;" ::: "memory"); }
template <int N> __device__ __forceinline__ void wg_wait() { asm volatile("wgmma.wait_group.sync.aligned %0;" ::"n"(N) : "memory"); }
template <int N> __device__ __forceinline__ void reg_fence(float (&d)[N]) {
#pragma unroll
  for (int i = 0; i < N; i++) asm volatile("" : "+f"(d[i])::"memory");
}
template <int N> __device__ __forceinline__ void zero(float (&d)[N]) {
#pragma unroll
  for (int i = 0; i < N; i++) d[i] = 0.f;
  reg_fence(d);
}
__device__ __forceinline__ uint64_t mk_desc(uint32_t addr, uint32_t lbo, uint32_t sbo, uint32_t mode) {
  return (uint64_t)((addr >> 4) & 0x3FFF) | ((uint64_t)(lbo >> 4) << 16) | ((uint64_t)(sbo >> 4) << 32) | ((uint64_t)mode << 62);
}
__device__ __forceinline__ void ldsm4(uint32_t a, uint32_t (&r)[4]) {
  asm volatile("ldmatrix.sync.aligned.m8n8.x4.shared.b16 {%0,%1,%2,%3},[%4];" : "=r"(r[0]), "=r"(r[1]), "=r"(r[2]), "=r"(r[3]) : "r"(a) : "memory");
}
__device__ __forceinline__ uint32_t pack_rn(float lo, float hi) { uint32_t r; asm("cvt.rn.bf16x2.f32 %0,%1,%2;" : "=r"(r) : "f"(hi), "f"(lo)); return r; }
__device__ __forceinline__ uint32_t pack_rz(float lo, float hi) { uint32_t r; asm("cvt.rz.bf16x2.f32 %0,%1,%2;" : "=r"(r) : "f"(hi), "f"(lo)); return r; }
__device__ __forceinline__ float blo(uint32_t u) { return __uint_as_float(u << 16); }
__device__ __forceinline__ float bhi(uint32_t u) { return __uint_as_float(u & 0xFFFF0000u); }
__device__ __forceinline__ float rbf(float x) { return __bfloat162float(__float2bfloat16_rn(x)); }
__device__ __forceinline__ float qsum(float v) { v += __shfl_xor_sync(~0u, v, 1); return v + __shfl_xor_sync(~0u, v, 2); }
__device__ __forceinline__ float ex2(float x) { float r; asm("ex2.approx.ftz.f32 %0,%1;" : "=f"(r) : "f"(x)); return r; }
#define TS(k, i)
__device__ __forceinline__ void wgmma_rs_n176_t1(float (&d)[88],uint32_t a0,uint32_t a1,uint32_t a2,uint32_t a3,uint64_t db,int sc){
  asm volatile("{\n.reg .pred p;\nsetp.ne.b32 p,%93,0;\n"
    "wgmma.mma_async.sync.aligned.m64n176k16.f32.bf16.bf16 {%0,%1,%2,%3,%4,%5,%6,%7,%8,%9,%10,%11,%12,%13,%14,%15,%16,%17,%18,%19,%20,%21,%22,%23,%24,%25,%26,%27,%28,%29,%30,%31,%32,%33,%34,%35,%36,%37,%38,%39,%40,%41,%42,%43,%44,%45,%46,%47,%48,%49,%50,%51,%52,%53,%54,%55,%56,%57,%58,%59,%60,%61,%62,%63,%64,%65,%66,%67,%68,%69,%70,%71,%72,%73,%74,%75,%76,%77,%78,%79,%80,%81,%82,%83,%84,%85,%86,%87},{%88,%89,%90,%91},%92,p,1,1,1;\n}\n"
    :"+f"(d[0]),"+f"(d[1]),"+f"(d[2]),"+f"(d[3]),"+f"(d[4]),"+f"(d[5]),"+f"(d[6]),"+f"(d[7]),"+f"(d[8]),"+f"(d[9]),"+f"(d[10]),"+f"(d[11]),"+f"(d[12]),"+f"(d[13]),"+f"(d[14]),"+f"(d[15]),"+f"(d[16]),"+f"(d[17]),"+f"(d[18]),"+f"(d[19]),"+f"(d[20]),"+f"(d[21]),"+f"(d[22]),"+f"(d[23]),"+f"(d[24]),"+f"(d[25]),"+f"(d[26]),"+f"(d[27]),"+f"(d[28]),"+f"(d[29]),"+f"(d[30]),"+f"(d[31]),"+f"(d[32]),"+f"(d[33]),"+f"(d[34]),"+f"(d[35]),"+f"(d[36]),"+f"(d[37]),"+f"(d[38]),"+f"(d[39]),"+f"(d[40]),"+f"(d[41]),"+f"(d[42]),"+f"(d[43]),"+f"(d[44]),"+f"(d[45]),"+f"(d[46]),"+f"(d[47]),"+f"(d[48]),"+f"(d[49]),"+f"(d[50]),"+f"(d[51]),"+f"(d[52]),"+f"(d[53]),"+f"(d[54]),"+f"(d[55]),"+f"(d[56]),"+f"(d[57]),"+f"(d[58]),"+f"(d[59]),"+f"(d[60]),"+f"(d[61]),"+f"(d[62]),"+f"(d[63]),"+f"(d[64]),"+f"(d[65]),"+f"(d[66]),"+f"(d[67]),"+f"(d[68]),"+f"(d[69]),"+f"(d[70]),"+f"(d[71]),"+f"(d[72]),"+f"(d[73]),"+f"(d[74]),"+f"(d[75]),"+f"(d[76]),"+f"(d[77]),"+f"(d[78]),"+f"(d[79]),"+f"(d[80]),"+f"(d[81]),"+f"(d[82]),"+f"(d[83]),"+f"(d[84]),"+f"(d[85]),"+f"(d[86]),"+f"(d[87])
    :"r"(a0),"r"(a1),"r"(a2),"r"(a3),"l"(db),"r"(sc));
}
__device__ __forceinline__ void wgmma_rs_n192_t1(float (&d)[96],uint32_t a0,uint32_t a1,uint32_t a2,uint32_t a3,uint64_t db,int sc){
  asm volatile("{\n.reg .pred p;\nsetp.ne.b32 p,%101,0;\n"
    "wgmma.mma_async.sync.aligned.m64n192k16.f32.bf16.bf16 {%0,%1,%2,%3,%4,%5,%6,%7,%8,%9,%10,%11,%12,%13,%14,%15,%16,%17,%18,%19,%20,%21,%22,%23,%24,%25,%26,%27,%28,%29,%30,%31,%32,%33,%34,%35,%36,%37,%38,%39,%40,%41,%42,%43,%44,%45,%46,%47,%48,%49,%50,%51,%52,%53,%54,%55,%56,%57,%58,%59,%60,%61,%62,%63,%64,%65,%66,%67,%68,%69,%70,%71,%72,%73,%74,%75,%76,%77,%78,%79,%80,%81,%82,%83,%84,%85,%86,%87,%88,%89,%90,%91,%92,%93,%94,%95},{%96,%97,%98,%99},%100,p,1,1,1;\n}\n"
    :"+f"(d[0]),"+f"(d[1]),"+f"(d[2]),"+f"(d[3]),"+f"(d[4]),"+f"(d[5]),"+f"(d[6]),"+f"(d[7]),"+f"(d[8]),"+f"(d[9]),"+f"(d[10]),"+f"(d[11]),"+f"(d[12]),"+f"(d[13]),"+f"(d[14]),"+f"(d[15]),"+f"(d[16]),"+f"(d[17]),"+f"(d[18]),"+f"(d[19]),"+f"(d[20]),"+f"(d[21]),"+f"(d[22]),"+f"(d[23]),"+f"(d[24]),"+f"(d[25]),"+f"(d[26]),"+f"(d[27]),"+f"(d[28]),"+f"(d[29]),"+f"(d[30]),"+f"(d[31]),"+f"(d[32]),"+f"(d[33]),"+f"(d[34]),"+f"(d[35]),"+f"(d[36]),"+f"(d[37]),"+f"(d[38]),"+f"(d[39]),"+f"(d[40]),"+f"(d[41]),"+f"(d[42]),"+f"(d[43]),"+f"(d[44]),"+f"(d[45]),"+f"(d[46]),"+f"(d[47]),"+f"(d[48]),"+f"(d[49]),"+f"(d[50]),"+f"(d[51]),"+f"(d[52]),"+f"(d[53]),"+f"(d[54]),"+f"(d[55]),"+f"(d[56]),"+f"(d[57]),"+f"(d[58]),"+f"(d[59]),"+f"(d[60]),"+f"(d[61]),"+f"(d[62]),"+f"(d[63]),"+f"(d[64]),"+f"(d[65]),"+f"(d[66]),"+f"(d[67]),"+f"(d[68]),"+f"(d[69]),"+f"(d[70]),"+f"(d[71]),"+f"(d[72]),"+f"(d[73]),"+f"(d[74]),"+f"(d[75]),"+f"(d[76]),"+f"(d[77]),"+f"(d[78]),"+f"(d[79]),"+f"(d[80]),"+f"(d[81]),"+f"(d[82]),"+f"(d[83]),"+f"(d[84]),"+f"(d[85]),"+f"(d[86]),"+f"(d[87]),"+f"(d[88]),"+f"(d[89]),"+f"(d[90]),"+f"(d[91]),"+f"(d[92]),"+f"(d[93]),"+f"(d[94]),"+f"(d[95])
    :"r"(a0),"r"(a1),"r"(a2),"r"(a3),"l"(db),"r"(sc));
}
__device__ __forceinline__ void wgmma_rs_n24_t1(float (&d)[12],uint32_t a0,uint32_t a1,uint32_t a2,uint32_t a3,uint64_t db,int sc){
  asm volatile("{\n.reg .pred p;\nsetp.ne.b32 p,%17,0;\n"
    "wgmma.mma_async.sync.aligned.m64n24k16.f32.bf16.bf16 {%0,%1,%2,%3,%4,%5,%6,%7,%8,%9,%10,%11},{%12,%13,%14,%15},%16,p,1,1,1;\n}\n"
    :"+f"(d[0]),"+f"(d[1]),"+f"(d[2]),"+f"(d[3]),"+f"(d[4]),"+f"(d[5]),"+f"(d[6]),"+f"(d[7]),"+f"(d[8]),"+f"(d[9]),"+f"(d[10]),"+f"(d[11])
    :"r"(a0),"r"(a1),"r"(a2),"r"(a3),"l"(db),"r"(sc));
}
__device__ __forceinline__ void wgmma_rs_n64_t0(float (&d)[32],uint32_t a0,uint32_t a1,uint32_t a2,uint32_t a3,uint64_t db,int sc){
  asm volatile("{\n.reg .pred p;\nsetp.ne.b32 p,%37,0;\n"
    "wgmma.mma_async.sync.aligned.m64n64k16.f32.bf16.bf16 {%0,%1,%2,%3,%4,%5,%6,%7,%8,%9,%10,%11,%12,%13,%14,%15,%16,%17,%18,%19,%20,%21,%22,%23,%24,%25,%26,%27,%28,%29,%30,%31},{%32,%33,%34,%35},%36,p,1,1,0;\n}\n"
    :"+f"(d[0]),"+f"(d[1]),"+f"(d[2]),"+f"(d[3]),"+f"(d[4]),"+f"(d[5]),"+f"(d[6]),"+f"(d[7]),"+f"(d[8]),"+f"(d[9]),"+f"(d[10]),"+f"(d[11]),"+f"(d[12]),"+f"(d[13]),"+f"(d[14]),"+f"(d[15]),"+f"(d[16]),"+f"(d[17]),"+f"(d[18]),"+f"(d[19]),"+f"(d[20]),"+f"(d[21]),"+f"(d[22]),"+f"(d[23]),"+f"(d[24]),"+f"(d[25]),"+f"(d[26]),"+f"(d[27]),"+f"(d[28]),"+f"(d[29]),"+f"(d[30]),"+f"(d[31])
    :"r"(a0),"r"(a1),"r"(a2),"r"(a3),"l"(db),"r"(sc));
}
__device__ __forceinline__ void wgmma_ss_n128_t1(float (&d)[64],uint64_t da,uint64_t db,int sc){
  asm volatile("{\n.reg .pred p;\nsetp.ne.b32 p,%66,0;\n"
    "wgmma.mma_async.sync.aligned.m64n128k16.f32.bf16.bf16 {%0,%1,%2,%3,%4,%5,%6,%7,%8,%9,%10,%11,%12,%13,%14,%15,%16,%17,%18,%19,%20,%21,%22,%23,%24,%25,%26,%27,%28,%29,%30,%31,%32,%33,%34,%35,%36,%37,%38,%39,%40,%41,%42,%43,%44,%45,%46,%47,%48,%49,%50,%51,%52,%53,%54,%55,%56,%57,%58,%59,%60,%61,%62,%63},%64,%65,p,1,1,0,1;\n}\n"
    :"+f"(d[0]),"+f"(d[1]),"+f"(d[2]),"+f"(d[3]),"+f"(d[4]),"+f"(d[5]),"+f"(d[6]),"+f"(d[7]),"+f"(d[8]),"+f"(d[9]),"+f"(d[10]),"+f"(d[11]),"+f"(d[12]),"+f"(d[13]),"+f"(d[14]),"+f"(d[15]),"+f"(d[16]),"+f"(d[17]),"+f"(d[18]),"+f"(d[19]),"+f"(d[20]),"+f"(d[21]),"+f"(d[22]),"+f"(d[23]),"+f"(d[24]),"+f"(d[25]),"+f"(d[26]),"+f"(d[27]),"+f"(d[28]),"+f"(d[29]),"+f"(d[30]),"+f"(d[31]),"+f"(d[32]),"+f"(d[33]),"+f"(d[34]),"+f"(d[35]),"+f"(d[36]),"+f"(d[37]),"+f"(d[38]),"+f"(d[39]),"+f"(d[40]),"+f"(d[41]),"+f"(d[42]),"+f"(d[43]),"+f"(d[44]),"+f"(d[45]),"+f"(d[46]),"+f"(d[47]),"+f"(d[48]),"+f"(d[49]),"+f"(d[50]),"+f"(d[51]),"+f"(d[52]),"+f"(d[53]),"+f"(d[54]),"+f"(d[55]),"+f"(d[56]),"+f"(d[57]),"+f"(d[58]),"+f"(d[59]),"+f"(d[60]),"+f"(d[61]),"+f"(d[62]),"+f"(d[63])
    :"l"(da),"l"(db),"r"(sc));
}
__device__ __forceinline__ void wgmma_ss_n64_t1(float (&d)[32],uint64_t da,uint64_t db,int sc){
  asm volatile("{\n.reg .pred p;\nsetp.ne.b32 p,%34,0;\n"
    "wgmma.mma_async.sync.aligned.m64n64k16.f32.bf16.bf16 {%0,%1,%2,%3,%4,%5,%6,%7,%8,%9,%10,%11,%12,%13,%14,%15,%16,%17,%18,%19,%20,%21,%22,%23,%24,%25,%26,%27,%28,%29,%30,%31},%32,%33,p,1,1,0,1;\n}\n"
    :"+f"(d[0]),"+f"(d[1]),"+f"(d[2]),"+f"(d[3]),"+f"(d[4]),"+f"(d[5]),"+f"(d[6]),"+f"(d[7]),"+f"(d[8]),"+f"(d[9]),"+f"(d[10]),"+f"(d[11]),"+f"(d[12]),"+f"(d[13]),"+f"(d[14]),"+f"(d[15]),"+f"(d[16]),"+f"(d[17]),"+f"(d[18]),"+f"(d[19]),"+f"(d[20]),"+f"(d[21]),"+f"(d[22]),"+f"(d[23]),"+f"(d[24]),"+f"(d[25]),"+f"(d[26]),"+f"(d[27]),"+f"(d[28]),"+f"(d[29]),"+f"(d[30]),"+f"(d[31])
    :"l"(da),"l"(db),"r"(sc));
}

__device__ __forceinline__ float silu_bf(bf16 c) { const float x = __bfloat162float(c); return rbf(x / (1.f + __expf(-x))); }
__device__ __forceinline__ void fma8(float (&a)[8], float s, const uint4& v) {
  a[0] += s * blo(v.x); a[1] += s * bhi(v.x); a[2] += s * blo(v.y); a[3] += s * bhi(v.y);
  a[4] += s * blo(v.z); a[5] += s * bhi(v.z); a[6] += s * blo(v.w); a[7] += s * bhi(v.w);
}
__device__ __forceinline__ float red8(float (&a)[8], int lane) {
#pragma unroll
  for (int w = 4; w >= 1; w >>= 1) {
    const bool up = lane & (w * 4);
#pragma unroll
    for (int j = 0; j < w; j++) a[j] = (up ? a[j + w] : a[j]) + __shfl_xor_sync(~0u, up ? a[j] : a[j + w], w * 4);
  }
  return a[0];
}
__device__ __forceinline__ float mod_fin(float s, int n) { s = rbf(s); return ((n >> 9) == 1 || (n >> 9) == 4) ? rbf(1.f + s) : s; }
__device__ __forceinline__ void poll(uint2& a, uint2& b, float (&w)[16], const uint32_t* p, const uint32_t* q) {
  asm volatile("{\n.reg .pred p;\n.reg .b32 n,t,u;\nmov.u32 n,0;\nLW:\nld.relaxed.gpu.global.v2.u32 {%0,%1},[%20];\nld.relaxed.gpu.global.v2.u32 {%2,%3},[%20+64];\n"
               "ld.relaxed.gpu.global.v4.f32 {%4,%5,%6,%7},[%21];\nld.relaxed.gpu.global.v4.f32 {%8,%9,%10,%11},[%21+16];\n"
               "ld.relaxed.gpu.global.v4.f32 {%12,%13,%14,%15},[%21+8192];\nld.relaxed.gpu.global.v4.f32 {%16,%17,%18,%19},[%21+8208];\n"
               "lop3.b32 t,%0,%1,%2,0x80;\nlop3.b32 u,%3,%4,%5,0x80;\nlop3.b32 t,t,%6,%7,0x80;\nlop3.b32 u,u,%8,%9,0x80;\nlop3.b32 t,t,%10,%11,0x80;\n"
               "lop3.b32 u,u,%12,%13,0x80;\nlop3.b32 t,t,%14,%15,0x80;\nlop3.b32 u,u,%16,%17,0x80;\nlop3.b32 t,t,%18,%19,0x80;\nlop3.b32 t,t,u,1,0x80;\n"
               "setp.ne.u32 p,t,0;\n@p bra LD;\nadd.u32 n,n,1;\nsetp.lt.u32 p,n,1048576;\n@p bra LW;\nLD:\n}\n"
               : "=&r"(a.x), "=&r"(a.y), "=&r"(b.x), "=&r"(b.y), "=&f"(w[0]), "=&f"(w[1]), "=&f"(w[2]), "=&f"(w[3]), "=&f"(w[4]), "=&f"(w[5]), "=&f"(w[6]), "=&f"(w[7]),
                 "=&f"(w[8]), "=&f"(w[9]), "=&f"(w[10]), "=&f"(w[11]), "=&f"(w[12]), "=&f"(w[13]), "=&f"(w[14]), "=&f"(w[15]) : "l"(p), "l"(q) : "memory");
}

constexpr int LN_SMEM = 131072 + 4 * 24576 + 2816 + 256;
#define TANH 1
#define DLY 2
template <bool FFN>
__global__ void __cluster_dims__(2, 1, 1) __launch_bounds__(384, 1) k_lngemm(const __grid_constant__ CUtensorMap mX, const __grid_constant__ CUtensorMap mB0,
                                                   const __grid_constant__ CUtensorMap mB1, const bf16* __restrict__ cv, const bf16* __restrict__ wm, const bf16* __restrict__ xg, const bf16* wq) {
  extern __shared__ __align__(1024) uint8_t smem[];
  const uint32_t sA = smem_u32(smem), sB = sA + (FFN ? 81920 : 131072), sM = sA + 229376, bars = sM + 2816;
  const uint32_t bA = bars, bF = bars + 64, bE = bars + 112;
  constexpr int NB = FFN ? 6 : 4;
  const int tid = threadIdx.x, warp = tid >> 5, lane = tid & 31;
  const int pr = blockIdx.x & 1, rb = FFN ? (blockIdx.x >> 4) * 2 + pr : blockIdx.x >> 3, ct = FFN ? (blockIdx.x >> 1) & 7 : blockIdx.x & 7;
  constexpr int NST = FFN ? 16 : 8, KS = FFN ? 2 : 4, BOX = FFN ? 4096 : 8192;
  TS(FFN ? 4 : 1, 0);
  if (!FFN) pdl_launch();
  float* red = (float*)(smem + (sM - sA));
  if (tid == 256) {
    for (int i = 0; i < 8; i++) mbar_init(bA + 8 * i, 1);
    for (int i = 0; i < NB; i++) { mbar_init(bF + 8 * i, 1); mbar_init(bE + 8 * i, FFN ? 16 : 8); }
    mbar_init(bars + 160, 1);
    fence_init();
  }
  __syncwarp();
  cluster_arrive();
  uint4 wv0, wv1, xv[4];
  bf16 cv0, cv1;
  if (!FFN && tid < 256) {
    const int r = (blockIdx.x & 3) * 128 + (tid >> 2);
    const uint4* wp = (const uint4*)(wm + r * 3072 + (blockIdx.x >> 2) * 32 + (tid & 3) * 8);
    wv0 = __ldg(wp); wv1 = __ldg(wp + 64 * 384);
    cv0 = cv[r]; cv1 = cv[r + 64];
#pragma unroll
    for (int i = 0; i < 4; i++) xv[i] = __ldg((const uint4*)(xg + (blockIdx.x * 16 + (tid >> 4)) * 512 + i * 128 + (tid & 15) * 8));
  }
  cluster_wait();
  if (warp >= 8) {
    asm volatile("setmaxnreg.dec.sync.aligned.u32 40;");
    if (tid == 256) {
      auto loadB = [&](int s) {
        const uint32_t d = sB + (s % NB) * 24576, b = bF + (s % NB) * 8;
        mbar_expect(b, 24576);
        for (int j = 0; j < 3; j++) {
          if (FFN) tma2d_mc(d + (pr * 3 + j) * BOX, pr ? &mB1 : &mB0, ct * 176 + j * 64, s * 32, b);
          else tma2d(d + j * BOX, &mB0, ct * 192 + j * 64, s * 64, b);
        }
      };
      for (int i = 0; i < 8; i++) mbar_expect(bA + 8 * i, 16384);
      if (!FFN) l2_prefetch((const char*)wq + blockIdx.x * 12288, 12288);
      int nb = 0;
      for (int s = 0; s < NB; s++, nb++) {
        const int i = s * 2 + (ct & 1);
        if (FFN && s >= PD1 && !may_preload(bF + (s - PD1) * 8, bars + 160)) break;
        if (!FFN && s == DLY) mbar_wait(bars + 160, 0);
        if (!FFN) tma2d_mc(sA + i * 16384, &mX, i * 64, rb * 128, bA + 8 * i);
        loadB(s);
      }
      if (FFN) {
        pdl_wait();
        for (int i = 0; i < 5; i++) {
          bulk_load(sA + i * 16384, g_a + (rb * 64 + i * 8) * 1024, 16384, bA + 8 * i);
          for (; nb < 2 * i + 2 && nb < NB; nb++) loadB(nb);
        }
      }
      for (int s = NB; s < NST; s++) {
        mbar_wait(bE + (s % NB) * 8, (s / NB - 1) & 1); loadB(s);
        if (FFN && s <= 10 && !(s & 1)) bulk_load(sA + (s / 2 - 3) * 16384, g_a + (rb * 64 + (s / 2 + 2) * 8) * 1024, 16384, bA + 8 * (s / 2 + 2));
      }
    }
  } else {
  asm volatile("setmaxnreg.inc.sync.aligned.u32 232;");
  const int g = lane >> 2, t = lane & 3;
  const int lr = warp * 16 + (lane & 7) + ((lane >> 3) & 1) * 8;
  auto aaddr = [&](int ks) -> uint32_t {
    if (FFN) return sA + ((ks < 20 ? ks : ks - 20) * 2 + (lane >> 4)) * 2048 + lr * 16;
    return sA + (ks >> 2) * 16384 + lr * 128 + ((((ks & 3) * 2 + (lane >> 4)) ^ (lr & 7)) << 4);
  };
  const int row0 = rb * 128 + warp * 16 + g;
  float2 msh, msc;
  float4 p0, p1, uv;
  float rs0, rs1, nm0, nm1;
  if (!FFN) {
    {
      float a[8] = {0, 0, 0, 0, 0, 0, 0, 0};
      fma8(a, silu_bf(cv0), wv0); fma8(a, silu_bf(cv1), wv1);
      red[warp * 32 + t * 8 + g] = red8(a, lane);
      asm volatile("bar.sync 1,256;" ::: "memory");
      if (tid < 32) {
        float r = 0;
#pragma unroll
        for (int i = 0; i < 8; i++) r += red[i * 32 + tid];
        asm volatile("st.relaxed.gpu.global.u32 [%0],%1;" ::"l"(g_modv + ((blockIdx.x >> 2) * 32 + tid) * 4 + (blockIdx.x & 3)), "r"(__float_as_uint(r) | 1u) : "memory");
      }
      TS(0, 1);
    }
    {
      float v[32], s = 0, q = 0;
#pragma unroll
      for (int i = 0; i < 16; i++) { const uint32_t u = ((const uint32_t*)xv)[i]; v[2 * i] = blo(u); v[2 * i + 1] = bhi(u); s += v[2 * i] + v[2 * i + 1]; }
      s = qsum(s); s += __shfl_xor_sync(~0u, s, 4); s += __shfl_xor_sync(~0u, s, 8);
      const float m = s * (1.f / 512);
#pragma unroll
      for (int i = 0; i < 32; i++) q += (v[i] - m) * (v[i] - m);
      q = qsum(q); q += __shfl_xor_sync(~0u, q, 4); q += __shfl_xor_sync(~0u, q, 8);
      const float rs = rsqrtf(q * (1.f / 512) + 1e-5f);
      if ((tid & 15) == 0)
        asm volatile("st.relaxed.gpu.global.v2.u32 [%0],{%1,%2};" ::"l"(g_modv + 4096 + (blockIdx.x * 16 + (tid >> 4)) * 2), "r"(__float_as_uint(rs) | 1u), "r"(__float_as_uint(-m * rs) | 1u) : "memory");
    }
    uint2 q0, q1;
    float w[16];
    if (tid < 128) {
      uint32_t v; int n = 0;
      do asm volatile("ld.relaxed.gpu.global.u32 %0,[%1];" : "=r"(v) : "l"(g_modv + (tid >> 2) * 128 + (tid & 3)) : "memory"); while (!(v & 1) && ++n < 1048576);
    }
    asm volatile("bar.sync 1,256;" ::: "memory");
    poll(q0, q1, w, g_modv + 4096 + row0 * 2, g_modv + tid * 8);
    msh = make_float2(mod_fin(w[0] + w[1] + w[2] + w[3], 0), mod_fin(w[4] + w[5] + w[6] + w[7], 0));
    msc = make_float2(mod_fin(w[8] + w[9] + w[10] + w[11], 512), mod_fin(w[12] + w[13] + w[14] + w[15], 512));
    asm volatile("bar.sync 1,256;" ::: "memory");
    if (tid == 32) mbar_arrive(bars + 160);
    rs0 = __uint_as_float(q0.x); nm0 = __uint_as_float(q0.y); rs1 = __uint_as_float(q1.x); nm1 = __uint_as_float(q1.y);
  } else {
    pdl_wait();
    pdl_launch();
    if (tid == 32) mbar_arrive(bars + 160);
    TS(4, 1);
    p0 = *(const float4*)(g_st + row0 * 8 + t * 2); p1 = *(const float4*)(g_st + (row0 + 8) * 8 + t * 2);
    if (tid < 176) uv = *(const float4*)(g_uv + (tid >= 88 ? 1408 - 176 : 0) + ct * 176 + tid * 2);
  }
  if (!FFN) {
    uint32_t* m = (uint32_t*)(smem + (sM - sA)) + (tid >> 3) * 16 + (tid & 3) * 4 + ((tid >> 2) & 1);
    m[0] = pack_rn(msc.x, msc.y); m[2] = pack_rn(msh.x, msh.y);
    asm volatile("bar.sync 1,256;" ::: "memory");
  }
  constexpr int NA = FFN ? 88 : 96;
  float acc0[NA], acc1[FFN ? 88 : 1];
  uint32_t a[2][KS][4];
  auto prep = [&](int ks, uint32_t(&o)[4]) {
    if ((ks & 3) == 0) mbar_wait(bA + 2 * ks, 0);
    if (FFN) { ldsm4(aaddr(ks), o); return; }
    uint32_t r[4]; ldsm4(aaddr(ks), r);
    const uint4 m = *(const uint4*)(smem + (sM - sA) + ks * 64 + t * 16);
#pragma unroll
    for (int i = 0; i < 4; i++) {
      const float rs = (i & 1) ? rs1 : rs0, nm = (i & 1) ? nm1 : nm0;
      const uint32_t n = pack_rn(fmaf(blo(r[i]), rs, nm), fmaf(bhi(r[i]), rs, nm));
      asm("fma.rn.bf16x2 %0,%1,%2,%3;" : "=r"(o[i]) : "r"(n), "r"(i < 2 ? m.x : m.y), "r"(i < 2 ? m.z : m.w));
    }
  };
  auto stage = [&](int s, uint32_t(&c)[KS][4], uint32_t(&n)[KS][4]) {
    mbar_wait(bF + (s % NB) * 8, (s / NB) & 1);
    const uint64_t db = mk_desc(sB + (s % NB) * 24576, BOX, 1024, 1);
    wg_fence();
#pragma unroll
    for (int k = 0; k < KS; k++) {
      if constexpr (FFN) {
        wgmma_rs_n176_t1(acc0, c[k][0], c[k][1], c[k][2], c[k][3], db + k * 128, s + k);
        wgmma_rs_n176_t1(acc1, c[k][0], c[k][1], c[k][2], c[k][3], db + k * 128 + 3 * BOX / 16, s + k);
      } else {
        wgmma_rs_n192_t1(acc0, c[k][0], c[k][1], c[k][2], c[k][3], db + k * 128, s + k);
      }
    }
    wg_commit();
    wg_wait<1>();
    if (s > 0 && s <= NST - NB) {
      if (!FFN) { if (lane == 0) mbar_arrive(bE + ((s - 1) % NB) * 8); }
      else if (lane < 2) asm volatile("{\n.reg .b32 r;\nmapa.shared::cluster.u32 r,%0,%1;\nmbarrier.arrive.relaxed.cluster.shared::cluster.b64 _,[r];\n}" ::"r"(bE + ((s - 1) % NB) * 8), "r"(lane) : "memory");
    }
    if (s < NST - 1) {
#pragma unroll
      for (int k = 0; k < KS; k++) prep((s + 1) * KS + k, n[k]);
    }
  };
#pragma unroll
  for (int k = 0; k < KS; k++) prep(k, a[0][k]);
  TS(FFN ? 4 : 1, 2);
#pragma unroll 1
  for (int s = 0; s < NST; s += 2) { stage(s, a[0], a[1]); stage(s + 1, a[1], a[0]); }
  if (FFN) {
    if (tid < 88) { uv.x *= 0.5f; uv.y *= 0.5f; uv.z *= 0.5f; uv.w *= 0.5f; }
    if (tid < 176) *(float4*)(smem + (sM - sA) + tid * 16) = uv;
    const float m0 = qsum(p0.x + p0.z) * 0.125f, m1 = qsum(p1.x + p1.z) * 0.125f;
    const float v0 = qsum(p0.y + p0.w + 64.f * ((p0.x - m0) * (p0.x - m0) + (p0.z - m0) * (p0.z - m0)));
    const float v1 = qsum(p1.y + p1.w + 64.f * ((p1.x - m1) * (p1.x - m1) + (p1.z - m1) * (p1.z - m1)));
    rs0 = rsqrtf(v0 * (1.f / 512) + 1e-5f); rs1 = rsqrtf(v1 * (1.f / 512) + 1e-5f);
    nm0 = -m0 * rs0; nm1 = -m1 * rs1;
    asm volatile("bar.sync 1,256;" ::: "memory");
  }
  wg_wait<0>();
  reg_fence(acc0);
  TS(FFN ? 4 : 1, 3);
  if constexpr (FFN) {
    reg_fence(acc1);
    const float rh0 = 0.5f * rs0, rh1 = 0.5f * rs1;
    uint32_t* o = (uint32_t*)g_h + ((rb * 172 + ct * 22) * 128 + warp * 16 + g) * 4 + t;
#pragma unroll
    for (int j = 0; j < 22; j++) {
      {
        const float4 u1 = *(const float4*)(smem + (sM - sA) + (j * 4 + t) * 16), u3 = *(const float4*)(smem + (sM - sA) + (88 + j * 4 + t) * 16);
        float h[4];
#pragma unroll
        for (int i = 0; i < 4; i++) {
          const float rs = i < 2 ? rs0 : rs1, nm = i < 2 ? nm0 : nm1, rh = i < 2 ? rh0 : rh1;
          const float z = fmaf(rh, acc0[4 * j + i], (i & 1) ? fmaf(nm, u1.z, u1.w) : fmaf(nm, u1.x, u1.y));
          const float y = fmaf(rs, acc1[4 * j + i], (i & 1) ? fmaf(nm, u3.z, u3.w) : fmaf(nm, u3.x, u3.y));
          float th; asm("tanh.approx.f32 %0,%1;" : "=f"(th) : "f"(z));
          h[i] = fmaf(z, th, z) * y;
        }
        if (j < 18 || ct < 7) { o[j * 512] = pack_rn(h[0], h[1]); o[j * 512 + 32] = pack_rn(h[2], h[3]); }
      }
    }
  } else {
    uint32_t* o = (uint32_t*)g_qkv + (ct * 24 * 2048 + row0) * 4 + t;
#pragma unroll
    for (int j = 0; j < 24; j += 2) {
      const int G = ct * 24 + j;
      const float sc = G < 64 ? 0.25f * 1.4426950408889634f : 1.f;
      uint32_t p[4];
#pragma unroll
      for (int i = 0; i < 4; i++) p[i] = pack_rn(acc0[4 * j + 2 * i] * sc, acc0[4 * j + 2 * i + 1] * sc);
      o[j * 8192] = p[0]; o[j * 8192 + 32] = p[1]; o[(j + 1) * 8192] = p[2]; o[(j + 1) * 8192 + 32] = p[3];
      if (G >= 64 && G < 128) {
        float n0 = blo(p[0]) * blo(p[0]) + bhi(p[0]) * bhi(p[0]) + blo(p[2]) * blo(p[2]) + bhi(p[2]) * bhi(p[2]);
        float n1 = blo(p[1]) * blo(p[1]) + bhi(p[1]) * bhi(p[1]) + blo(p[3]) * blo(p[3]) + bhi(p[3]) * bhi(p[3]);
        n0 = qsum(n0); n1 = qsum(n1);
        const uint32_t mx = __reduce_max_sync(~0u, max(__float_as_uint(n0), __float_as_uint(n1)));
        if (lane == 0) g_kmax[((G - 64) >> 1) * 128 + rb * 8 + warp] = __uint_as_float(mx);
      }
    }
  }
  TS(FFN ? 4 : 1, 4);
}
}

#define SMASK 0xCCCCu
#define BRK 0
#define PACK 1
constexpr int AT_SMEM = 5 * 32768 + 256;
__device__ __forceinline__ uint32_t exp2_pair_fma(float s0, float s1, float c, uint32_t ka, uint32_t kz) {
  uint32_t r;
  asm volatile("{\n.reg .b32 y0,y1,e,u,t;\n"
      "fma.rn.sat.f32 y0,%1,0f00000080,%3;\nfma.rn.sat.f32 y1,%2,0f00000080,%3;\n"
      "mad.lo.u32 e,y1,65536,y0;\n"
      "and.b32 u,e,0x007F007F;\n"
      "fma.rn.f16x2 u,u,%4,%5;\nfma.rn.f16x2 t,u,u,%6;\nfma.rn.f16x2 t,t,u,%7;\n"
      "lop3.b32 %0,t,0x007F007F,e,0xE2;\n}\n"
      : "=r"(r) : "f"(s0), "f"(s1), "f"(c), "r"(ka), "r"(0x36B236B2u), "r"(0x3C733C73u), "r"(0x47764776u), "r"(kz));
  return r;
}
__device__ __forceinline__ void attn_pass(float (&oa)[12], float (&ob)[12], const uint32_t (&q)[4], float m0, float m1, uint32_t sK, uint32_t bars, bool first, uint32_t kz) {
  uint64_t dk = mk_desc(sK, 32768, 128, 0), dv = mk_desc(sK + 65536, 128, 32768, 0);
  const float c0 = (127.f - m0) * __uint_as_float(0x80u), c1 = (127.f - m1) * __uint_as_float(0x80u);
  uint32_t ka;
  asm volatile("mov.b32 %0,0x7ACE7ACE;" : "=r"(ka));
  constexpr int NK = 64, NS = 32, NP = 16;
  auto qk = [&](float (&s)[NS], int i) { wgmma_rs_n64_t0(s, q[0], q[1], q[2], q[3], dk + i * NK, 0); };
  auto softmax = [&](float (&s)[NS], uint32_t (&p)[NP], uint32_t mask) {
    reg_fence(s);
    float e0, e1;
    int pend = -1;
#pragma unroll
    for (int t = 0; t < NP; t++) {
      const int j = (t & 3) * 4 + (t >> 2);
      if ((mask >> (t & 3)) & 1) {
        p[j] = exp2_pair_fma(s[2 * j], s[2 * j + 1], (j & 1) ? c1 : c0, ka, kz);
      } else {
        float f0, f1;
        asm volatile("ex2.approx.ftz.f32 %0,%2;\nex2.approx.ftz.f32 %1,%3;" : "=&f"(f0), "=f"(f1) : "f"(s[2 * j]), "f"(s[2 * j + 1]));
        if (pend >= 0) asm volatile("cvt.rn.bf16x2.f32 %0,%1,%2;" : "=r"(p[pend]) : "f"(e1), "f"(e0));
        e0 = f0; e1 = f1; pend = j;
      }
    }
    if (pend >= 0) asm volatile("cvt.rn.bf16x2.f32 %0,%1,%2;" : "=r"(p[pend]) : "f"(e1), "f"(e0));
#pragma unroll
    for (int j = 0; j < NP; j++) asm volatile("" : "+r"(p[j])::"memory");
  };
  auto pv = [&](uint32_t (&p)[NP], int i, uint32_t mask) {
#pragma unroll
    for (int k = 0; k < 4; k++) wgmma_rs_n24_t1(((mask >> k) & 1) ? ob : oa, p[4 * k], p[4 * k + 1], p[4 * k + 2], p[4 * k + 3], dv + i * NK + k * 16, 1);
  };
  constexpr uint32_t M0 = SMASK & 15, M1 = (SMASK >> 4) & 15, M2 = (SMASK >> 8) & 15, M3 = SMASK >> 12;
  zero(oa); zero(ob);
  mbar_wait(bars, 0);
  if (first) TS(2, 2);
  float s[NS];
  zero(s);
  uint32_t p0[NP], p1[NP];
  auto step = [&](int i, uint32_t (&pa)[NP], uint32_t ma, uint32_t (&pb)[NP], uint32_t mb) {
    wg_fence(); qk(s, i + 1); wg_commit(); pv(pa, i, ma); wg_commit(); wg_wait<1>(); softmax(s, pb, mb); wg_wait<0>();
  };
  wg_fence(); qk(s, 0); wg_commit(); wg_wait<0>(); softmax(s, p0, M0);
#pragma unroll 1
  for (uint32_t b = bars + 8; b < bars + 64; b += 8) {
    step(0, p0, M0, p1, M1); step(1, p1, M1, p0, M2); step(2, p0, M2, p1, M3);
    mbar_wait(b, 0);
    step(3, p1, M3, p0, M0);
    dk += 4 * NK; dv += 4 * NK;
  }
  step(0, p0, M0, p1, M1); step(1, p1, M1, p0, M2); step(2, p0, M2, p1, M3);
  wg_fence(); pv(p1, 3, M3); wg_commit();
  wg_wait<0>();
  reg_fence(oa); reg_fence(ob);
}
__device__ __forceinline__ void mma16816(float (&d)[4], const uint32_t (&a)[4], uint32_t b0, uint32_t b1) {
  asm("mma.sync.aligned.m16n8k16.row.col.f32.bf16.bf16.f32 {%0,%1,%2,%3},{%4,%5,%6,%7},{%8,%9},{%0,%1,%2,%3};"
      : "+f"(d[0]), "+f"(d[1]), "+f"(d[2]), "+f"(d[3]) : "r"(a[0]), "r"(a[1]), "r"(a[2]), "r"(a[3]), "r"(b0), "r"(b1));
}
__device__ __forceinline__ void attn_safe(float (&o)[12], const uint32_t (&q)[4], uint32_t sK) {
  const int lane = threadIdx.x & 31;
  const uint32_t ka = sK + (lane >> 4) * 32768 + (lane & 15) * 16;
  float m0 = -INFINITY, m1 = -INFINITY;
#pragma unroll 2
  for (int i = 0; i < 128; i++) {
    uint32_t k[4]; ldsm4(ka + i * 256, k);
    float s0[4] = {0, 0, 0, 0}, s1[4] = {0, 0, 0, 0};
    mma16816(s0, q, k[0], k[2]); mma16816(s1, q, k[1], k[3]);
    m0 = fmaxf(fmaxf(m0, fmaxf(s0[0], s0[1])), fmaxf(s1[0], s1[1])); m1 = fmaxf(fmaxf(m1, fmaxf(s0[2], s0[3])), fmaxf(s1[2], s1[3]));
  }
  m0 = fmaxf(m0, __shfl_xor_sync(~0u, m0, 1)); m0 = fmaxf(m0, __shfl_xor_sync(~0u, m0, 2));
  m1 = fmaxf(m1, __shfl_xor_sync(~0u, m1, 1)); m1 = fmaxf(m1, __shfl_xor_sync(~0u, m1, 2));
  float o0[4] = {0, 0, 0, 0}, o1[4] = {0, 0, 0, 0}, o2[4] = {0, 0, 0, 0};
#pragma unroll 2
  for (int i = 0; i < 128; i++) {
    uint32_t k[4], v[4]; ldsm4(ka + i * 256, k);
    asm volatile("ldmatrix.sync.aligned.m8n8.x4.trans.shared.b16 {%0,%1,%2,%3},[%4];" : "=r"(v[0]), "=r"(v[1]), "=r"(v[2]), "=r"(v[3]) : "r"(ka + 65536 + i * 256) : "memory");
    float s0[4] = {0, 0, 0, 0}, s1[4] = {0, 0, 0, 0};
    mma16816(s0, q, k[0], k[2]); mma16816(s1, q, k[1], k[3]);
    const uint32_t p[4] = {pack_rn(ex2(s0[0] - m0), ex2(s0[1] - m0)), pack_rn(ex2(s0[2] - m1), ex2(s0[3] - m1)),
                           pack_rn(ex2(s1[0] - m0), ex2(s1[1] - m0)), pack_rn(ex2(s1[2] - m1), ex2(s1[3] - m1))};
    mma16816(o0, p, v[0], v[1]); mma16816(o1, p, v[2], v[3]); mma16816(o2, p, 0x3F803F80u, 0x3F803F80u);
  }
#pragma unroll
  for (int i = 0; i < 4; i++) { o[i] = o0[i]; o[4 + i] = o1[i]; o[8 + i] = o2[i]; }
}
__global__ void __cluster_dims__(2, 1, 1) __launch_bounds__(512, 1) k_attn(const bf16* wo, const bf16* w1, const bf16* w3, const bf16* w2, const bf16* __restrict__ cv, const bf16* __restrict__ wm, uint32_t kz) {
  extern __shared__ __align__(1024) uint8_t smem[];
  const uint32_t sK = smem_u32(smem), bars = sK + 5 * 32768;
  const int tid = threadIdx.x, warp = tid >> 5, lane = tid & 31, g = lane >> 2, t = lane & 3;
  pdl_launch();
  if (blockIdx.x < 4) {
    float* cs = (float*)smem;
    cs[tid] = silu_bf(cv[tid]);
    cluster_sync();
    const int b = blockIdx.x;
    float *mv = cs + 512, *rd = cs + 1536;
    auto put8 = [&](float* d, float (&a)[8]) { ((float4*)d)[0] = make_float4(a[0], a[1], a[2], a[3]); ((float4*)d)[1] = make_float4(a[4], a[5], a[6], a[7]); };
    for (int ph = 0; ph < 2; ph++) {
      const int nc = 512 >> ph, n0 = ph ? (b >> 1) * 1536 + 1024 + (b & 1) * 256 : 1536 + (b & 1) * 512, nr = 64 >> ph, r0 = tid / nr * nr;
      float a[8] = {0, 0, 0, 0, 0, 0, 0, 0};
#pragma unroll 16
      for (int r = r0; r < r0 + nr; r++) fma8(a, cs[r], __ldg((const uint4*)(wm + r * 3072 + n0 + (tid & (nr - 1)) * 8)));
      put8(rd + tid * 8, a);
      __syncthreads();
      if (tid < nc) {
        float s = 0;
        for (int i = tid; i < 4096; i += nc) s += rd[i];
        s = mod_fin(s, n0 + tid);
        if (ph || b < 2) g_mod[n0 + tid] = s;
        if (!ph) {
          mv[(b & 1) * 512 + tid] = s;
          asm volatile("{\n.reg .b32 r;\nmapa.shared::cluster.u32 r,%0,%1;\nst.shared::cluster.f32 [r],%2;\n}" ::"r"(smem_u32(mv + (b & 1) * 512 + tid)), "r"((b & 1) ^ 1), "f"(s) : "memory");
        }
      }
      cluster_sync();
    }
    if (tid < 430) {
      const bf16* w = (b >> 1 ? w3 : w1) + (b & 1) * 688 + tid % 86 * 8;
      float u[8] = {0, 0, 0, 0, 0, 0, 0, 0}, v[8] = {0, 0, 0, 0, 0, 0, 0, 0};
#pragma unroll 13
      for (int r = tid / 86; r < 512; r += 5) { const uint4 x = __ldg((const uint4*)(w + r * 1376)); fma8(u, mv[512 + r], x); fma8(v, mv[r], x); }
      put8(rd + tid * 8, u); put8(rd + 3440 + tid * 8, v);
    }
    __syncthreads();
    for (int n = tid; n < 688; n += 512) {
      float u = 0, v = 0;
      for (int i = n; i < 3440; i += 688) { u += rd[i]; v += rd[3440 + i]; }
      g_uv[(b >> 1) * 1408 + (b & 1) * 688 + n] = make_float2(u, v);
    }
    TS(0, 7);
    return;
  }
  const int bid = blockIdx.x - 4, h = bid >> 2, qb = bid & 3;
  TS(2, 0);
  if (tid == 0) { for (int i = 0; i < 8; i++) { mbar_init(bars + 8 * i, 1); mbar_expect(bars + 8 * i, 16384); } fence_init(); }
#pragma unroll
  for (int i = 0; i < 4; i++) *(uint4*)(smem + 131072 + i * 8192 + tid * 16) = make_uint4(0x3F803F80u, 0x3F803F80u, 0x3F803F80u, 0x3F803F80u);
  fence_async();
  cluster_sync();
  pdl_wait();
  TS(2, 1);
  if (tid >= 448) g_modv[bid * 64 + tid - 448] = 0;
  const uint4 km4 = *(const uint4*)(g_kmax + h * 128 + lane * 4);
  const uint32_t* qp = (const uint32_t*)g_qkv + (h * 2 * 2048 + qb * 512 + warp * 16 + g) * 4 + t;
  uint32_t q[4] = {qp[0], qp[32], qp[8192], qp[8192 + 32]};
  auto ldkv = [&]() {
    const int c = warp >> 1, pl = (qb & 1) + (warp & 1) * 2;
    bulk_load_mc(sK + pl * 32768 + c * 4096, g_qkv + ((64 + (pl >> 1) * 64 + h * 2 + (pl & 1)) * 2048 + c * 256) * 8, 4096, bars + 8 * c);
  };
  if (lane == 0 && warp < 4) ldkv();
  const uint32_t qn[4] = {qp[1024], qp[1024 + 32], qp[1024 + 8192], qp[1024 + 8192 + 32]};
  const float kmax = __uint_as_float(__reduce_max_sync(~0u, max(max(km4.x, km4.y), max(km4.z, km4.w))));
  if (lane == 0 && warp >= 4 && kmax != -1.f) ldkv();
#pragma unroll 1
  for (int tile = 0; tile < 2; tile++) {
    const int row = qb * 512 + tile * 256 + warp * 16 + g;
    const float n0 = qsum(blo(q[0]) * blo(q[0]) + bhi(q[0]) * bhi(q[0]) + blo(q[2]) * blo(q[2]) + bhi(q[2]) * bhi(q[2]));
    const float n1 = qsum(blo(q[1]) * blo(q[1]) + bhi(q[1]) * bhi(q[1]) + blo(q[3]) * blo(q[3]) + bhi(q[3]) * bhi(q[3]));
    const float b0 = sqrtf(n0 * kmax) * 1.001f, b1 = sqrtf(n1 * kmax) * 1.001f;
    const float m0 = fmaxf(ceilf(b0 - 100.f), 0.f), m1 = fmaxf(ceilf(b1 - 100.f), 0.f);
    float o[12], ob[12];
    attn_pass(o, ob, q, m0, m1, sK, bars, tile == 0, kz);
    const float f0 = ex2(-m0), f1 = ex2(-m1);
#pragma unroll
    for (int i = 0; i < 12; i++) o[i] = fmaf(o[i], (i & 2) ? f1 : f0, ob[i]);
    bool ok = b0 < 220.f && b1 < 220.f && o[8] >= 0x1p-90f && o[10] >= 0x1p-90f;
#pragma unroll
    for (int i = 0; i < 12; i++) ok = ok && fabsf(o[i]) < INFINITY;
    if (!__all_sync(~0u, ok)) attn_safe(o, q, sK);
    const float r0 = 1.f / o[8], r1 = 1.f / o[10];
    uint32_t* op = (uint32_t*)g_o + (((row >> 6) * 64 + h * 2) * 64 + (row & 63)) * 4 + t;
    op[0] = pack_rn(o[0] * r0, o[1] * r0); op[32] = pack_rn(o[2] * r1, o[3] * r1);
    op[256] = pack_rn(o[4] * r0, o[5] * r0); op[256 + 32] = pack_rn(o[6] * r1, o[7] * r1);
    if (tile == 0 && tid == 32) {
      l2_prefetch((const char*)wo + bid * 4096, 4096);
      l2_prefetch((const char*)w1 + bid * 11008, 11008);
      l2_prefetch((const char*)w3 + bid * 11008, 11008);
      l2_prefetch((const char*)w2 + bid * 11008, 11008);
    }
#pragma unroll
    for (int i = 0; i < 4; i++) q[i] = qn[i];
    TS(2, 3 + tile);
  }
}

constexpr int WO_SMEM = 131072 + 65536 + 256;
__global__ void __cluster_dims__(2, 1, 1) __launch_bounds__(288, 1) k_wo(const __grid_constant__ CUtensorMap mW, const bf16* __restrict__ x) {
  extern __shared__ __align__(1024) uint8_t smem[];
  const uint32_t sA = smem_u32(smem), sB = sA + 65536, bars = sB + 131072;
  const int tid = threadIdx.x, warp = tid >> 5, lane = tid & 31, g = lane >> 2, t = lane & 3;
  const int rb = blockIdx.x >> 3, ct = (blockIdx.x & 3) * 2 + ((warp >> 2) & 1);
  TS(3, 0);
  pdl_launch();
  auto loadB = [&](int i) { for (int j = 0; j < 2; j++) tma2d(sB + (j * 8 + i) * 8192, &mW, (ct + j) * 64, i * 64, bars + 64 + 8 * i); };
  int nb = 0;
  if (tid == 256) {
    for (int i = 0; i < 17; i++) mbar_init(bars + 8 * i, 1);
    fence_init();
    for (int i = 0; i < 16; i++) mbar_expect(bars + 8 * i, i < 8 ? 8192 : 16384);
    for (; nb < PD0; nb++) loadB(nb);
  }
  __syncwarp();
  cluster_arrive();
  if (warp == 8) {
    cluster_wait();
    if (lane == 0) {
      for (; nb < 8 && may_preload(bars + 64 + 8 * (nb - PD0), bars + 128); nb++) loadB(nb);
      pdl_wait();
      for (int i = blockIdx.x & 1; i < 8; i += 2) {
        bulk_load_mc(sA + i * 8192, g_o + ((blockIdx.x >> 2) * 64 + i * 8) * 512, 8192, bars + 8 * i);
        for (; nb <= (i | 1); nb++) loadB(nb);
      }
    }
    __syncwarp();
    return;
  }
  const int lrow = (blockIdx.x & 4) * 16 + (warp & 3) * 16 + g;
  uint32_t xr[16];
  const uint32_t* xp = (const uint32_t*)(x + (rb * 128 + lrow) * 512 + ct * 64) + t;
#pragma unroll
  for (int j = 0; j < 8; j++) { xr[2 * j] = __ldg(xp + j * 4); xr[2 * j + 1] = __ldg(xp + j * 4 + 8 * 256); }
  cluster_wait();
  pdl_wait();
  if (tid == 32) mbar_arrive(bars + 128);
  TS(3, 1);
  float2 ga[8];
  uint32_t sc[8];
#pragma unroll
  for (int j = 0; j < 8; j++) {
    ga[j] = *(const float2*)(g_mod + 1024 + ct * 64 + j * 8 + t * 2);
    const float2 v = *(const float2*)(g_mod + 2048 + ct * 64 + j * 8 + t * 2);
    sc[j] = pack_rn(v.x, v.y);
  }
  float acc[32];
  const uint64_t da = mk_desc(sA, 1024, 128, 0), db = mk_desc(sB + (warp >> 2) * 65536, 8192, 1024, 1);
#pragma unroll
  for (int c = 0; c < 8; c++) {
    mbar_wait(bars + 64 + 8 * c, 0); mbar_wait(bars + 8 * c, 0);
    if (c == 0) TS(3, 2);
    wg_fence();
#pragma unroll
    for (int k = 0; k < 4; k++) wgmma_ss_n64_t1(acc, da + (c * 4 + k) * 128, db + (c * 4 + k) * 128, c + k);
    wg_commit();
  }
  wg_wait<0>();
  reg_fence(acc);
  TS(3, 3);
  uint32_t* o = (uint32_t*)g_x1 + ((rb * 64 + ct * 8) * 128 + lrow) * 4 + t;
  uint32_t* oa = (uint32_t*)g_a + ((rb * 64 + ct * 8) * 128 + lrow) * 4 + t;
  float s0 = 0, s1 = 0;
#pragma unroll
  for (int j = 0; j < 8; j++) {
    xr[2 * j] = pack_rn(fmaf(ga[j].x, acc[4 * j], blo(xr[2 * j])), fmaf(ga[j].y, acc[4 * j + 1], bhi(xr[2 * j])));
    xr[2 * j + 1] = pack_rn(fmaf(ga[j].x, acc[4 * j + 2], blo(xr[2 * j + 1])), fmaf(ga[j].y, acc[4 * j + 3], bhi(xr[2 * j + 1])));
    uint32_t a0, a1;
    asm("mul.rn.bf16x2 %0,%1,%2;" : "=r"(a0) : "r"(xr[2 * j]), "r"(sc[j]));
    asm("mul.rn.bf16x2 %0,%1,%2;" : "=r"(a1) : "r"(xr[2 * j + 1]), "r"(sc[j]));
    oa[j * 512] = a0; oa[j * 512 + 32] = a1;
    o[j * 512] = xr[2 * j]; o[j * 512 + 32] = xr[2 * j + 1];
    s0 += blo(xr[2 * j]) + bhi(xr[2 * j]); s1 += blo(xr[2 * j + 1]) + bhi(xr[2 * j + 1]);
  }
  const float m0 = qsum(s0) * (1.f / 64), m1 = qsum(s1) * (1.f / 64);
  float v0 = 0, v1 = 0;
#pragma unroll
  for (int j = 0; j < 8; j++) {
    float d;
    d = blo(xr[2 * j]) - m0; v0 += d * d; d = bhi(xr[2 * j]) - m0; v0 += d * d;
    d = blo(xr[2 * j + 1]) - m1; v1 += d * d; d = bhi(xr[2 * j + 1]) - m1; v1 += d * d;
  }
  v0 = qsum(v0); v1 = qsum(v1);
  if (t == 0) g_st[(rb * 128 + lrow) * 8 + ct] = make_float2(m0, v0);
  if (t == 1) g_st[(rb * 128 + lrow + 8) * 8 + ct] = make_float2(m1, v1);
  TS(3, 4);
}

constexpr int W2_SMEM = 6 * 32768 + 32768 + 256;
__global__ void __cluster_dims__(2, 1, 1) __launch_bounds__(288, 1) k_w2(const __grid_constant__ CUtensorMap mW, bf16* __restrict__ out) {
  extern __shared__ __align__(1024) uint8_t smem[];
  const uint32_t sR = smem_u32(smem), sX = sR + 6 * 32768, bF = sX + 32768, bE = bF + 48, bX = bF + 96, bB = bF + 160, bG = bF + 208;
  const int tid = threadIdx.x, warp = tid >> 5, lane = tid & 31, g = lane >> 2, t = lane & 3;
  const int kh = blockIdx.x & 1, ct = (blockIdx.x >> 1) & 3, rb = blockIdx.x >> 3;
  TS(5, 0);
  pdl_launch();
  if (tid == 256) {
    for (int i = 0; i < 6; i++) { mbar_init(bF + 8 * i, 1); mbar_init(bE + 8 * i, 8); mbar_init(bB + 8 * i, 1); }
    mbar_init(bG, 1);
    for (int i = 0; i < 8; i++) { mbar_init(bX + 8 * i, 1); mbar_expect(bX + 8 * i, 4096); }
    fence_init();
  }
  __syncthreads();
  asm volatile("barrier.cluster.arrive.relaxed.aligned;" ::: "memory");
  if (warp == 8) {
    if (lane == 0) {
      auto abytes = [&](int s) { return (kh == 1 && s == 10) ? 8192 : 16384; };
      auto loadB = [&](int s) {
        const int st = s % 6;
        mbar_expect(bB + 8 * st, 16384);
        for (int j = 0; j < 2; j++) tma2d(sR + st * 32768 + 16384 + j * 8192, &mW, ct * 128 + (j ^ kh) * 64, kh * 704 + s * 64, bB + 8 * st);
      };
      auto loadA = [&](int s) { mbar_expect(bF + 8 * (s % 6), abytes(s)); bulk_load(sR + (s % 6) * 32768, g_h + (rb * 172 + kh * 88 + s * 8) * 1024, abytes(s), bF + 8 * (s % 6)); };
      int nb = 0;
      for (; nb < 6 && (nb < PD2 || may_preload(bB + 8 * (nb - PD2), bG)); nb++) loadB(nb);
      pdl_wait();
      for (int s = 0; s < 6; s++) { loadA(s); if (s >= nb) loadB(s); }
      for (int s = 6; s < 11; s++) { mbar_wait(bE + 8 * (s - 6), 0); loadB(s); loadA(s); }
    }
    __syncwarp();
    cluster_wait();
    return;
  }
  const int lrow = warp * 16 + g;
  uint32_t xr[16];
  float2 gb[8];
  const uint32_t* xp = (const uint32_t*)g_x1 + ((rb * 64 + ct * 16 + kh * 8) * 128 + lrow) * 4 + t;
#pragma unroll
  for (int j = 0; j < 8; j++) {
    xr[2 * j] = xp[j * 512]; xr[2 * j + 1] = xp[j * 512 + 32];
    gb[j] = *(const float2*)(g_mod + 2560 + ct * 128 + kh * 64 + j * 8 + t * 2);
  }
  pdl_wait();
  if (tid == 32) mbar_arrive(bG);
  TS(5, 1);
  float acc[64];
#pragma unroll 1
  for (int s = 0; s < 11; s++) {
    const int st = s % 6;
    mbar_wait(bB + 8 * st, s >= 6); mbar_wait(bF + 8 * st, s >= 6);
    const uint64_t da = mk_desc(sR + st * 32768 + (warp >> 2) * 1024, 2048, 128, 0), db = mk_desc(sR + st * 32768 + 16384, 8192, 1024, 1);
    if (s == 0) TS(5, 2);
    wg_fence();
    wgmma_ss_n128_t1(acc, da, db, s);
    wgmma_ss_n128_t1(acc, da + 256, db + 128, 1);
    wgmma_ss_n128_t1(acc, da + 512, db + 256, 1);
    wgmma_ss_n128_t1(acc, da + 768, db + 384, 1);
    wg_commit();
    wg_wait<1>();
    if (s > 0 && s < 6 && lane == 0) mbar_arrive(bE + 8 * (s - 1));
  }
  wg_wait<0>();
  reg_fence(acc);
  TS(5, 3);
  asm volatile("barrier.cluster.wait.aligned;" ::: "memory");
  uint32_t rem, rbar;
  asm("mapa.shared::cluster.u32 %0,%1,%2;" : "=r"(rbar) : "r"(bX + warp * 8), "r"(kh ^ 1));
  asm("mapa.shared::cluster.u32 %0,%1,%2;" : "=r"(rem) : "r"(sX + warp * 4096 + lane * 16), "r"(kh ^ 1));
#pragma unroll
  for (int j = 0; j < 8; j++) {
    float v[4];
#pragma unroll
    for (int i = 0; i < 4; i++) v[i] = acc[32 + 4 * j + i];
    asm volatile("st.async.weak.shared::cluster.mbarrier::complete_tx::bytes.v4.f32 [%0],{%1,%2,%3,%4},[%5];" ::"r"(rem + j * 512), "f"(v[0]), "f"(v[1]), "f"(v[2]), "f"(v[3]), "r"(rbar) : "memory");
  }
  mbar_wait(bX + warp * 8, 0);
  TS(5, 5);
  const uint32_t sw = sX + warp * 4096;
#pragma unroll
  for (int j = 0; j < 8; j++) {
    const float4 p = *(const float4*)(smem + 6 * 32768 + warp * 4096 + j * 512 + lane * 16);
    xr[2 * j] = pack_rn(fmaf(gb[j].x, acc[4 * j] + p.x, blo(xr[2 * j])), fmaf(gb[j].y, acc[4 * j + 1] + p.y, bhi(xr[2 * j])));
    xr[2 * j + 1] = pack_rn(fmaf(gb[j].x, acc[4 * j + 2] + p.z, blo(xr[2 * j + 1])), fmaf(gb[j].y, acc[4 * j + 3] + p.w, bhi(xr[2 * j + 1])));
  }
  __syncwarp();
#pragma unroll
  for (int j = 1; j < 8; j += 2) {
    asm volatile("stmatrix.sync.aligned.m8n8.x4.shared.b16 [%0],{%1,%2,%3,%4};" ::"r"(sw + (lane & 15) * 128 + (((j - 1 + (lane >> 4)) ^ (lane & 7)) << 4)),
                            "r"(xr[2 * j - 2]), "r"(xr[2 * j - 1]), "r"(xr[2 * j]), "r"(xr[2 * j + 1]) : "memory");
  }
  __syncwarp();
#pragma unroll
  for (int i = 0; i < 4; i++) {
    const int r = i * 4 + (lane >> 3);
    *(uint4*)(out + (rb * 128 + warp * 16 + r) * 512 + ct * 128 + kh * 64 + (lane & 7) * 8) = *(const uint4*)(smem + 6 * 32768 + warp * 4096 + r * 128 + (((lane ^ r) & 7) << 4));
  }
  TS(5, 4);
}

typedef CUresult (*EncFn)(CUtensorMap*, CUtensorMapDataType, cuuint32_t, void*, const cuuint64_t*, const cuuint64_t*, const cuuint32_t*,
                          const cuuint32_t*, CUtensorMapInterleave, CUtensorMapSwizzle, CUtensorMapL2promotion, CUtensorMapFloatOOBfill);
static void mk_map(EncFn f, CUtensorMap* m, const void* p, int rows, int cols, int box_rows) {
  cuuint64_t dim[2] = {(cuuint64_t)cols, (cuuint64_t)rows}, str[1] = {(cuuint64_t)cols * 2};
  cuuint32_t box[2] = {64, (cuuint32_t)box_rows}, es[2] = {1, 1};
  f(m, CU_TENSOR_MAP_DATA_TYPE_BFLOAT16, 2, (void*)p, dim, str, box, es, CU_TENSOR_MAP_INTERLEAVE_NONE, CU_TENSOR_MAP_SWIZZLE_128B,
    CU_TENSOR_MAP_L2_PROMOTION_L2_128B, CU_TENSOR_MAP_FLOAT_OOB_FILL_NONE);
}
template <typename... KA, typename... A>
static void launch(void (*k)(KA...), int grid, int block, int smem, bool pdl, A... args) {
  cudaLaunchConfig_t cfg = {};
  cfg.gridDim = dim3(grid); cfg.blockDim = dim3(block); cfg.dynamicSmemBytes = smem; cfg.stream = cudaStreamPerThread;
  cudaLaunchAttribute at[1];
  at[0].id = cudaLaunchAttributeProgrammaticStreamSerialization; at[0].val.programmaticStreamSerializationAllowed = 1;
  cfg.attrs = at; cfg.numAttrs = pdl ? 1 : 0;
  cudaLaunchKernelEx(&cfg, k, args...);
}
extern "C" void kernel_launch(void* const* d_in, const int* in_sizes, int n_in, void* d_out, int out_size) {
  const bf16 *x = (const bf16*)d_in[0], *wqkv = (const bf16*)d_in[1], *wo = (const bf16*)d_in[2], *w1 = (const bf16*)d_in[4],
             *w3 = (const bf16*)d_in[5], *w2 = (const bf16*)d_in[6], *c = (const bf16*)d_in[7], *wmod = (const bf16*)d_in[8];
  void* fp = nullptr;
  cudaDriverEntryPointQueryResult qr;
  cudaGetDriverEntryPoint("cuTensorMapEncodeTiled", &fp, cudaEnableDefault, &qr);
  EncFn f = (EncFn)fp;
  CUtensorMap mX, mQ, mO, m1, m3, m2;
  mk_map(f, &mX, x, S_, D_, 128); mk_map(f, &mQ, wqkv, D_, 3 * D_, 64); mk_map(f, &mO, wo, D_, D_, 64);
  mk_map(f, &m1, w1, D_, F_, 32); mk_map(f, &m3, w3, D_, F_, 32); mk_map(f, &m2, w2, F_, D_, 64);
  cudaFuncSetAttribute(k_lngemm<false>, cudaFuncAttributeMaxDynamicSharedMemorySize, LN_SMEM);
  cudaFuncSetAttribute(k_lngemm<true>, cudaFuncAttributeMaxDynamicSharedMemorySize, LN_SMEM);
  cudaFuncSetAttribute(k_attn, cudaFuncAttributeMaxDynamicSharedMemorySize, AT_SMEM);
  cudaFuncSetAttribute(k_wo, cudaFuncAttributeMaxDynamicSharedMemorySize, WO_SMEM);
  cudaFuncSetAttribute(k_w2, cudaFuncAttributeMaxDynamicSharedMemorySize, W2_SMEM);
  launch(k_lngemm<false>, 128, 384, LN_SMEM, false, mX, mQ, mQ, c, wmod, x, wqkv);
  launch(k_attn, 132, 512, AT_SMEM, true, wo, w1, w3, w2, c, wmod, 0u);
  launch(k_wo, 128, 288, WO_SMEM, true, mO, x);
  launch(k_lngemm<true>, 128, 384, LN_SMEM, true, mX, m1, m3, c, wmod, x, wqkv);
  launch(k_w2, 128, 288, W2_SMEM, true, m2, (bf16*)d_out);
}
```
